```python
import torch

def _softmax(x, axis=-1):
    return torch.softmax(x, dim=axis)
def _gelu(x):
    return torch.nn.functional.gelu(x, approximate="tanh")
def _silu(x):
    return torch.nn.functional.silu(x)
def _sigmoid(x):
    return torch.sigmoid(x)
def _layernorm(x, axis=-1, eps=1e-5):
    m = x.mean(dim=axis, keepdim=True)
    v = x.var(dim=axis, keepdim=True, unbiased=False)
    return (x - m) / torch.sqrt(v + eps)
def _scatter_add(tgt, idx, src, axis=0):
    return tgt.clone().index_add_(axis, idx, src)
def _segment_sum(src, seg, n):
    out = torch.zeros((n,) + src.shape[1:], dtype=src.dtype)
    return out.index_add_(0, seg, src)
def _pad(x, pw):
    flat = tuple(v for pair in reversed(pw) for v in pair)
    return torch.nn.functional.pad(x, flat)

kernel_name = 'recurrent_scan__sliding_local_dilated__moe_arch_mod__prompt'

def setup_inputs():

    _w = (lambda a: (lambda t: t.to(torch.bfloat16) if t.is_floating_point() else t)(torch.as_tensor(a)))
    def _A_setup():
        B, S, D = 1, 2048, 640
        return {
            "x": _w((lambda *s: torch.randn(*s, dtype=torch.bfloat16) * 0.05)(B, S, D)),
            "wqkv": _w((lambda *s: torch.randn(*s, dtype=torch.bfloat16) * 0.05)(D, 3 * D)),
            "wo": _w((lambda *s: torch.randn(*s, dtype=torch.bfloat16) * 0.05)(D, D)),
        }
    _A_in = _A_setup()

    def _B_setup():
        B, S, D, F, C = 1, 2048, 640, 1728, 2
        return {
            "x": _w((lambda *s: torch.randn(*s, dtype=torch.bfloat16) * 0.05)(B, S, D)),
            "w_r": _w((lambda *s: torch.randn(*s, dtype=torch.bfloat16) * 0.05)(D)),
            "w_gate": _w((lambda *s: torch.randn(*s, dtype=torch.bfloat16) * 0.05)(D, F)),
            "w_up": _w((lambda *s: torch.randn(*s, dtype=torch.bfloat16) * 0.05)(D, F)),
            "w_down": _w((lambda *s: torch.randn(*s, dtype=torch.bfloat16) * 0.05)(F, D)),
        }
    _B_in = _B_setup()

    return {
        "A_x": _A_in["x"],
        "A_wqkv": _A_in["wqkv"],
        "A_wo": _A_in["wo"],
        "B_x": _B_in["x"],
        "B_w_r": _B_in["w_r"],
        "B_w_gate": _B_in["w_gate"],
        "B_w_up": _B_in["w_up"],
        "B_w_down": _B_in["w_down"],
    }

def reference(A_x, A_wqkv, A_wo, B_x, B_w_r, B_w_gate, B_w_up, B_w_down):
    def _A_ref(x, wqkv, wo):
        B, S, D = x.shape
        H = 32; Dh = D // H
        W, dil = 8, 2
        qkv = (lambda x, *d: x.permute(*d))((x @ wqkv).reshape(B, S, 3, H, Dh), 2, 0, 3, 1, 4)
        q, k, v = qkv[0], qkv[1], qkv[2]
        scale = Dh ** -0.5
        pos = torch.arange(S)
        off = torch.arange(W) * dil
        idx = pos[:, None] - off[None, :]
        mask = idx >= 0
        idx_c = torch.where(mask, idx, 0).reshape(-1)
        kg = k[:, :, idx_c, :].reshape(B, H, S, W, Dh)
        vg = v[:, :, idx_c, :].reshape(B, H, S, W, Dh)
        logits = torch.einsum("bhsd,bhswd->bhsw", q, kg) * scale
        logits = torch.where(mask[None, None, :, :], logits, -1e9)
        attn = _softmax(logits, axis=-1)
        o = torch.einsum("bhsw,bhswd->bhsd", attn, vg)
        return (lambda x, *d: x.permute(*d))(o, 0, 2, 1, 3).reshape(B, S, D) @ wo

    def _B_ref(x, w_r, w_gate, w_up, w_down):
        B, S, D = x.shape
        C = 2
        r = x @ w_r
        idx = torch.argsort(-r, axis=-1)[:, :C]
        idx_e = (lambda x, n, axis: torch.repeat_interleave(x, n, dim=axis))(idx.reshape(B, C, 1), D, axis=2)
        x_sel = (lambda x, i, axis: torch.take_along_dim(x, i, dim=axis))(x, idx_e, axis=1)
        g = _silu(x_sel @ w_gate)
        u = x_sel @ w_up
        y = (g * u) @ w_down
        r_sel = _sigmoid((lambda x, i, axis: torch.take_along_dim(x, i, dim=axis))(r, idx, axis=1))
        y = y * r_sel.reshape(B, C, 1)
        b_off = (torch.arange(B) * S).reshape(B, 1)
        flat_idx = (idx + b_off).reshape(B * C)
        zero = (x * 0.0).reshape(B * S, D)
        upd = _scatter_add(zero, flat_idx, y.reshape(B * C, D), axis=0)
        return x + upd.reshape(B, S, D)

    x = A_x
    xn = _layernorm(x, axis=-1)
    s = _A_ref(xn, A_wqkv, A_wo)
    g = _silu(_B_ref(xn, B_w_r, B_w_gate, B_w_up, B_w_down))
    return x + s * g
```

```cpp
#include <cuda_runtime.h>
#include <cuda_bf16.h>
#include <cuda.h>
#include <stdint.h>

namespace {

typedef __nv_bfloat16 bf16;

constexpr int SEQ = 2048, DM = 640;
constexpr int NTHREADS = 512;
constexpr int NFFN = 108;
#define GU0 6000
#define GU1 220
#define GU2 600
#define NPC 10
#define GT0 1000
#define GT1 480
#define PFM0 2
#define ODDX 0
#define WOP 150
#define EX1T 8400
#define EX2T 10500
#define HALOC 4
#define FFNLATE 0
#define GUU 4
#define NPF 12
#define ORD 2
#define ZSKIP 0
#define ZSTART 900
#define T2SLEEP 30
#define PACE0 -200
#define PACE1 1000
#define CSKB 10
#define NCS 10
#define CSI(j) ((j) < 4 ? (j) : (j) == 4 ? 12 : (j) < 13 ? (j) - 1 : (j))
#define POLLMODE 0
#define SERAT 2
#define YSLEEP 300
#define PF0 0
#define PSLEEP 100
#define ZSLEEP 100
#define RSLEEP 100
#define W0SLEEP 250
#define LEAD 3

constexpr int ST = 47104;
constexpr int ST_BM = 16384, ST_BR = 40960;
constexpr int OFF_X = 0;
constexpr int OFF_G = 20480;
constexpr int OFF_PART = 40960;
constexpr int OFF_DN = 43008;
constexpr int OFF_WO = 63488;
constexpr int WO_SLOT = 15360;
constexpr int OFF_GU = 4 * ST;
constexpr int M_ST = OFF_GU + 40960;
constexpr int M_CS = M_ST + 1024;
constexpr int M_UPD = M_CS + 1024;
constexpr int M_TOP = M_UPD + 640;
constexpr int M_SEL = M_TOP + 64;
constexpr int B_Z = M_SEL + 16, B_G = B_Z + 8, B_AX = B_Z + 32, B_PREP = B_AX + 40, B_GU = B_AX + 64, B_X = B_GU + 8, B_H = B_X + 8,
              B_UPD = B_H + 8, B_FULL = B_GU + 32, B_EMPTY = B_FULL + 32, B_HO = B_EMPTY + 32, B_WO = B_HO + 32;
constexpr int SMEM_BYTES = B_WO + 32;
static_assert(SMEM_BYTES <= 232448 && OFF_WO + 2 * WO_SLOT <= 2 * ST && OFF_WO + 5 * WO_SLOT <= 3 * ST && OFF_WO + 8 * WO_SLOT <= 4 * ST, "smem");

enum { T_X, T_W, T_WR, T_GU, T_XT, T_D, T_WO, T_WOR, T_OUT, T_N };
struct Params {
    CUtensorMap tm[T_N];
    const uint8_t* x;
    const uint8_t* w_r;
    const uint8_t* pf[4];
    uint8_t* scr;
    uint32_t up_first;
    int by_sm;
    uint16_t map[66];
};

constexpr uint32_t XB = 32512;
constexpr uint32_t G_Y = 25600;
constexpr uint32_t G_TOP = G_Y + 5120;
constexpr uint32_t G_CS = G_TOP + 1024;
constexpr uint32_t G_ST = G_CS + 128;
constexpr uint32_t G_FLAG = G_ST + 512;
constexpr uint32_t G_EPOCH = 128 * XB;
static_assert(G_FLAG + 128 == XB, "scratch");
__device__ __align__(1024) uint8_t g_scr[G_EPOCH + 1024];

#define TSINIT
#define TR(v)
#define TRD(v)
#define TRW(v, i)
#define TS(i)
#define TSG(i)
constexpr unsigned SPIN = 1u << 20;

__device__ __forceinline__ void mbar_init(uint32_t bar, int cnt) {
    asm volatile("mbarrier.init.shared::cta.b64 [%0], %1;" :: "r"(bar), "r"(cnt) : "memory");
}
__device__ __forceinline__ void mbar_expect_tx(uint32_t bar, int bytes) {
    asm volatile("mbarrier.arrive.expect_tx.shared::cta.b64 _, [%0], %1;" :: "r"(bar), "r"(bytes) : "memory");
}
__device__ __forceinline__ void mbar_arrive(uint32_t bar) {
    asm volatile("mbarrier.arrive.shared::cta.b64 _, [%0];" :: "r"(bar) : "memory");
}
__device__ __forceinline__ uint32_t mapa(uint32_t a, uint32_t cta) {
    uint32_t r;
    asm("mapa.shared::cluster.u32 %0, %1, %2;" : "=r"(r) : "r"(a), "r"(cta));
    return r;
}
__device__ __forceinline__ void mbar_arrive_cl(uint32_t cbar) {
    asm volatile("mbarrier.arrive.shared::cluster.b64 _, [%0];" :: "r"(cbar) : "memory");
}
__device__ __forceinline__ void mbar_wait(uint32_t bar, int parity) {
    asm volatile("{\n.reg .pred p;\nLAB_WAIT:\nmbarrier.try_wait.parity.shared::cta.b64 p, [%0], %1;\n@!p bra LAB_WAIT;\n}"
                 :: "r"(bar), "r"(parity) : "memory");
}
__device__ __forceinline__ void tma(uint32_t dst, const CUtensorMap* tm, uint32_t bar, int c0, int c1, int c2 = 0) {
    asm volatile("cp.async.bulk.tensor.3d.shared::cluster.global.mbarrier::complete_tx::bytes [%0], [%1, {%3, %4, %5}], [%2];"
                 :: "r"(dst), "l"(tm), "r"(bar), "r"(c0), "r"(c1), "r"(c2) : "memory");
}
__device__ __forceinline__ void tma_mc(uint32_t dst, const CUtensorMap* tm, uint32_t bar, int c0, int c1) {
    asm volatile("cp.async.bulk.tensor.3d.shared::cluster.global.mbarrier::complete_tx::bytes.multicast::cluster [%0], [%1, {%3, %4, %5}], [%2], %6;"
                 :: "r"(dst), "l"(tm), "r"(bar), "r"(c0), "r"(c1), "r"(0), "h"((uint16_t)3) : "memory");
}
__device__ __forceinline__ void tma_st(const CUtensorMap* tm, uint32_t src, int c0, int c1, int c2) {
    asm volatile("cp.async.bulk.tensor.3d.global.shared::cta.bulk_group [%0, {%2, %3, %4}], [%1];\ncp.async.bulk.commit_group;"
                 :: "l"(tm), "r"(src), "r"(c0), "r"(c1), "r"(c2) : "memory");
}
__device__ __forceinline__ void l2_prefetch(const void* p, int bytes) {
    asm volatile("cp.async.bulk.prefetch.L2.global [%0], %1;" :: "l"(p), "r"(bytes) : "memory");
}
__device__ __forceinline__ void cluster_arrive() { asm volatile("barrier.cluster.arrive.relaxed.aligned;" ::: "memory"); }
__device__ __forceinline__ void cluster_wait() { asm volatile("barrier.cluster.wait.aligned;" ::: "memory"); }
__device__ __forceinline__ void bar_sync(int id, int n) { asm volatile("bar.sync %0, %1;" :: "r"(id), "r"(n) : "memory"); }
__device__ __forceinline__ void bar_arrive(int id, int n) { asm volatile("bar.arrive %0, %1;" :: "r"(id), "r"(n) : "memory"); }
__device__ __forceinline__ bool bar_or(int id, int n, bool v) {
    uint32_t r;
    asm volatile("{\n.reg .pred p, q;\nsetp.ne.u32 p, %3, 0;\nbar.red.or.pred q, %1, %2, p;\nselp.u32 %0, 1, 0, q;\n}"
                 : "=r"(r) : "r"(id), "r"(n), "r"((uint32_t)v) : "memory");
    return r != 0;
}
__device__ __forceinline__ void fence_proxy_async_smem() { asm volatile("fence.proxy.async.shared::cta;" ::: "memory"); }
__device__ __forceinline__ void stg128(void* p, uint32_t a, uint32_t b, uint32_t c, uint32_t d) {
    asm volatile("{\n.reg .b64 l, h;\n.reg .b128 q;\nmov.b64 l, {%1, %2};\nmov.b64 h, {%3, %4};\nmov.b128 q, {l, h};\n"
                 "st.relaxed.gpu.global.b128 [%0], q;\n}" :: "l"(p), "r"(a), "r"(b), "r"(c), "r"(d) : "memory");
}
__device__ __forceinline__ void ldg128(const void* p, uint32_t& a, uint32_t& b, uint32_t& c, uint32_t& d) {
    asm volatile("{\n.reg .b64 l, h;\n.reg .b128 q;\nld.relaxed.gpu.global.b128 q, [%4];\nmov.b128 {l, h}, q;\n"
                 "mov.b64 {%0, %1}, l;\nmov.b64 {%2, %3}, h;\n}" : "=r"(a), "=r"(b), "=r"(c), "=r"(d) : "l"(p) : "memory");
}
__device__ __forceinline__ void stg64(void* p, uint32_t a, uint32_t b) {
    asm volatile("{\n.reg .b64 l;\nmov.b64 l, {%1, %2};\nst.relaxed.gpu.global.b64 [%0], l;\n}" :: "l"(p), "r"(a), "r"(b) : "memory");
}
__device__ __forceinline__ void stg32(void* p, uint32_t a) {
    asm volatile("st.relaxed.gpu.global.u32 [%0], %1;" :: "l"(p), "r"(a) : "memory");
}
__device__ __forceinline__ uint2 ldg64(const void* p) {
    uint2 v;
    asm volatile("{\n.reg .b64 l;\nld.relaxed.gpu.global.b64 l, [%2];\nmov.b64 {%0, %1}, l;\n}" : "=r"(v.x), "=r"(v.y) : "l"(p) : "memory");
    return v;
}
__device__ __forceinline__ unsigned ldg32(const void* p) {
    unsigned v;
    asm volatile("ld.relaxed.gpu.global.u32 %0, [%1];" : "=r"(v) : "l"(p) : "memory");
    return v;
}
__device__ __forceinline__ void ldsm_x4(uint32_t (&r)[4], uint32_t a) {
    asm volatile("ldmatrix.sync.aligned.m8n8.x4.shared.b16 {%0,%1,%2,%3}, [%4];"
                 : "=r"(r[0]), "=r"(r[1]), "=r"(r[2]), "=r"(r[3]) : "r"(a));
}
__device__ __forceinline__ void ldsm_x4_t(uint32_t (&r)[4], uint32_t a) {
    asm volatile("ldmatrix.sync.aligned.m8n8.x4.trans.shared.b16 {%0,%1,%2,%3}, [%4];"
                 : "=r"(r[0]), "=r"(r[1]), "=r"(r[2]), "=r"(r[3]) : "r"(a));
}
__device__ __forceinline__ void stsm_x4(uint32_t a, const uint32_t (&r)[4]) {
    asm volatile("stmatrix.sync.aligned.m8n8.x4.shared.b16 [%0], {%1,%2,%3,%4};"
                 :: "r"(a), "r"(r[0]), "r"(r[1]), "r"(r[2]), "r"(r[3]));
}
__device__ __forceinline__ uint32_t movm(uint32_t a) {
    uint32_t d;
    asm("movmatrix.sync.aligned.m8n8.trans.b16 %0, %1;" : "=r"(d) : "r"(a));
    return d;
}
__device__ __forceinline__ void mma16816(float (&c)[4], uint32_t a0, uint32_t a1, uint32_t a2, uint32_t a3, uint32_t b0, uint32_t b1) {
    asm("mma.sync.aligned.m16n8k16.row.col.f32.bf16.bf16.f32 {%0,%1,%2,%3}, {%4,%5,%6,%7}, {%8,%9}, {%0,%1,%2,%3};"
        : "+f"(c[0]), "+f"(c[1]), "+f"(c[2]), "+f"(c[3]) : "r"(a0), "r"(a1), "r"(a2), "r"(a3), "r"(b0), "r"(b1));
}
__device__ __forceinline__ void mma1688(float (&c)[4], uint32_t a0, uint32_t a1, uint32_t b0) {
    asm("mma.sync.aligned.m16n8k8.row.col.f32.bf16.bf16.f32 {%0,%1,%2,%3}, {%4,%5}, {%6}, {%0,%1,%2,%3};"
        : "+f"(c[0]), "+f"(c[1]), "+f"(c[2]), "+f"(c[3]) : "r"(a0), "r"(a1), "r"(b0));
}
__device__ __forceinline__ void wgmma_fence() { asm volatile("wgmma.fence.sync.aligned;" ::: "memory"); }
__device__ __forceinline__ void wgmma_commit() { asm volatile("wgmma.commit_group.sync.aligned;" ::: "memory"); }
template <int N> __device__ __forceinline__ void wgmma_wait() { asm volatile("wgmma.wait_group.sync.aligned %0;" :: "n"(N) : "memory"); }
__device__ __forceinline__ uint64_t mk(uint32_t lo, uint32_t hi) { return (uint64_t)lo | ((uint64_t)hi << 32); }
constexpr uint32_t HI128 = (1024 >> 4) | (1u << 30), HI64 = (512 >> 4) | (2u << 30), HI32 = (256 >> 4) | (3u << 30);
__device__ __forceinline__ uint32_t pack_bf16(float lo, float hi) {
    uint32_t r;
    asm("cvt.rn.bf16x2.f32 %0, %1, %2;" : "=r"(r) : "f"(hi), "f"(lo));
    return r;
}
__device__ __forceinline__ float bflo(uint32_t u) { return __uint_as_float(u << 16); }
__device__ __forceinline__ float bfhi(uint32_t u) { return __uint_as_float(u & 0xFFFF0000u); }
__device__ __forceinline__ float bf16r(float v) { return __uint_as_float(pack_bf16(0.f, v)); }
__device__ __forceinline__ float ex2(float v) { float r; asm("ex2.approx.ftz.f32 %0, %1;" : "=f"(r) : "f"(v)); return r; }
__device__ __forceinline__ float rcp(float v) { float r; asm("rcp.approx.ftz.f32 %0, %1;" : "=f"(r) : "f"(v)); return r; }
__device__ __forceinline__ float sqrt_a(float v) { float r; asm("sqrt.approx.ftz.f32 %0, %1;" : "=f"(r) : "f"(v)); return r; }
__device__ __forceinline__ float tanh_a(float v) { float r; asm("tanh.approx.f32 %0, %1;" : "=f"(r) : "f"(v)); return r; }
constexpr float LOG2E = 1.4426950408889634f;
__device__ __forceinline__ float sigm(float v) { return rcp(1.0f + ex2(-LOG2E * v)); }
__device__ __forceinline__ uint4 lds128(uint32_t a) {
    uint4 v;
    asm volatile("ld.shared.v4.u32 {%0,%1,%2,%3}, [%4];" : "=r"(v.x), "=r"(v.y), "=r"(v.z), "=r"(v.w) : "r"(a));
    return v;
}
__device__ __forceinline__ float4 lds128f(uint32_t a) {
    float4 v;
    asm volatile("ld.shared.v4.f32 {%0,%1,%2,%3}, [%4];" : "=f"(v.x), "=f"(v.y), "=f"(v.z), "=f"(v.w) : "r"(a));
    return v;
}
__device__ __forceinline__ float2 lds64f(uint32_t a) {
    float2 v;
    asm volatile("ld.shared.v2.f32 {%0,%1}, [%2];" : "=f"(v.x), "=f"(v.y) : "r"(a));
    return v;
}
__device__ __forceinline__ uint32_t lds32(uint32_t a) {
    uint32_t v;
    asm volatile("ld.shared.u32 %0, [%1];" : "=r"(v) : "r"(a));
    return v;
}
__device__ __forceinline__ void sts128(uint32_t a, uint32_t x, uint32_t y, uint32_t z, uint32_t w) {
    asm volatile("st.shared.v4.u32 [%0], {%1,%2,%3,%4};" :: "r"(a), "r"(x), "r"(y), "r"(z), "r"(w) : "memory");
}
__device__ __forceinline__ void sts64(uint32_t a, uint32_t x, uint32_t y) {
    asm volatile("st.shared.v2.u32 [%0], {%1,%2};" :: "r"(a), "r"(x), "r"(y) : "memory");
}
__device__ __forceinline__ void sts32(uint32_t a, uint32_t x) { asm volatile("st.shared.u32 [%0], %1;" :: "r"(a), "r"(x) : "memory"); }
__device__ __forceinline__ unsigned redux_max(unsigned v) {
    unsigned r;
    asm volatile("redux.sync.max.u32 %0, %1, 0xffffffff;" : "=r"(r) : "r"(v));
    return r;
}
__device__ __forceinline__ float shx(float v, int o) { return __shfl_xor_sync(0xffffffffu, v, o); }
__device__ __forceinline__ uint32_t U(float v) { return __float_as_uint(v); }
__device__ __forceinline__ float F(uint32_t v) { return __uint_as_float(v); }

__device__ __forceinline__ void wgmma_n192_lo(float (&d)[120], uint64_t da, uint64_t db, int scale_d) {
    asm volatile("{\n.reg .pred p;\nsetp.ne.b32 p, %98, 0;\n"
        "wgmma.mma_async.sync.aligned.m64n192k16.f32.bf16.bf16 "
        "{%0, %1, %2, %3, %4, %5, %6, %7, %8, %9, %10, %11, %12, %13, %14, %15, "
        "%16, %17, %18, %19, %20, %21, %22, %23, %24, %25, %26, %27, %28, %29, %30, %31, "
        "%32, %33, %34, %35, %36, %37, %38, %39, %40, %41, %42, %43, %44, %45, %46, %47, "
        "%48, %49, %50, %51, %52, %53, %54, %55, %56, %57, %58, %59, %60, %61, %62, %63, "
        "%64, %65, %66, %67, %68, %69, %70, %71, %72, %73, %74, %75, %76, %77, %78, %79, "
        "%80, %81, %82, %83, %84, %85, %86, %87, %88, %89, %90, %91, %92, %93, %94, %95}, "
        "%96, %97, p, 1, 1, 0, 1;\n}\n"
        : "+f"(d[0]), "+f"(d[1]), "+f"(d[2]), "+f"(d[3]), "+f"(d[4]), "+f"(d[5]), "+f"(d[6]), "+f"(d[7]),
          "+f"(d[8]), "+f"(d[9]), "+f"(d[10]), "+f"(d[11]), "+f"(d[12]), "+f"(d[13]), "+f"(d[14]), "+f"(d[15]),
          "+f"(d[16]), "+f"(d[17]), "+f"(d[18]), "+f"(d[19]), "+f"(d[20]), "+f"(d[21]), "+f"(d[22]), "+f"(d[23]),
          "+f"(d[24]), "+f"(d[25]), "+f"(d[26]), "+f"(d[27]), "+f"(d[28]), "+f"(d[29]), "+f"(d[30]), "+f"(d[31]),
          "+f"(d[32]), "+f"(d[33]), "+f"(d[34]), "+f"(d[35]), "+f"(d[36]), "+f"(d[37]), "+f"(d[38]), "+f"(d[39]),
          "+f"(d[40]), "+f"(d[41]), "+f"(d[42]), "+f"(d[43]), "+f"(d[44]), "+f"(d[45]), "+f"(d[46]), "+f"(d[47]),
          "+f"(d[48]), "+f"(d[49]), "+f"(d[50]), "+f"(d[51]), "+f"(d[52]), "+f"(d[53]), "+f"(d[54]), "+f"(d[55]),
          "+f"(d[56]), "+f"(d[57]), "+f"(d[58]), "+f"(d[59]), "+f"(d[60]), "+f"(d[61]), "+f"(d[62]), "+f"(d[63]),
          "+f"(d[64]), "+f"(d[65]), "+f"(d[66]), "+f"(d[67]), "+f"(d[68]), "+f"(d[69]), "+f"(d[70]), "+f"(d[71]),
          "+f"(d[72]), "+f"(d[73]), "+f"(d[74]), "+f"(d[75]), "+f"(d[76]), "+f"(d[77]), "+f"(d[78]), "+f"(d[79]),
          "+f"(d[80]), "+f"(d[81]), "+f"(d[82]), "+f"(d[83]), "+f"(d[84]), "+f"(d[85]), "+f"(d[86]), "+f"(d[87]),
          "+f"(d[88]), "+f"(d[89]), "+f"(d[90]), "+f"(d[91]), "+f"(d[92]), "+f"(d[93]), "+f"(d[94]), "+f"(d[95])
        : "l"(da), "l"(db), "r"(scale_d));
}
__device__ __forceinline__ void wgmma_n48_hi(float (&d)[120], uint64_t da, uint64_t db, int scale_d) {
    asm volatile("{\n.reg .pred p;\nsetp.ne.b32 p, %26, 0;\n"
        "wgmma.mma_async.sync.aligned.m64n48k16.f32.bf16.bf16 "
        "{%0, %1, %2, %3, %4, %5, %6, %7, %8, %9, %10, %11, %12, %13, %14, %15, "
        "%16, %17, %18, %19, %20, %21, %22, %23}, "
        "%24, %25, p, 1, 1, 0, 1;\n}\n"
        : "+f"(d[96]), "+f"(d[97]), "+f"(d[98]), "+f"(d[99]), "+f"(d[100]), "+f"(d[101]), "+f"(d[102]), "+f"(d[103]),
          "+f"(d[104]), "+f"(d[105]), "+f"(d[106]), "+f"(d[107]), "+f"(d[108]), "+f"(d[109]), "+f"(d[110]), "+f"(d[111]),
          "+f"(d[112]), "+f"(d[113]), "+f"(d[114]), "+f"(d[115]), "+f"(d[116]), "+f"(d[117]), "+f"(d[118]), "+f"(d[119])
        : "l"(da), "l"(db), "r"(scale_d));
}
__device__ __forceinline__ void wgmma_rs_n80(float (&d)[40], uint32_t a0, uint32_t a1, uint32_t a2, uint32_t a3, uint64_t db, int scale_d) {
    asm volatile("{\n.reg .pred p;\nsetp.ne.b32 p, %45, 0;\n"
        "wgmma.mma_async.sync.aligned.m64n80k16.f32.bf16.bf16 "
        "{%0, %1, %2, %3, %4, %5, %6, %7, %8, %9, %10, %11, %12, %13, %14, %15, "
        "%16, %17, %18, %19, %20, %21, %22, %23, %24, %25, %26, %27, %28, %29, %30, %31, "
        "%32, %33, %34, %35, %36, %37, %38, %39}, "
        "{%40, %41, %42, %43}, %44, p, 1, 1, 1;\n}\n"
        : "+f"(d[0]), "+f"(d[1]), "+f"(d[2]), "+f"(d[3]), "+f"(d[4]), "+f"(d[5]), "+f"(d[6]), "+f"(d[7]),
          "+f"(d[8]), "+f"(d[9]), "+f"(d[10]), "+f"(d[11]), "+f"(d[12]), "+f"(d[13]), "+f"(d[14]), "+f"(d[15]),
          "+f"(d[16]), "+f"(d[17]), "+f"(d[18]), "+f"(d[19]), "+f"(d[20]), "+f"(d[21]), "+f"(d[22]), "+f"(d[23]),
          "+f"(d[24]), "+f"(d[25]), "+f"(d[26]), "+f"(d[27]), "+f"(d[28]), "+f"(d[29]), "+f"(d[30]), "+f"(d[31]),
          "+f"(d[32]), "+f"(d[33]), "+f"(d[34]), "+f"(d[35]), "+f"(d[36]), "+f"(d[37]), "+f"(d[38]), "+f"(d[39])
        : "r"(a0), "r"(a1), "r"(a2), "r"(a3), "l"(db), "r"(scale_d));
}
__device__ __forceinline__ void wgmma_n8(float (&d)[4], uint64_t da, uint64_t db, int scale_d) {
    asm volatile("{\n.reg .pred p;\nsetp.ne.b32 p, %6, 0;\n"
                 "wgmma.mma_async.sync.aligned.m64n8k16.f32.bf16.bf16 {%0, %1, %2, %3}, %4, %5, p, 1, 1, 1, 0;\n}\n"
                 : "+f"(d[0]), "+f"(d[1]), "+f"(d[2]), "+f"(d[3]) : "l"(da), "l"(db), "r"(scale_d));
}

__device__ __forceinline__ constexpr int jt_of(int sec, int c) { return c < 8 ? sec * 8 + c : 24 + sec * 2 + (c - 8); }

__device__ __forceinline__ bool elect() {
    uint32_t r;
    asm volatile("{\n.reg .pred p;\nelect.sync _|p, 0xffffffff;\nselp.u32 %0, 1, 0, p;\n}" : "=r"(r));
    return r != 0;
}
__device__ __forceinline__ uint32_t clock32() { uint32_t r; asm volatile("mov.u32 %0, %%clock;" : "=r"(r)); return r; }
__device__ __forceinline__ bool any(bool v) { return __any_sync(0xffffffffu, v); }
__device__ __forceinline__ bool retry(unsigned& spins) { __nanosleep(RSLEEP); return ++spins < SPIN; }
__device__ __forceinline__ uint32_t opaque_tid() { uint32_t r; asm volatile("mov.u32 %0, %%tid.x;" : "=r"(r)); return r; }

__global__ void __cluster_dims__(2, 1, 1) __launch_bounds__(NTHREADS, 1)
fused_kernel(const __grid_constant__ Params P) {
    extern __shared__ __align__(1024) uint8_t smem[];
    const uint32_t sb = (uint32_t)__cvta_generic_to_shared(smem);
    const uint32_t warp = __shfl_sync(0xffffffffu, threadIdx.x >> 5, 0);
    const uint32_t rank = blockIdx.x & 1;
    uint32_t me;
    asm("mov.u32 %0, %%smid;" : "=r"(me));
    me = P.map[(P.by_sm ? me : blockIdx.x) >> 1];
    constexpr uint32_t sbd = 1024 >> 4;
    if ((sb & 0xFFFFFF) != 1024) __trap();
    if (me & 0x40) {
        __nanosleep(2000);
        return;
    }
    const uint32_t hg = me & 7, rb = ((me >> 2) & 14) | rank, fp = me >> 8;
    const uint32_t b = rb * 8 + hg;
    const uint32_t k0 = (((hg >> 2) ^ (rb >> 1)) & 1) * 320;

    TSINIT;
    TS(0); TSG(1);
    if (warp >= 8 && elect()) {
        const uint32_t bb = sb + B_Z - 256 + warp * 32;
        const int cnt = ((0x0FF00772u >> (4 * (warp - 8))) & 15) + 1;
        mbar_init(bb, cnt); mbar_init(bb + 8, cnt); mbar_init(bb + 16, cnt); mbar_init(bb + 24, cnt);
        if (warp == 11) { mbar_expect_tx(sb + B_H, 1024); mbar_expect_tx(sb + B_GU, 40960); }
        asm volatile("fence.mbarrier_init.release.cluster;" ::: "memory");
    }
    __syncwarp();
    cluster_arrive();

    if (warp < 8) {
        asm volatile("setmaxnreg.inc.sync.aligned.u32 208;");
        const uint32_t lane = opaque_tid() & 31, g = lane >> 2, t = lane & 3;
        const uint32_t p = warp >> 2, w = warp & 3;
        const uint32_t empty_cl = mapa(sb + B_EMPTY, lane & 1);
        uint8_t* const orow = P.scr + (rb * (8 * XB) + warp * 2560 + lane * 16);
        const uint32_t ta = sb + warp * 2560 + (lane & 15) * 160 + (lane >> 4) * 16;
        uint32_t A[7][20];
        TRD(r12); TRD(r26); TRD(r28); TRD(r32); TRD(r34); TRD(r61); TRD(r20); TRD(r21); TRD(r22); TRD(r42); TRD(r44);
        uint32_t par;
        uint8_t* const halo = orow + (hg * XB + (8 + p - warp) * 2560);
        uint8_t* const flag = P.scr + (G_FLAG + b * XB + warp * 4);
        if (lane == 0) stg32(flag, 0u);
        if (w == 3) {
#pragma unroll 1
            for (uint32_t j = 0; j < 2560; j += 512) stg128(halo + j, 0u, 0u, 0u, 0u);
        }
        cluster_wait();
        {
            float acc[120];
#pragma unroll 1
            for (uint32_t kb = 2; kb < 12; kb++) {
                const uint32_t s = kb & 3;
                const bool hold = kb == 12 - LEAD && p;
                if (hold) {
                    wgmma_wait<0>();
                    if (lane < 2) mbar_arrive_cl(empty_cl + 8 * ((11 - LEAD) & 3));
                    bar_sync(1, 256);
                }
                mbar_wait(sb + B_FULL + 8 * s, ((kb - 2) >> 2) & 1);
                TS(kb);
                wgmma_fence();
                const uint32_t st = sbd + s * (ST >> 4);
#pragma unroll
                for (int ks = 0; ks < 4; ks++) {
                    const uint64_t da = mk(st + p * 512 + ks * 2 + 0x10000, HI128);
                    wgmma_n192_lo(acc, da, mk(st + (ST_BM >> 4) + (ks >> 1) * 768 + (ks & 1) * 128 + (256 << 16), HI128), ks || kb > 2);
                    wgmma_n48_hi(acc, da, mk(st + (ST_BR >> 4) + (ks >> 1) * 192 + (ks & 1) * 32 + (64 << 16), HI32), ks || kb > 2);
                    if (ks == 0) {
                        wgmma_commit();
                        wgmma_wait<1>();
                        if (!hold)
                        if (kb > 2 && lane < 2) mbar_arrive_cl(empty_cl + 8 * ((kb - 1) & 3));
                    }
                }
                wgmma_commit();
            }
            if (!p) bar_arrive(1, 256);
            mbar_wait(sb + B_PREP, 0);
            const float2 s0 = lds64f(sb + M_ST + (warp * 16 + g) * 8), s1 = lds64f(sb + M_ST + (warp * 16 + g + 8) * 8);
            par = lds32(sb + M_SEL + 8);
            float4 cs[15];
#pragma unroll
            for (int j = 14; j >= 5; j--) cs[CSI(j)] = lds128f(sb + M_CS + t * 16 + CSI(j) * 64);
            wgmma_wait<0>();
#pragma unroll
            for (int i = 0; i < 120; i++) asm volatile("" : "+f"(acc[i]) :: "memory");
            if (lane < 2) mbar_arrive_cl(empty_cl + 24);
            TR(r12);
            uint32_t Q[10], Ql[10], KX[10], VX[10], Y[20];
#define KI(c) ((c) == 2 ? 8 : (c) == 7 ? 9 : (c) - ((c) > 2) - ((c) > 7))
#define KY(c) Y[KI(c)]
#define VY(c) Y[10 + (c)]
            uint32_t Z[20];
            const bool start = w == 0 && rb == 0, remote = w == 0 && rb != 0;
            const uint32_t slot = sb + OFF_WO + (warp - p - 1) * 2560 + lane * 16;
            {
                const float n0 = -s0.x * s0.y, n1 = -s1.x * s1.y;
#define CS0(j) ((j) & 1 ? cs[(j) >> 1].z : cs[(j) >> 1].x)
#define CS1(j) ((j) & 1 ? cs[(j) >> 1].w : cs[(j) >> 1].y)
#pragma unroll
                for (int c = 0; c < 10; c++) {
                    const int jk = jt_of(1, c), jv = jt_of(2, c);
                    VY(c) = movm(pack_bf16(fmaf(CS0(jv), n1, acc[4 * jv + 2] * s1.x), fmaf(CS1(jv), n1, acc[4 * jv + 3] * s1.x)));
                    KY(c) = pack_bf16(fmaf(CS0(jk), n1, acc[4 * jk + 2] * s1.x), fmaf(CS1(jk), n1, acc[4 * jk + 3] * s1.x));
                }
                if (w == 3) {
#pragma unroll
                    for (int j = 0; j < 5; j++) {
                        Y[4 * j] = (Y[4 * j] & ~0x10001u) | par;
                        stg128(halo + j * 512, Y[4 * j], Y[4 * j + 1], Y[4 * j + 2], Y[4 * j + 3]);
                    }
                } else {
                    mbar_wait(sb + B_EMPTY + 8, 1);
#pragma unroll
                    for (int j = 0; j < 5; j++) sts128(slot + 2560 + j * 512, Y[4 * j], Y[4 * j + 1], Y[4 * j + 2], Y[4 * j + 3]);
                }
                TR(r26);
#pragma unroll
                for (int c = 0; c < 10; c++) {
                    const int jk = jt_of(1, c), jv = jt_of(2, c);
                    KX[c] = pack_bf16(fmaf(CS0(jk), n0, acc[4 * jk] * s0.x), fmaf(CS1(jk), n0, acc[4 * jk + 1] * s0.x));
                    VX[c] = movm(pack_bf16(fmaf(CS0(jv), n0, acc[4 * jv] * s0.x), fmaf(CS1(jv), n0, acc[4 * jv + 1] * s0.x)));
                    asm volatile("" : "+r"(KX[c]), "+r"(VX[c]));
                }
                asm volatile("{\n.reg .pred p;\nLAB_SPLIT:\nsetp.eq.u32 p, %0, 0;\n@p nanosleep.u32 1;\n@p bra LAB_SPLIT;\n}" :: "r"(par) : "memory");
#pragma unroll
                for (int j = 0; j < 5; j++) cs[CSI(j)] = lds128f(sb + M_CS + t * 16 + CSI(j) * 64);
                bar_sync(2 + p, 128);
                TR(r28);
                if (remote) {
#pragma unroll
                    for (int j = 0; j < 5; j++) ldg128(halo - 8 * XB + j * 512, Z[4 * j], Z[4 * j + 1], Z[4 * j + 2], Z[4 * j + 3]);
                } else {
#pragma unroll
                    for (int j = 0; j < 5; j++) {
                        const uint4 v = lds128(slot + (w ? 0 : 2560) + j * 512);
                        Z[4 * j] = v.x; Z[4 * j + 1] = v.y; Z[4 * j + 2] = v.z; Z[4 * j + 3] = v.w;
                    }
                }
                if (lane < 2) mbar_arrive_cl(empty_cl + 32);
#pragma unroll
                for (int c = 0; c < 10; c++) {
                    const int jq = jt_of(0, c);
                    Ql[c] = pack_bf16(fmaf(CS0(jq), -s0.y, acc[4 * jq]), fmaf(CS1(jq), -s0.y, acc[4 * jq + 1]));
                    Q[c] = pack_bf16(fmaf(CS0(jq), -s1.y, acc[4 * jq + 2]), fmaf(CS1(jq), -s1.y, acc[4 * jq + 3]));
                    asm volatile("" : "+r"(Ql[c]), "+r"(Q[c]));
                }
            }
            auto unit = [&](const uint32_t (&q)[10], const uint32_t (&z)[20], const int c0, const uint32_t mx, const float sq, const float nz, const int h) {
                const uint32_t qa = t < 2 ? q[c0 + 2] : 0u, qb = t < 2 ? 0u : q[c0 + 2];
                float xa[4] = {0.f, 0.f, 0.f, 0.f}, za[4] = {0.f, 0.f, 0.f, 0.f}, xb[4], zb[4];
                mma1688(xa, qa, qb, KX[c0 + 2]);
                mma1688(za, qa, qb, z[KI(c0 + 2)]);
#pragma unroll
                for (int e = 0; e < 4; e++) { xb[e] = xa[e]; zb[e] = za[e]; }
                mma16816(xa, q[c0], q[c0 + 3], q[c0 + 1], q[c0 + 4], KX[c0], KX[c0 + 1]);
                mma16816(za, q[c0], q[c0 + 3], q[c0 + 1], q[c0 + 4], z[KI(c0)], z[KI(c0 + 1)]);
                mma16816(xb, q[c0], q[c0 + 3], q[c0 + 1], q[c0 + 4], KX[c0 + 3], KX[c0 + 4]);
                mma16816(zb, q[c0], q[c0 + 3], q[c0 + 1], q[c0 + 4], z[KI(c0 + 3)], z[KI(c0 + 4)]);
                const bool h0 = mx & 1u, h1 = (int)mx < 0;
                const float l00 = h0 ? xa[0] : za[0] + nz, l01 = h1 ? xa[1] : za[1] + nz;
                const float l10 = h0 ? xb[2] : zb[2] + nz, l11 = h1 ? xb[3] : zb[3] + nz;
                float m0 = fmaxf(l00, l01), m1 = fmaxf(l10, l11);
                m0 = fmaxf(m0, shx(m0, 1)); m1 = fmaxf(m1, shx(m1, 1));
                m0 = fmaxf(m0, shx(m0, 2)) * -sq; m1 = fmaxf(m1, shx(m1, 2)) * -sq;
                const uint32_t pa = pack_bf16(ex2(fmaf(l00, sq, m0)), ex2(fmaf(l01, sq, m0)));
                const uint32_t pb = pack_bf16(ex2(fmaf(l10, sq, m1)), ex2(fmaf(l11, sq, m1)));
                float dn[4] = {0.f, 0.f, 0.f, 0.f};
                mma1688(dn, pa, pb, 0x3F803F80u);
                const float i0 = rcp(dn[0]), i1 = rcp(dn[2]), i2 = t < 2 ? i0 : i1;
#pragma unroll
                for (int c = 0; c < 5; c++) {
                    float oc[4] = {0.f, 0.f, 0.f, 0.f};
                    mma16816(oc, pa & mx, pb & mx, pa & ~mx, pb & ~mx, VX[c0 + c], z[10 + c0 + c]);
                    const bool first = c < 2 || (c == 2 && t < 2);
                    const float iv = c < 2 ? i0 : (c > 2 ? i1 : i2);
                    A[0][2 * (c0 + c) + h] = pack_bf16((first ? oc[0] : oc[2]) * iv, (first ? oc[1] : oc[3]) * iv);
                }
            };
            const uint32_t mo = (2 * t > g ? 0xFFFFu : 0u) | (2 * t + 1 > g ? 0xFFFF0000u : 0u);
            constexpr float SC = 0.22360679774997896f * LOG2E;
            {
                unsigned spins = 0;
#pragma unroll 1
                while (remote && any((Z[0] & Z[4] & Z[8] & Z[12] & Z[16] & par) == 0u) && ++spins < SPIN) {
#pragma unroll
                    for (int j = 0; j < 5; j++) ldg128(halo - 8 * XB + j * 512, Z[4 * j], Z[4 * j + 1], Z[4 * j + 2], Z[4 * j + 3]);
                }
                TR(r32);
                const float nz = start ? -INFINITY : 0.f;
                unit(Q, Y, 0, mo, s1.x * SC, 0.f, 1);
                unit(Q, Y, 5, mo, s1.x * SC, 0.f, 1);
                unit(Ql, Z, 0, ~mo, s0.x * SC, nz, 0);
                unit(Ql, Z, 5, ~mo, s0.x * SC, nz, 0);
            }
#pragma unroll
            for (int j = 0; j < 5; j++)
                stg128(orow + hg * XB + j * 512, (A[0][4 * j] & ~0x10001u) | par, A[0][4 * j + 1], A[0][4 * j + 2], A[0][4 * j + 3]);
            if (lane == 0) stg32(flag, par);
            TR(r34);
            if (p) bar_arrive(8, 256);
            if (w) {
                mbar_wait(sb + B_X, 0);
                float2 u0 = s0, u1 = s1;
                const float2 z0 = lds64f(sb + M_ST + (p * 64 + g) * 8), z1 = lds64f(sb + M_ST + (p * 64 + g + 8) * 8);
                uint32_t a = ta, xn[4];
                ldsm_x4(xn, a + OFF_X);
#pragma unroll 1
                for (uint32_t it = 0; it < (w < 3 ? 7u : 6u); it++) {
                    uint32_t xf[4] = {xn[0], xn[1], xn[2], xn[3]};
                    const uint32_t an = a + (it < 4 ? 32 : (it == 4 ? w * (32 - 2560) - 160 : 96));
                    ldsm_x4(xn, an + OFF_X);
                    const float r0 = 0.5f * u0.x, r1 = 0.5f * u1.x, n0 = -r0 * u0.y, n1 = -r1 * u1.y;
#pragma unroll
                    for (int q = 0; q < 4; q++) {
                        const float v0 = fmaf(bflo(xf[q]), q & 1 ? r1 : r0, q & 1 ? n1 : n0), v1 = fmaf(bfhi(xf[q]), q & 1 ? r1 : r0, q & 1 ? n1 : n0);
                        xf[q] = pack_bf16(fmaf(v0, tanh_a(v0), v0), fmaf(v1, tanh_a(v1), v1));
                    }
                    stsm_x4(a + OFF_G, xf);
                    a = an;
                    if (it == 4) { u0 = z0; u1 = z1; }
                }
            }
            TR(r61);
        }
        float acc2[40];
        {
            unsigned spins = 0;
            bool again, first = true;
            if (w) {
#pragma unroll 1
                for (uint32_t i = 0; i < 32; i += 8) mbar_wait(sb + B_WO + i, 0);
            } else {
                const uint8_t* fp = P.scr + (G_FLAG + (rb * 8 + (lane & 7)) * XB + p * 16 + (lane >> 3) * 4);
#pragma unroll 1
                while (any(ldg32(fp) != par) && ++spins < SPIN) { }
            }
            TR(r20);
            bar_sync(8 + p, 256);
#pragma unroll 1
            do {
                const uint8_t* src = orow - XB;
#pragma unroll
                for (uint32_t i = 1; i < 7; i++) {
                    if (i == hg + 1) src += XB;
#pragma unroll
                    for (int j = 0; j < 5; j++)
                        ldg128(src + i * XB + j * 512, A[i][4 * j], A[i][4 * j + 1], A[i][4 * j + 2], A[i][4 * j + 3]);
                }
                if (hg == 6) src += XB;
                bar_arrive(10, 32);
                TR(r21);
#pragma unroll
                for (int i = 0; i < 8; i++) {
                    uint32_t (&a)[20] = A[i % 7];
                    if (i != 4 && i != 6) wgmma_fence();
#pragma unroll
                    for (int j = 0; j < 5; j++)
                        wgmma_rs_n80(acc2, a[4 * j], a[4 * j + 1], a[4 * j + 2], a[4 * j + 3],
                                     mk(sbd + ((OFF_WO + ((i + 1) & 7) * WO_SLOT) >> 4) + j * 64 + (320 << 16), HI64), i || j);
                    if (i < 2 || i == 6) wgmma_commit();
                    if (i == SERAT && !p && first) bar_arrive(9, 256);
                    if (i == 0) TR(r22);
                    if (i == 1) {
                        wgmma_wait<1>();
#pragma unroll
                        for (int j = 0; j < 5; j++)
                            ldg128(src + 7 * XB + j * 512, A[0][4 * j], A[0][4 * j + 1], A[0][4 * j + 2], A[0][4 * j + 3]);
                    }
                }
                wgmma_commit();
                first = false;
                TR(r42);
                uint32_t mn = par;
#pragma unroll
                for (int i = 1; i < 8; i++) mn &= A[i % 7][0] & A[i % 7][4] & A[i % 7][8] & A[i % 7][12] & A[i % 7][16];
                again = bar_or(2 + p, 128, mn == 0u && ++spins < SPIN);
                if (again) {
                    wgmma_wait<0>();
#pragma unroll
                    for (int j = 0; j < 5; j++)
                        ldg128(orow + hg * XB + j * 512, A[0][4 * j], A[0][4 * j + 1], A[0][4 * j + 2], A[0][4 * j + 3]);
                }
            } while (again);
        }
        {
            mbar_wait(sb + B_UPD, 0);
            const float2 sel = lds64f(sb + M_SEL);
            const uint32_t row = warp * 16 + (lane & 15);
            const uint32_t go = row == U(sel.x) ? M_UPD - row * 160 : (row == U(sel.y) ? M_UPD + 160 - row * 160 : OFF_G);
            const uint32_t a0 = ta + (hg & 1) * 32, a4 = ta + (~hg & 1) * 128;
            uint32_t xf[5][4], gf[5][4];
            wgmma_wait<1>();
#pragma unroll
            for (int c = 0; c < 5; c++) {
                ldsm_x4(xf[c], (c < 4 ? a0 + c * 32 : a4) + OFF_X);
                ldsm_x4(gf[c], (c < 4 ? a0 + c * 32 : a4) + go);
            }
            wgmma_wait<0>();
#pragma unroll
            for (int i = 0; i < 40; i++) asm volatile("" : "+f"(acc2[i]) :: "memory");
            TR(r44);
#pragma unroll
            for (int c = 0; c < 5; c++) {
#pragma unroll
                for (int q = 0; q < 4; q++)
                    asm("fma.rn.bf16x2 %0, %1, %2, %0;" : "+r"(xf[c][q]) : "r"(pack_bf16(acc2[8 * c + 2 * q], acc2[8 * c + 2 * q + 1])), "r"(gf[c][q]));
                stsm_x4((c < 4 ? a0 + c * 32 : a4) + OFF_X, xf[c]);
            }
            fence_proxy_async_smem();
            __syncwarp();
            if (lane == 0) {
                tma_st(&P.tm[T_OUT], sb + OFF_X + warp * 2560, hg * 80, rb * 64 + 16 * w, p);
                asm volatile("cp.async.bulk.wait_group.read 0;" ::: "memory");
            }
        }
        TS(46);
        TRW(r12, 12); TRW(r26, 26); TRW(r28, 28); TRW(r32, 32); TRW(r34, 34); TRW(r61, 61); TRW(r20, 20); TRW(r21, 21); TRW(r22, 22); TRW(r42, 42); TRW(r44, 44);
    } else if (warp >= 12) {
        asm volatile("setmaxnreg.dec.sync.aligned.u32 32;");
        if (warp == 12) {
            uint32_t slot = clock32() + PACE0;
            if (elect()) {
                mbar_expect_tx(sb + B_FULL + 16, ST);
                tma(sb + 2 * ST, &P.tm[T_X], sb + B_FULL + 16, k0, rb * 64);
            }
            __syncwarp();
            cluster_wait();
            if (elect()) {
                TS(48);
#pragma unroll 1
                for (uint32_t kb = 0; kb < 10; kb++) {
                    const uint32_t s = (kb + 2) & 3;
                    const uint32_t st = sb + s * ST, fb = sb + B_FULL + 8 * s;
                    const uint32_t kc = kb * 64 + (kb < 5 ? k0 : -k0);
                    if (kb >= 4) {
                        mbar_wait(fb + 32, kb >> 3);
                        if (kb < 9) mbar_wait(sb + B_AX - 32 + 8 * kb, 0);
                    }
                    if (kb > 0) {
                        slot += PACE1;
#pragma unroll 1
                        while ((int)(clock32() - slot) < 0) { }
                        mbar_expect_tx(fb, ST);
                        tma(st, &P.tm[T_X], fb, kc, rb * 64);
                    }
                    tma_mc(st + ST_BM + rank * 12288, &P.tm[T_W], fb, hg * 80 + (hg & ODDX) * 16, kc + rank * 32);
                    tma_mc(st + ST_BR + rank * 3072, &P.tm[T_WR], fb, hg * 80 + 64 - (hg & ODDX) * 64, kc + rank * 32);
                }
                TS(49);
                mbar_wait(sb + B_EMPTY, 1);
                mbar_expect_tx(sb + B_X, 20480);
                tma(sb + OFF_X, &P.tm[T_XT], sb + B_X, hg * 80, rb * 64);
                uint32_t wb = sb + B_WO - 8;
#pragma unroll 1
                for (uint32_t i = 0; i < 8; i++) {
                    if ((0x93 >> i) & 1) {
                        wb += 8;
                        mbar_wait(wb - (B_WO - B_EMPTY - 8), i == 0);
                        mbar_expect_tx(wb, i == 0 ? 12800 + 20480 : (i < 7 ? 3 * 12800 : 12800));
                    }
                    if (WOP) {
#pragma unroll 1
                        while ((int)(clock32() - slot) < 0) { }
                        slot = clock32() + WOP;
                    }
                    if (i == 0) tma(sb + OFF_DN, &P.tm[T_D], wb, 0, 32 * fp, 5 * rank);
                    const uint32_t d = sb + OFF_WO + ((i + 1) & 7) * WO_SLOT;
                    const uint32_t kr = 80 * (i ? i - (i <= hg) : hg);
                    tma_mc(d + rank * 5120, &P.tm[T_WO], wb, hg * 80 + (hg & 1) * 16 + rank * 32, kr);
                    tma_mc(d + 10240 + rank * 2560, &P.tm[T_WOR], wb, hg * 80 + (~hg & 1) * 64, kr + rank * 40);
                }
                TS(50);
            }
        } else if (warp == 13) {
            uint32_t slot = clock32() + GU0;
            if (elect()) {
#pragma unroll 1
                for (uint32_t i = PFM0 * NPC; i < 4 * NPC; i++) {
                    const uint32_t m = i / NPC, n = m == 2 ? 6400 / NPC : 17280 / NPC;
                    slot += m == 2 ? GU1 / 3 : GU1;
#pragma unroll 1
                    while ((int)(clock32() - slot) < 0) __nanosleep(20);
                    l2_prefetch(P.pf[m] + ((i - m * NPC) * 128 + b) * n, n);
                }
                TS(59);
            }
        } else if (warp == 14) {
            uint32_t slot = clock32() + GT0;
            cluster_wait();
            if (elect()) {
#pragma unroll 1
                for (uint32_t i = 0; i < 20; i++) {
                    slot += GT1;
#pragma unroll 1
                    while ((int)(clock32() - slot) < 0) __nanosleep(20);
                    tma(sb + OFF_GU + i * 2048, &P.tm[T_GU], sb + B_GU, 32 * fp, rank * 320 + i * 16);
                }
            }
        }
    } else {
        asm volatile("setmaxnreg.dec.sync.aligned.u32 64;");
        const uint32_t at = opaque_tid() - 256, lane = at & 31, g = lane >> 2, t = lane & 3, c7 = lane & 7, aw = warp - 8;
        const uint32_t epoch = ldg32(P.scr + G_EPOCH) + 1, tag = (epoch & 15u) | 16u;
        const uint32_t empty_cl = mapa(sb + B_EMPTY, lane & 1);
        unsigned spins = 0;
        TRD(r51); TRD(r30); TRD(r52); TRD(r53); TRD(r54); TRD(r55); TRD(r20); TRD(r21); TRD(r22); TRD(r23);
        const uint32_t t0 = clock32();
        {
            const uint2 wv = __ldg(reinterpret_cast<const uint2*>(P.w_r + k0 * 2 + min(at, 79u) * 8));
            if (at < 80) sts64(sb + M_UPD + at * 8, wv.x, wv.y);
        }
        uint8_t* const stw = P.scr + (b * XB + G_ST + (lane & 4) * 64 + (at >> 3) * 16);
        uint8_t* const csw = P.scr + (b * XB + G_CS + at);
        uint8_t* const tpw = P.scr + (G_TOP + (hg >> 2) * XB + rb * 64 + aw * 16);
        const bool tpub = lane == 0 && (hg & 3) == 3;
        if (t == 0) { stg128(stw, 0u, 0u, 0u, 0u); stg32(csw, 0u); }
        if (tpub) stg128(tpw, 0u, 0u, 0u, 0u);
        uint8_t* const yp = P.scr + (G_Y + (fp & 63) * XB + rank * 1280 + t * 256 + aw * 64 + g * 8);
        stg64(yp, 0u, 0u); stg64(yp + 2560, 0u, 0u);
        if (t == 0) { stg64(yp + 1024, 0u, 0u); stg64(yp + 1024 + 2560, 0u, 0u); }
        cluster_wait();
        bar_sync(4, 128);
        uint32_t k1, sv;
        {
            const uint32_t xoff = (32 * (hg & 3) + (at >> 3)) * 128 + ((c7 ^ ((at >> 3) & 7)) << 4);
            const uint32_t jt = (rb >> 2) * 8 + rank * 4 + aw;
            const uint32_t coff = jt < 24 ? ST_BM + (jt >> 3) * 4096 + lane * 128 + (((jt ^ lane) & 7) << 4)
                                          : ST_BR + ((jt >> 1) & 3) * 1024 + lane * 32 + (((jt ^ g) & 1) << 4);
            float q[8], c8[8];
#pragma unroll
            for (int e = 0; e < 8; e++) q[e] = c8[e] = 0.f;
#pragma unroll 1
            for (uint32_t kb = 2; kb < 7; kb++) {
                const uint32_t st = sb + (kb & 3) * ST;
                const uint4 wv = lds128(sb + M_UPD - 256 + kb * 128 + c7 * 16);
                mbar_wait(sb + B_FULL + 8 * (kb & 3), kb == 6);
                const uint4 v = lds128(st + xoff), vn = lds128(st + xoff + 2048);
                const uint4 cv = lds128(st + coff), cn = lds128(st + coff + (jt < 24 ? 12288 : 3072));
                if (lane < 2) mbar_arrive_cl(empty_cl + (B_AX - B_EMPTY - 16) + 8 * kb + (cn.x & 0));
                const uint32_t u[4] = {v.x, v.y, v.z, v.w}, un[4] = {vn.x, vn.y, vn.z, vn.w}, ww[4] = {wv.x, wv.y, wv.z, wv.w};
                const uint32_t cc[4] = {cv.x, cv.y, cv.z, cv.w}, cd[4] = {cn.x, cn.y, cn.z, cn.w};
#pragma unroll
                for (int e = 0; e < 4; e++) {
                    const float a0 = bflo(u[e]), a1 = bfhi(u[e]), b0 = bflo(un[e]), b1 = bfhi(un[e]), w0 = bflo(ww[e]), w1 = bfhi(ww[e]);
                    q[0] += a0 + a1; q[4] += b0 + b1; q[3] += w0 + w1;
                    q[1] = fmaf(a0, a0, fmaf(a1, a1, q[1])); q[5] = fmaf(b0, b0, fmaf(b1, b1, q[5]));
                    q[2] = fmaf(a0, w0, fmaf(a1, w1, q[2])); q[6] = fmaf(b0, w0, fmaf(b1, w1, q[6]));
                    c8[2 * e] += bflo(cc[e]) + bflo(cd[e]); c8[2 * e + 1] += bfhi(cc[e]) + bfhi(cd[e]);
                }
            }
            TR(r51);
            q[7] = q[3];
#pragma unroll
            for (int e = 0; e < 4; e++) {
                q[e] = ((lane & 4) ? q[e + 4] : q[e]) + shx((lane & 4) ? q[e] : q[e + 4], 4);
                q[e] += shx(q[e], 1); q[e] += shx(q[e], 2);
            }
            const float mh = q[0] * (1.0f / 320);
            if (t == 0) stg128(stw, U(mh), U(fmaf(-mh, q[0], q[1])), U(q[2]), (U(q[3]) & ~31u) | tag);
#define TSTEP(H) { const bool up = (lane & (4 * H)) != 0; _Pragma("unroll") for (int e = 0; e < H; e++) { \
            const float send = up ? c8[e] : c8[e + H]; const float keep = up ? c8[e + H] : c8[e]; \
            c8[e] = keep + shx(send, 4 * H); } }
            TSTEP(4) TSTEP(2) TSTEP(1)
#undef TSTEP
            c8[0] += shx(c8[0], 1); c8[0] += shx(c8[0], 2);
            if (t == 0) stg32(csw, (U(c8[0]) & ~31u) | tag);
            bar_sync(4, 128);
            TR(r30);
            const uint8_t* csp = P.scr + (G_CS + (aw * 32 + (lane >> 4) * 8 + hg) * XB + (lane & 15) * 8);
            const uint8_t* stp = P.scr + (G_ST + (rb * 8 + aw) * XB + lane * 16);
            uint32_t ra[4], rc[4];
            uint2 ca, cc;
#pragma unroll 1
            while (clock32() - t0 < EX1T) __nanosleep(20);
#pragma unroll 1
            do {
                ldg128(stp, ra[0], ra[1], ra[2], ra[3]);
                ldg128(stp + 4 * XB, rc[0], rc[1], rc[2], rc[3]);
                ca = ldg64(csp); cc = ldg64(csp + 16 * XB);
            } while (any((ra[3] ^ tag | rc[3] ^ tag | ca.x ^ tag | ca.y ^ tag | cc.x ^ tag | cc.y ^ tag) & 31u) && retry(spins));
            TR(r20);
            const float dm = 0.5f * (F(ra[0]) - F(rc[0])), m = bf16r(F(rc[0]) + dm);
            const float sd = bf16r(sqrt_a(bf16r(bf16r(fmaxf(fmaf(dm, dm, (F(ra[1]) + F(rc[1])) * (1.0f / DM)), 0.f)) + 1e-5f)));
            const float rs = rcp(sd);
            sts64(sb + M_ST + at * 8, U(rs), U(m));
            sts32(sb + M_SEL + 8, (tag & 1) ? 1u : 0x10000u);
            sts64(sb + M_CS + (at >> 3) * 64 + t * 16 + (g & 1) * 8, U(F(ca.x) + F(cc.x)), U(F(ca.y) + F(cc.y)));
            TR(r52);
            k1 = pack_bf16(0.f, fmaf(-m, F(ra[3]) + F(rc[3]), F(ra[2]) + F(rc[2])) * rs);
            k1 ^= ((int)k1 >> 31) | 0x80000000u;
            k1 = (k1 & 0xFFFF0000u) | ((2047 - (rb * 128 + 2 * (at & 63) + (at >> 6))) << 5) | tag;
            uint32_t w1 = redux_max(k1), w2 = redux_max(k1 == w1 ? 0u : k1);
            if (lane < 2) mbar_arrive(sb + B_PREP);
            sv = U(m) | (U(sd) >> 16);
            const uint32_t v1 = redux_max(k1 == w1 ? sv : 0u), v2 = redux_max(k1 == w2 ? sv : 0u);
            if (tpub) stg128(tpw, w1, v1, w2, v2);
            uint32_t ka[4], kb[4];
#pragma unroll 1
            while (clock32() - t0 < EX2T) __nanosleep(20);
            uint32_t src = 0;
            TR(r21);
#pragma unroll 1
            do {
                const uint8_t* tp = P.scr + (G_TOP + src + lane * 16);
                ldg128(tp, ka[0], ka[1], ka[2], ka[3]);
                ldg128(tp + 512, kb[0], kb[1], kb[2], kb[3]);
                const bool bad = (ka[0] ^ tag | kb[0] ^ tag) & 31u;
                if (!any(bad)) break;
                if (bad) src ^= XB;
            } while (++spins < SPIN);
            TR(r22);
            if (kb[0] > ka[0]) {
#pragma unroll
                for (int e = 0; e < 4; e++) { const uint32_t x = ka[e]; ka[e] = kb[e]; kb[e] = x; }
            }
            if (kb[0] > ka[2]) { ka[2] = kb[0]; ka[3] = kb[1]; }
            w1 = redux_max(ka[0]);
            const uint32_t t1 = redux_max(ka[0] == w1 ? ka[1] : 0u);
            if (ka[0] == w1) { ka[0] = ka[2]; ka[1] = ka[3]; }
            w2 = redux_max(ka[0]);
            const uint32_t t2 = redux_max(ka[0] == w2 ? ka[1] : 0u);
            k1 = (lane & 1) ? w2 : w1;
            sv = (lane & 1) ? t2 : t1;
        }
        TR(r53);
        const uint32_t tok = ~(k1 >> 5) & 2047;
        const unsigned owns = __ballot_sync(0xffffffffu, (tok >> 7) == rb) & 3u;
        if (at < 2) sts32(sb + M_SEL + at * 4, (tok >> 7) == rb ? (tok & 1) * 64 + ((tok & 127) >> 1) : ~0u);
        if ((at | b) == 0) *reinterpret_cast<uint32_t*>(P.scr + G_EPOCH) = epoch;
        __syncwarp();
        if ((at | owns) == 0) mbar_arrive(sb + B_UPD);
        if (fp < NFFN / 2) {
            uint4 xv = __ldg(reinterpret_cast<const uint4*>(P.x + (tok * 1280 + rank * 640 + min(at >> 1, 39u) * 16)));
            if (at < 40) sts128(sb + M_UPD + at * 16, 0u, 0u, 0u, 0u);
            const uint32_t m2 = __byte_perm(sv, 0, 0x3232);
            asm("sub.rn.bf16x2 %0, %0, %4;\nsub.rn.bf16x2 %1, %1, %4;\nsub.rn.bf16x2 %2, %2, %4;\nsub.rn.bf16x2 %3, %3, %4;"
                : "+r"(xv.x), "+r"(xv.y), "+r"(xv.z), "+r"(xv.w) : "r"(m2));
            mbar_wait(sb + B_X, 0);
            if (at < 80) sts128(sb + OFF_PART + at * 16, xv.x, xv.y, xv.z, xv.w);
            fence_proxy_async_smem();
            mbar_wait(sb + B_GU, 0);
            bar_sync(4, 128);
            float c[4], d[4];
            TR(r23);
            wgmma_fence();
#pragma unroll 1
            for (uint32_t i = 0; i < 20; i += GUU) {
#pragma unroll
                for (uint32_t j = 0; j < GUU; j++)
                    wgmma_n8(j & 1 ? d : c, mk(sbd + (OFF_GU >> 4) + (i + j) * 128 + (64 << 16), HI64), mk(sbd + (OFF_PART >> 4) + (i + j) * 4 + (2 << 16), 8), i + (j >> 1));
            }
            wgmma_commit();
            wgmma_wait<0>();
            asm volatile("" : "+f"(c[0]), "+f"(c[1]), "+f"(c[2]), "+f"(c[3]), "+f"(d[0]), "+f"(d[1]), "+f"(d[2]), "+f"(d[3]) :: "memory");
            c[0] += d[0]; c[1] += d[1]; c[2] += d[2]; c[3] += d[3];
            bar_sync(4, 128);
            if (t == 0) {
#pragma unroll
                for (uint32_t r = 0; r < 2; r++) {
                    const uint32_t rd = mapa(sb, rank ^ r);
                    asm volatile("st.async.shared::cluster.mbarrier::complete_tx::bytes.v4.f32 [%0], {%1,%2,%3,%4}, [%5];"
                                 :: "r"(rd + OFF_PART + r * 1280 + at * 4), "f"(c[0]), "f"(c[1]), "f"(c[2]), "f"(c[3]), "r"(rd + B_H) : "memory");
                }
            }
            TR(r54);
            mbar_wait(sb + B_H, 0);
            const uint32_t pa = sb + OFF_PART + (at & 63) * 4 + P.up_first;
            const float rs = rcp(bflo(sv));
            const float gs = bf16r((F(lds32(pa)) + F(lds32(pa + 1280))) * rs), us = bf16r((F(lds32(pa ^ 256)) + F(lds32((pa ^ 256) + 1280))) * rs);
            asm volatile("st.shared.u16 [%0], %1;" :: "r"(sb + M_UPD + 96 + (aw & 1) * 256 + (t >> 1) * 128 + (t & 1) * 16 + g * 2),
                         "r"(pack_bf16(bf16r(gs * sigm(gs)) * us, 0.f)) : "memory");
            fence_proxy_async_smem();
            mbar_wait(sb + B_WO, 0);
            bar_sync(4, 128);
            wgmma_fence();
#pragma unroll
            for (uint32_t i = 0; i < 10; i++)
                wgmma_n8(i < 8 ? c : d, mk(sbd + (OFF_DN >> 4) + i * 128, HI128), mk(sbd + ((M_UPD + 96) >> 4) + (i & 1) * 16 - (i & 6) + (8 << 16), 8), i & 7);
            wgmma_commit();
            wgmma_wait<0>();
            asm volatile("" : "+f"(c[0]), "+f"(c[1]), "+f"(c[2]), "+f"(c[3]), "+f"(d[0]), "+f"(d[1]), "+f"(d[2]), "+f"(d[3]) :: "memory");
            stg64(yp, (U(c[0]) & ~31u) | tag, U(c[2]));
            stg64(yp + 2560, (U(c[1]) & ~31u) | tag, U(c[3]));
            if (t == 0) {
                stg64(yp + 1024, (U(d[0]) & ~31u) | tag, U(d[2]));
                stg64(yp + 1024 + 2560, (U(d[1]) & ~31u) | tag, U(d[3]));
            }
            TR(r55);
        }
        TRW(r51, 51); TRW(r30, 30); TRW(r52, 52); TRW(r53, 53); TRW(r54, 54); TRW(r55, 55); TRW(r20, 20); TRW(r21, 21); TRW(r22, 22); TRW(r23, 23);
        if (owns) {
            const uint32_t i0 = min((at * 205) >> 12, 5u);
            mbar_wait(sb + B_X, 0);
            k1 ^= ((~(int)k1) >> 31) | 0x80000000u;
            const float sg = bf16r(sigm(bfhi(k1)));
#pragma unroll 1
            for (uint32_t tk = ~owns & 1; tk <= (owns >> 1); tk++) {
                const uint8_t* yr = P.scr + (G_Y + i0 * (9 * XB - 320) + tk * 2560 + hg * 320 + min(at, 119u) * 16);
                uint32_t v[9][4], bad;
#pragma unroll 1
                do {
                    __nanosleep(YSLEEP);
                    bad = 0;
#pragma unroll
                    for (int i = 0; i < 9; i++) ldg128(yr + i * XB, v[i][0], v[i][1], v[i][2], v[i][3]);
#pragma unroll
                    for (int i = 0; i < 9; i++) bad |= v[i][0] ^ tag | v[i][2] ^ tag;
                } while (any(bad & 31u) && ++spins < SPIN);
                float y[4] = {F(v[0][0]), F(v[0][1]), F(v[0][2]), F(v[0][3])};
#pragma unroll
                for (int i = 1; i < 9; i++) { y[0] += F(v[i][0]); y[1] += F(v[i][1]); y[2] += F(v[i][2]); y[3] += F(v[i][3]); }
                bar_sync(4, 128);
                sts128(sb + OFF_PART + at * 16, U(y[0]), U(y[1]), U(y[2]), U(y[3]));
                bar_sync(4, 128);
                float ys = F(lds32(sb + OFF_PART + at * 4));
#pragma unroll
                for (int i = 1; i < 6; i++) ys += F(lds32(sb + OFF_PART + i * 320 + at * 4));
                const uint32_t col = (at & ~15u) * 2 + (at & 14) + (at & 1) * 16, row = lds32(sb + M_SEL + tk * 4);
                const float2 st = lds64f(sb + M_ST + row * 8);
                uint32_t xv;
                asm volatile("ld.shared.u16 %0, [%1];" : "=r"(xv) : "r"(sb + OFF_X + row * 160 + col));
                ys = fmaf(bflo(xv) - st.y, st.x, bf16r(bf16r(ys) * __shfl_sync(0xffffffffu, sg, tk)));
                if (at < 80) asm volatile("st.shared.u16 [%0], %1;" :: "r"(sb + M_UPD + tk * 160 + col), "r"(pack_bf16(ys * sigm(ys), 0.f)) : "memory");
            }
            bar_sync(4, 128);
            if (at == 0) mbar_arrive(sb + B_UPD);
            TS(56);
        }
    }
}

typedef CUresult (*EncodeFn)(CUtensorMap*, CUtensorMapDataType, cuuint32_t, void*, const cuuint64_t*, const cuuint64_t*,
                             const cuuint32_t*, const cuuint32_t*, CUtensorMapInterleave, CUtensorMapSwizzle,
                             CUtensorMapL2promotion, CUtensorMapFloatOOBfill);

bool encode(EncodeFn fn, CUtensorMap* tm, const void* ptr, cuuint64_t d0, cuuint64_t d1, cuuint64_t d2, cuuint64_t s1, cuuint64_t s2,
            cuuint32_t b0, cuuint32_t b1, cuuint32_t b2, CUtensorMapSwizzle sw) {
    const cuuint64_t dims[3] = {d0, d1, d2}, strides[2] = {s1, s2};
    const cuuint32_t box[3] = {b0, b1, b2}, es[3] = {1, 1, 1};
    return fn(tm, CU_TENSOR_MAP_DATA_TYPE_BFLOAT16, 3, const_cast<void*>(ptr), dims, strides, box, es,
              CU_TENSOR_MAP_INTERLEAVE_NONE, sw, CU_TENSOR_MAP_L2_PROMOTION_L2_128B,
              CU_TENSOR_MAP_FLOAT_OOB_FILL_NONE) == CUDA_SUCCESS;
}

}

extern "C" void kernel_launch(void* const* d_in, const int* in_sizes, int n_in, void* d_out, int out_size) {
    static Params P;
    static int grid = 0;
    static const void* cached[9] = {};
    bool same = cached[8] == d_out;
    for (int i = 0; i < 8; i++) same = same && cached[i] == d_in[i];
    if (!same) {
        const void *x = d_in[0], *wqkv = d_in[1], *wo = d_in[2], *wg = d_in[5], *wu = d_in[6], *wd = d_in[7];
        void* fnp = nullptr;
        cudaDriverEntryPointQueryResult qr;
        cudaGetDriverEntryPoint("cuTensorMapEncodeTiled", &fnp, cudaEnableDefault, &qr);
        EncodeFn fn = (EncodeFn)fnp;
        const CUtensorMapSwizzle S0 = CU_TENSOR_MAP_SWIZZLE_NONE, S32 = CU_TENSOR_MAP_SWIZZLE_32B, S64 = CU_TENSOR_MAP_SWIZZLE_64B,
                                 S128 = CU_TENSOR_MAP_SWIZZLE_128B;
        const bool ok = fn != nullptr &&
            encode(fn, &P.tm[T_X], x, 640, 1024, 2, 2560, 1280, 64, 64, 2, S128) &&
            encode(fn, &P.tm[T_XT], x, 640, 1024, 2, 2560, 1280, 80, 64, 2, S0) &&
            encode(fn, &P.tm[T_OUT], d_out, 640, 1024, 2, 2560, 1280, 80, 16, 1, S0) &&
            encode(fn, &P.tm[T_W], wqkv, 640, 640, 3, 3840, 1280, 64, 32, 3, S128) &&
            encode(fn, &P.tm[T_WR], wqkv, 640, 640, 3, 3840, 1280, 16, 32, 3, S32) &&
            encode(fn, &P.tm[T_GU], wg < wu ? wg : wu, 1728, 640, 2, 3456, wg < wu ? (const char*)wu - (const char*)wg : (const char*)wg - (const char*)wu,
                   32, 16, 2, S64) &&
            encode(fn, &P.tm[T_D], wd, 64, 1728, 10, 1280, 128, 64, 32, 5, S128) &&
            encode(fn, &P.tm[T_WO], wo, 640, 640, 1, 1280, 1280 * 640, 32, 80, 1, S64) &&
            encode(fn, &P.tm[T_WOR], wo, 640, 640, 1, 1280, 1280 * 640, 16, 40, 1, S64);
        if (!ok) return;
        P.up_first = wg < wu ? 0 : 256;
        P.pf[0] = (const uint8_t*)wg; P.pf[1] = (const uint8_t*)wu; P.pf[2] = (const uint8_t*)wo; P.pf[3] = (const uint8_t*)wd;
        P.x = (const uint8_t*)x; P.w_r = (const uint8_t*)d_in[4];
        if (cudaGetSymbolAddress((void**)&P.scr, g_scr) != cudaSuccess) return;
        cudaFuncSetAttribute(fused_kernel, cudaFuncAttributeMaxDynamicSharedMemorySize, SMEM_BYTES);
        int ncl = 0, sms = 0, dev = 0;
        {
            cudaLaunchConfig_t cfg = {};
            cfg.gridDim = dim3(128); cfg.blockDim = dim3(NTHREADS); cfg.dynamicSmemBytes = SMEM_BYTES;
            cudaLaunchAttribute at[1];
            at[0].id = cudaLaunchAttributeClusterDimension;
            at[0].val.clusterDim.x = 2; at[0].val.clusterDim.y = 1; at[0].val.clusterDim.z = 1;
            cfg.attrs = at; cfg.numAttrs = 1;
            if (cudaOccupancyMaxActiveClusters(&ncl, fused_kernel, &cfg) != cudaSuccess || ncl < 64) return;
            cudaGetDevice(&dev);
            cudaDeviceGetAttribute(&sms, cudaDevAttrMultiProcessorCount, dev);
        }
        P.by_sm = sms == 132 && ncl == 66;
        grid = P.by_sm ? 132 : 128;
        static const int hg_of_pos[8] = {1, 5, 3, 0, 4, 7, 2, 6};
        int nf = 0;
        for (int t = 0; t < 66; t++) {
            int gpc, pos;
            if (!P.by_sm) { gpc = t >> 3; pos = t & 7; }
            else if (t < 32) { gpc = t & 7; pos = t >> 3; }
            else if (t < 60) { gpc = 1 + (t - 32) % 7; pos = 4 + (t - 32) / 7; }
            else if (t < 62) { gpc = 8; pos = 0; }
            else { gpc = 0; pos = t - 58; }
            const bool ffn = gpc < 8 && pos != 0 && !(pos == 1 && gpc < 2);
            P.map[t] = (uint16_t)(gpc * 8 + hg_of_pos[pos] + ((ffn ? nf++ : 127) << 8));
        }
        for (int i = 0; i < 8; i++) cached[i] = d_in[i];
        cached[8] = d_out;
    }
    fused_kernel<<<grid, NTHREADS, SMEM_BYTES>>>(P);
}
```

```cpp
#include <cuda_runtime.h>
#include <cuda_bf16.h>
#include <cuda.h>
#include <stdint.h>

namespace {

typedef __nv_bfloat16 bf16;

constexpr int SEQ = 2048, DM = 640;
constexpr int NTHREADS = 512;
constexpr int NFFN = 108;
#define LEAD 2
#define PACE0 -150
#define PACE1 950
#define PX0 1200
#define PX1 500
#define GU0 6000
#define GU1 220
#define GT0 2000
#define GT1 430
#define WOP 150
#define AUXS 500
#define EX1T 7600
#define EX2D 2200
#define SERAT 2
#define CHKJ 2
#define LDJ 4
#define YSL 200
#define ODDX 0

constexpr int ST = 47104;
constexpr int ST_BM = 16384, ST_BR = 40960;
constexpr int OFF_X = 0;
constexpr int OFF_DN = 20480;
constexpr int OFF_PART = 40960;
constexpr int OFF_G = 43008;
constexpr int OFF_WO = 63488;
constexpr int WO_SLOT = 15360;
constexpr int OFF_GU = 4 * ST;
constexpr int M_ST = OFF_GU + 40960;
constexpr int M_CS = M_ST + 1024;
constexpr int M_UPD = M_CS + 1024;
constexpr int M_TOP = M_UPD + 640;
constexpr int M_SEL = M_TOP + 64;
constexpr int B_Z = M_SEL + 16, B_G = B_Z + 8, B_AX = B_Z + 32, B_PREP = B_AX + 40, B_UPD = B_PREP + 8, B_GU = B_AX + 64, B_X = B_GU + 8, B_H = B_X + 8,
              B_SEL = B_H + 8, B_FULL = B_GU + 32, B_EMPTY = B_FULL + 32, B_HO = B_EMPTY + 32, B_WO = B_HO + 32;
constexpr int SMEM_BYTES = B_WO + 32;
static_assert(SMEM_BYTES <= 232448 && OFF_WO + 2 * WO_SLOT <= 2 * ST && OFF_WO + 5 * WO_SLOT <= 3 * ST && OFF_WO + 8 * WO_SLOT <= 4 * ST, "smem");

enum { T_X, T_W, T_WR, T_GU, T_D, T_WO, T_WOR, T_OUT, T_N };
struct Params {
    CUtensorMap tm[T_N];
    const uint8_t* x;
    const uint8_t* w_r;
    const uint8_t* w;
    const uint8_t* wo;
    const uint8_t* wd;
    uint8_t* scr;
    uint32_t up_first;
    int by_sm;
    uint16_t map[66];
};

constexpr uint32_t XB = 27392;
constexpr uint32_t G_TOP = 25600;
constexpr uint32_t G_CS = G_TOP + 1024;
constexpr uint32_t G_ST = G_CS + 128;
constexpr uint32_t G_FLAG = G_ST + 512;
constexpr uint32_t G_Y = 128 * XB;
constexpr uint32_t G_EPOCH = G_Y + 128 * 512;
static_assert(G_FLAG + 128 == XB, "scratch");
__device__ __align__(1024) uint8_t g_scr[G_EPOCH + 1024];

#define TSINIT
#define TR(v)
#define TRD(v)
#define TRW(v, i)
#define TS(i)
#define TSG(i)
constexpr unsigned SPIN = 1u << 20;

__device__ __forceinline__ void mbar_init(uint32_t bar, int cnt) {
    asm volatile("mbarrier.init.shared::cta.b64 [%0], %1;" :: "r"(bar), "r"(cnt) : "memory");
}
__device__ __forceinline__ void mbar_expect_tx(uint32_t bar, int bytes) {
    asm volatile("mbarrier.arrive.expect_tx.shared::cta.b64 _, [%0], %1;" :: "r"(bar), "r"(bytes) : "memory");
}
__device__ __forceinline__ void mbar_arrive(uint32_t bar) {
    asm volatile("mbarrier.arrive.shared::cta.b64 _, [%0];" :: "r"(bar) : "memory");
}
__device__ __forceinline__ uint32_t mapa(uint32_t a, uint32_t cta) {
    uint32_t r;
    asm("mapa.shared::cluster.u32 %0, %1, %2;" : "=r"(r) : "r"(a), "r"(cta));
    return r;
}
__device__ __forceinline__ void mbar_arrive_cl(uint32_t cbar) {
    asm volatile("mbarrier.arrive.shared::cluster.b64 _, [%0];" :: "r"(cbar) : "memory");
}
__device__ __forceinline__ void mbar_wait(uint32_t bar, int parity) {
    asm volatile("{\n.reg .pred p;\nLAB_WAIT:\nmbarrier.try_wait.parity.shared::cta.b64 p, [%0], %1;\n@!p bra LAB_WAIT;\n}"
                 :: "r"(bar), "r"(parity) : "memory");
}
__device__ __forceinline__ bool mbar_try(uint32_t bar, int parity) {
    uint32_t r;
    asm volatile("{\n.reg .pred p;\nmbarrier.test_wait.parity.shared::cta.b64 p, [%1], %2;\nselp.u32 %0, 1, 0, p;\n}"
                 : "=r"(r) : "r"(bar), "r"(parity) : "memory");
    return r != 0;
}
__device__ __forceinline__ void tma(uint32_t dst, const CUtensorMap* tm, uint32_t bar, int c0, int c1, int c2 = 0) {
    asm volatile("cp.async.bulk.tensor.3d.shared::cluster.global.mbarrier::complete_tx::bytes [%0], [%1, {%3, %4, %5}], [%2];"
                 :: "r"(dst), "l"(tm), "r"(bar), "r"(c0), "r"(c1), "r"(c2) : "memory");
}
__device__ __forceinline__ void tma_mc(uint32_t dst, const CUtensorMap* tm, uint32_t bar, int c0, int c1) {
    asm volatile("cp.async.bulk.tensor.3d.shared::cluster.global.mbarrier::complete_tx::bytes.multicast::cluster [%0], [%1, {%3, %4, %5}], [%2], %6;"
                 :: "r"(dst), "l"(tm), "r"(bar), "r"(c0), "r"(c1), "r"(0), "h"((uint16_t)3) : "memory");
}
__device__ __forceinline__ void tma_st(const CUtensorMap* tm, uint32_t src, int c0, int c1, int c2) {
    asm volatile("cp.async.bulk.tensor.3d.global.shared::cta.bulk_group [%0, {%2, %3, %4}], [%1];\ncp.async.bulk.commit_group;"
                 :: "l"(tm), "r"(src), "r"(c0), "r"(c1), "r"(c2) : "memory");
}
__device__ __forceinline__ void l2_prefetch(const void* p, int bytes) {
    asm volatile("cp.async.bulk.prefetch.L2.global [%0], %1;" :: "l"(p), "r"(bytes) : "memory");
}
__device__ __forceinline__ void cluster_arrive() { asm volatile("barrier.cluster.arrive.relaxed.aligned;" ::: "memory"); }
__device__ __forceinline__ void cluster_wait() { asm volatile("barrier.cluster.wait.aligned;" ::: "memory"); }
__device__ __forceinline__ void bar_sync(int id, int n) { asm volatile("bar.sync %0, %1;" :: "r"(id), "r"(n) : "memory"); }
__device__ __forceinline__ void bar_arrive(int id, int n) { asm volatile("bar.arrive %0, %1;" :: "r"(id), "r"(n) : "memory"); }
__device__ __forceinline__ bool bar_or(int id, int n, bool v) {
    uint32_t r;
    asm volatile("{\n.reg .pred p, q;\nsetp.ne.u32 p, %3, 0;\nbar.red.or.pred q, %1, %2, p;\nselp.u32 %0, 1, 0, q;\n}"
                 : "=r"(r) : "r"(id), "r"(n), "r"((uint32_t)v) : "memory");
    return r != 0;
}
__device__ __forceinline__ void fence_proxy_async_smem() { asm volatile("fence.proxy.async.shared::cta;" ::: "memory"); }
__device__ __forceinline__ void stg128(void* p, uint32_t a, uint32_t b, uint32_t c, uint32_t d) {
    asm volatile("{\n.reg .b64 l, h;\n.reg .b128 q;\nmov.b64 l, {%1, %2};\nmov.b64 h, {%3, %4};\nmov.b128 q, {l, h};\n"
                 "st.relaxed.gpu.global.b128 [%0], q;\n}" :: "l"(p), "r"(a), "r"(b), "r"(c), "r"(d) : "memory");
}
__device__ __forceinline__ void ldg128(const void* p, uint32_t& a, uint32_t& b, uint32_t& c, uint32_t& d) {
    asm volatile("{\n.reg .b64 l, h;\n.reg .b128 q;\nld.relaxed.gpu.global.b128 q, [%4];\nmov.b128 {l, h}, q;\n"
                 "mov.b64 {%0, %1}, l;\nmov.b64 {%2, %3}, h;\n}" : "=r"(a), "=r"(b), "=r"(c), "=r"(d) : "l"(p) : "memory");
}
__device__ __forceinline__ void stg64(void* p, uint32_t a, uint32_t b) {
    asm volatile("{\n.reg .b64 l;\nmov.b64 l, {%1, %2};\nst.relaxed.gpu.global.b64 [%0], l;\n}" :: "l"(p), "r"(a), "r"(b) : "memory");
}
__device__ __forceinline__ void red4(void* p, float a, float b) {
    asm volatile("red.relaxed.gpu.global.add.v4.f32 [%0], {%1, %2, %3, %3};" :: "l"(p), "f"(a), "f"(b), "f"(1.0f) : "memory");
}
__device__ __forceinline__ void stg32(void* p, uint32_t a) {
    asm volatile("st.relaxed.gpu.global.u32 [%0], %1;" :: "l"(p), "r"(a) : "memory");
}
__device__ __forceinline__ uint2 ldg64(const void* p) {
    uint2 v;
    asm volatile("{\n.reg .b64 l;\nld.relaxed.gpu.global.b64 l, [%2];\nmov.b64 {%0, %1}, l;\n}" : "=r"(v.x), "=r"(v.y) : "l"(p) : "memory");
    return v;
}
__device__ __forceinline__ unsigned ldg32(const void* p) {
    unsigned v;
    asm volatile("ld.relaxed.gpu.global.u32 %0, [%1];" : "=r"(v) : "l"(p) : "memory");
    return v;
}
__device__ __forceinline__ void ldsm_x4(uint32_t (&r)[4], uint32_t a) {
    asm volatile("ldmatrix.sync.aligned.m8n8.x4.shared.b16 {%0,%1,%2,%3}, [%4];"
                 : "=r"(r[0]), "=r"(r[1]), "=r"(r[2]), "=r"(r[3]) : "r"(a));
}
__device__ __forceinline__ void ldsm_x4_t(uint32_t (&r)[4], uint32_t a) {
    asm volatile("ldmatrix.sync.aligned.m8n8.x4.trans.shared.b16 {%0,%1,%2,%3}, [%4];"
                 : "=r"(r[0]), "=r"(r[1]), "=r"(r[2]), "=r"(r[3]) : "r"(a));
}
__device__ __forceinline__ void stsm_x4(uint32_t a, const uint32_t (&r)[4]) {
    asm volatile("stmatrix.sync.aligned.m8n8.x4.shared.b16 [%0], {%1,%2,%3,%4};"
                 :: "r"(a), "r"(r[0]), "r"(r[1]), "r"(r[2]), "r"(r[3]));
}
__device__ __forceinline__ uint32_t movm(uint32_t a) {
    uint32_t d;
    asm("movmatrix.sync.aligned.m8n8.trans.b16 %0, %1;" : "=r"(d) : "r"(a));
    return d;
}
__device__ __forceinline__ void mma16816(float (&c)[4], uint32_t a0, uint32_t a1, uint32_t a2, uint32_t a3, uint32_t b0, uint32_t b1) {
    asm("mma.sync.aligned.m16n8k16.row.col.f32.bf16.bf16.f32 {%0,%1,%2,%3}, {%4,%5,%6,%7}, {%8,%9}, {%0,%1,%2,%3};"
        : "+f"(c[0]), "+f"(c[1]), "+f"(c[2]), "+f"(c[3]) : "r"(a0), "r"(a1), "r"(a2), "r"(a3), "r"(b0), "r"(b1));
}
__device__ __forceinline__ void mma1688(float (&c)[4], uint32_t a0, uint32_t a1, uint32_t b0) {
    asm("mma.sync.aligned.m16n8k8.row.col.f32.bf16.bf16.f32 {%0,%1,%2,%3}, {%4,%5}, {%6}, {%0,%1,%2,%3};"
        : "+f"(c[0]), "+f"(c[1]), "+f"(c[2]), "+f"(c[3]) : "r"(a0), "r"(a1), "r"(b0));
}
__device__ __forceinline__ void wgmma_fence() { asm volatile("wgmma.fence.sync.aligned;" ::: "memory"); }
__device__ __forceinline__ void wgmma_commit() { asm volatile("wgmma.commit_group.sync.aligned;" ::: "memory"); }
template <int N> __device__ __forceinline__ void wgmma_wait() { asm volatile("wgmma.wait_group.sync.aligned %0;" :: "n"(N) : "memory"); }
__device__ __forceinline__ uint64_t mk(uint32_t lo, uint32_t hi) { return (uint64_t)lo | ((uint64_t)hi << 32); }
constexpr uint32_t HI128 = (1024 >> 4) | (1u << 30), HI64 = (512 >> 4) | (2u << 30), HI32 = (256 >> 4) | (3u << 30);
__device__ __forceinline__ uint32_t pack_bf16(float lo, float hi) {
    uint32_t r;
    asm("cvt.rn.bf16x2.f32 %0, %1, %2;" : "=r"(r) : "f"(hi), "f"(lo));
    return r;
}
__device__ __forceinline__ float bflo(uint32_t u) { return __uint_as_float(u << 16); }
__device__ __forceinline__ float bfhi(uint32_t u) { return __uint_as_float(u & 0xFFFF0000u); }
__device__ __forceinline__ float bf16r(float v) { return __uint_as_float(pack_bf16(0.f, v)); }
__device__ __forceinline__ float ex2(float v) { float r; asm("ex2.approx.ftz.f32 %0, %1;" : "=f"(r) : "f"(v)); return r; }
__device__ __forceinline__ float rcp(float v) { float r; asm("rcp.approx.ftz.f32 %0, %1;" : "=f"(r) : "f"(v)); return r; }
__device__ __forceinline__ float sqrt_a(float v) { float r; asm("sqrt.approx.ftz.f32 %0, %1;" : "=f"(r) : "f"(v)); return r; }
__device__ __forceinline__ float tanh_a(float v) { float r; asm("tanh.approx.f32 %0, %1;" : "=f"(r) : "f"(v)); return r; }
constexpr float LOG2E = 1.4426950408889634f;
__device__ __forceinline__ float sigm(float v) { return rcp(1.0f + ex2(-LOG2E * v)); }
__device__ __forceinline__ uint4 lds128(uint32_t a) {
    uint4 v;
    asm volatile("ld.shared.v4.u32 {%0,%1,%2,%3}, [%4];" : "=r"(v.x), "=r"(v.y), "=r"(v.z), "=r"(v.w) : "r"(a));
    return v;
}
__device__ __forceinline__ float4 lds128f(uint32_t a) {
    float4 v;
    asm volatile("ld.shared.v4.f32 {%0,%1,%2,%3}, [%4];" : "=f"(v.x), "=f"(v.y), "=f"(v.z), "=f"(v.w) : "r"(a));
    return v;
}
__device__ __forceinline__ float2 lds64f(uint32_t a) {
    float2 v;
    asm volatile("ld.shared.v2.f32 {%0,%1}, [%2];" : "=f"(v.x), "=f"(v.y) : "r"(a));
    return v;
}
__device__ __forceinline__ uint32_t lds32(uint32_t a) {
    uint32_t v;
    asm volatile("ld.shared.u32 %0, [%1];" : "=r"(v) : "r"(a));
    return v;
}
__device__ __forceinline__ void sts128(uint32_t a, uint32_t x, uint32_t y, uint32_t z, uint32_t w) {
    asm volatile("st.shared.v4.u32 [%0], {%1,%2,%3,%4};" :: "r"(a), "r"(x), "r"(y), "r"(z), "r"(w) : "memory");
}
__device__ __forceinline__ void sts64(uint32_t a, uint32_t x, uint32_t y) {
    asm volatile("st.shared.v2.u32 [%0], {%1,%2};" :: "r"(a), "r"(x), "r"(y) : "memory");
}
__device__ __forceinline__ void sts32(uint32_t a, uint32_t x) { asm volatile("st.shared.u32 [%0], %1;" :: "r"(a), "r"(x) : "memory"); }
__device__ __forceinline__ unsigned redux_max(unsigned v) {
    unsigned r;
    asm volatile("redux.sync.max.u32 %0, %1, 0xffffffff;" : "=r"(r) : "r"(v));
    return r;
}
__device__ __forceinline__ float shx(float v, int o) { return __shfl_xor_sync(0xffffffffu, v, o); }
__device__ __forceinline__ uint32_t U(float v) { return __float_as_uint(v); }
__device__ __forceinline__ float F(uint32_t v) { return __uint_as_float(v); }

__device__ __forceinline__ void wgmma_n192_lo(float (&d)[120], uint64_t da, uint64_t db, int scale_d) {
    asm volatile("{\n.reg .pred p;\nsetp.ne.b32 p, %98, 0;\n"
        "wgmma.mma_async.sync.aligned.m64n192k16.f32.bf16.bf16 "
        "{%0, %1, %2, %3, %4, %5, %6, %7, %8, %9, %10, %11, %12, %13, %14, %15, "
        "%16, %17, %18, %19, %20, %21, %22, %23, %24, %25, %26, %27, %28, %29, %30, %31, "
        "%32, %33, %34, %35, %36, %37, %38, %39, %40, %41, %42, %43, %44, %45, %46, %47, "
        "%48, %49, %50, %51, %52, %53, %54, %55, %56, %57, %58, %59, %60, %61, %62, %63, "
        "%64, %65, %66, %67, %68, %69, %70, %71, %72, %73, %74, %75, %76, %77, %78, %79, "
        "%80, %81, %82, %83, %84, %85, %86, %87, %88, %89, %90, %91, %92, %93, %94, %95}, "
        "%96, %97, p, 1, 1, 0, 1;\n}\n"
        : "+f"(d[0]), "+f"(d[1]), "+f"(d[2]), "+f"(d[3]), "+f"(d[4]), "+f"(d[5]), "+f"(d[6]), "+f"(d[7]),
          "+f"(d[8]), "+f"(d[9]), "+f"(d[10]), "+f"(d[11]), "+f"(d[12]), "+f"(d[13]), "+f"(d[14]), "+f"(d[15]),
          "+f"(d[16]), "+f"(d[17]), "+f"(d[18]), "+f"(d[19]), "+f"(d[20]), "+f"(d[21]), "+f"(d[22]), "+f"(d[23]),
          "+f"(d[24]), "+f"(d[25]), "+f"(d[26]), "+f"(d[27]), "+f"(d[28]), "+f"(d[29]), "+f"(d[30]), "+f"(d[31]),
          "+f"(d[32]), "+f"(d[33]), "+f"(d[34]), "+f"(d[35]), "+f"(d[36]), "+f"(d[37]), "+f"(d[38]), "+f"(d[39]),
          "+f"(d[40]), "+f"(d[41]), "+f"(d[42]), "+f"(d[43]), "+f"(d[44]), "+f"(d[45]), "+f"(d[46]), "+f"(d[47]),
          "+f"(d[48]), "+f"(d[49]), "+f"(d[50]), "+f"(d[51]), "+f"(d[52]), "+f"(d[53]), "+f"(d[54]), "+f"(d[55]),
          "+f"(d[56]), "+f"(d[57]), "+f"(d[58]), "+f"(d[59]), "+f"(d[60]), "+f"(d[61]), "+f"(d[62]), "+f"(d[63]),
          "+f"(d[64]), "+f"(d[65]), "+f"(d[66]), "+f"(d[67]), "+f"(d[68]), "+f"(d[69]), "+f"(d[70]), "+f"(d[71]),
          "+f"(d[72]), "+f"(d[73]), "+f"(d[74]), "+f"(d[75]), "+f"(d[76]), "+f"(d[77]), "+f"(d[78]), "+f"(d[79]),
          "+f"(d[80]), "+f"(d[81]), "+f"(d[82]), "+f"(d[83]), "+f"(d[84]), "+f"(d[85]), "+f"(d[86]), "+f"(d[87]),
          "+f"(d[88]), "+f"(d[89]), "+f"(d[90]), "+f"(d[91]), "+f"(d[92]), "+f"(d[93]), "+f"(d[94]), "+f"(d[95])
        : "l"(da), "l"(db), "r"(scale_d));
}
__device__ __forceinline__ void wgmma_n48_hi(float (&d)[120], uint64_t da, uint64_t db, int scale_d) {
    asm volatile("{\n.reg .pred p;\nsetp.ne.b32 p, %26, 0;\n"
        "wgmma.mma_async.sync.aligned.m64n48k16.f32.bf16.bf16 "
        "{%0, %1, %2, %3, %4, %5, %6, %7, %8, %9, %10, %11, %12, %13, %14, %15, "
        "%16, %17, %18, %19, %20, %21, %22, %23}, "
        "%24, %25, p, 1, 1, 0, 1;\n}\n"
        : "+f"(d[96]), "+f"(d[97]), "+f"(d[98]), "+f"(d[99]), "+f"(d[100]), "+f"(d[101]), "+f"(d[102]), "+f"(d[103]),
          "+f"(d[104]), "+f"(d[105]), "+f"(d[106]), "+f"(d[107]), "+f"(d[108]), "+f"(d[109]), "+f"(d[110]), "+f"(d[111]),
          "+f"(d[112]), "+f"(d[113]), "+f"(d[114]), "+f"(d[115]), "+f"(d[116]), "+f"(d[117]), "+f"(d[118]), "+f"(d[119])
        : "l"(da), "l"(db), "r"(scale_d));
}
__device__ __forceinline__ void wgmma_rs_n80(float (&d)[40], uint32_t a0, uint32_t a1, uint32_t a2, uint32_t a3, uint64_t db, int scale_d) {
    asm volatile("{\n.reg .pred p;\nsetp.ne.b32 p, %45, 0;\n"
        "wgmma.mma_async.sync.aligned.m64n80k16.f32.bf16.bf16 "
        "{%0, %1, %2, %3, %4, %5, %6, %7, %8, %9, %10, %11, %12, %13, %14, %15, "
        "%16, %17, %18, %19, %20, %21, %22, %23, %24, %25, %26, %27, %28, %29, %30, %31, "
        "%32, %33, %34, %35, %36, %37, %38, %39}, "
        "{%40, %41, %42, %43}, %44, p, 1, 1, 1;\n}\n"
        : "+f"(d[0]), "+f"(d[1]), "+f"(d[2]), "+f"(d[3]), "+f"(d[4]), "+f"(d[5]), "+f"(d[6]), "+f"(d[7]),
          "+f"(d[8]), "+f"(d[9]), "+f"(d[10]), "+f"(d[11]), "+f"(d[12]), "+f"(d[13]), "+f"(d[14]), "+f"(d[15]),
          "+f"(d[16]), "+f"(d[17]), "+f"(d[18]), "+f"(d[19]), "+f"(d[20]), "+f"(d[21]), "+f"(d[22]), "+f"(d[23]),
          "+f"(d[24]), "+f"(d[25]), "+f"(d[26]), "+f"(d[27]), "+f"(d[28]), "+f"(d[29]), "+f"(d[30]), "+f"(d[31]),
          "+f"(d[32]), "+f"(d[33]), "+f"(d[34]), "+f"(d[35]), "+f"(d[36]), "+f"(d[37]), "+f"(d[38]), "+f"(d[39])
        : "r"(a0), "r"(a1), "r"(a2), "r"(a3), "l"(db), "r"(scale_d));
}
__device__ __forceinline__ void wgmma_rs_n192_lo(float (&d)[120], uint32_t a0, uint32_t a1, uint32_t a2, uint32_t a3, uint64_t db, int scale_d) {
    asm volatile("{\n.reg .pred p;\nsetp.ne.b32 p, %101, 0;\n"
        "wgmma.mma_async.sync.aligned.m64n192k16.f32.bf16.bf16 "
        "{%0, %1, %2, %3, %4, %5, %6, %7, %8, %9, %10, %11, %12, %13, %14, %15, "
        "%16, %17, %18, %19, %20, %21, %22, %23, %24, %25, %26, %27, %28, %29, %30, %31, "
        "%32, %33, %34, %35, %36, %37, %38, %39, %40, %41, %42, %43, %44, %45, %46, %47, "
        "%48, %49, %50, %51, %52, %53, %54, %55, %56, %57, %58, %59, %60, %61, %62, %63, "
        "%64, %65, %66, %67, %68, %69, %70, %71, %72, %73, %74, %75, %76, %77, %78, %79, "
        "%80, %81, %82, %83, %84, %85, %86, %87, %88, %89, %90, %91, %92, %93, %94, %95}, "
        "{%96, %97, %98, %99}, %100, p, 1, 1, 1;\n}\n"
        : "+f"(d[0]), "+f"(d[1]), "+f"(d[2]), "+f"(d[3]), "+f"(d[4]), "+f"(d[5]), "+f"(d[6]), "+f"(d[7]),
          "+f"(d[8]), "+f"(d[9]), "+f"(d[10]), "+f"(d[11]), "+f"(d[12]), "+f"(d[13]), "+f"(d[14]), "+f"(d[15]),
          "+f"(d[16]), "+f"(d[17]), "+f"(d[18]), "+f"(d[19]), "+f"(d[20]), "+f"(d[21]), "+f"(d[22]), "+f"(d[23]),
          "+f"(d[24]), "+f"(d[25]), "+f"(d[26]), "+f"(d[27]), "+f"(d[28]), "+f"(d[29]), "+f"(d[30]), "+f"(d[31]),
          "+f"(d[32]), "+f"(d[33]), "+f"(d[34]), "+f"(d[35]), "+f"(d[36]), "+f"(d[37]), "+f"(d[38]), "+f"(d[39]),
          "+f"(d[40]), "+f"(d[41]), "+f"(d[42]), "+f"(d[43]), "+f"(d[44]), "+f"(d[45]), "+f"(d[46]), "+f"(d[47]),
          "+f"(d[48]), "+f"(d[49]), "+f"(d[50]), "+f"(d[51]), "+f"(d[52]), "+f"(d[53]), "+f"(d[54]), "+f"(d[55]),
          "+f"(d[56]), "+f"(d[57]), "+f"(d[58]), "+f"(d[59]), "+f"(d[60]), "+f"(d[61]), "+f"(d[62]), "+f"(d[63]),
          "+f"(d[64]), "+f"(d[65]), "+f"(d[66]), "+f"(d[67]), "+f"(d[68]), "+f"(d[69]), "+f"(d[70]), "+f"(d[71]),
          "+f"(d[72]), "+f"(d[73]), "+f"(d[74]), "+f"(d[75]), "+f"(d[76]), "+f"(d[77]), "+f"(d[78]), "+f"(d[79]),
          "+f"(d[80]), "+f"(d[81]), "+f"(d[82]), "+f"(d[83]), "+f"(d[84]), "+f"(d[85]), "+f"(d[86]), "+f"(d[87]),
          "+f"(d[88]), "+f"(d[89]), "+f"(d[90]), "+f"(d[91]), "+f"(d[92]), "+f"(d[93]), "+f"(d[94]), "+f"(d[95])
        : "r"(a0), "r"(a1), "r"(a2), "r"(a3), "l"(db), "r"(scale_d));
}
__device__ __forceinline__ void wgmma_rs_n48_hi(float (&d)[120], uint32_t a0, uint32_t a1, uint32_t a2, uint32_t a3, uint64_t db, int scale_d) {
    asm volatile("{\n.reg .pred p;\nsetp.ne.b32 p, %29, 0;\n"
        "wgmma.mma_async.sync.aligned.m64n48k16.f32.bf16.bf16 "
        "{%0, %1, %2, %3, %4, %5, %6, %7, %8, %9, %10, %11, %12, %13, %14, %15, "
        "%16, %17, %18, %19, %20, %21, %22, %23}, "
        "{%24, %25, %26, %27}, %28, p, 1, 1, 1;\n}\n"
        : "+f"(d[96]), "+f"(d[97]), "+f"(d[98]), "+f"(d[99]), "+f"(d[100]), "+f"(d[101]), "+f"(d[102]), "+f"(d[103]),
          "+f"(d[104]), "+f"(d[105]), "+f"(d[106]), "+f"(d[107]), "+f"(d[108]), "+f"(d[109]), "+f"(d[110]), "+f"(d[111]),
          "+f"(d[112]), "+f"(d[113]), "+f"(d[114]), "+f"(d[115]), "+f"(d[116]), "+f"(d[117]), "+f"(d[118]), "+f"(d[119])
        : "r"(a0), "r"(a1), "r"(a2), "r"(a3), "l"(db), "r"(scale_d));
}
__device__ __forceinline__ void wgmma_n8(float (&d)[4], uint64_t da, uint64_t db, int scale_d) {
    asm volatile("{\n.reg .pred p;\nsetp.ne.b32 p, %6, 0;\n"
                 "wgmma.mma_async.sync.aligned.m64n8k16.f32.bf16.bf16 {%0, %1, %2, %3}, %4, %5, p, 1, 1, 1, 0;\n}\n"
                 : "+f"(d[0]), "+f"(d[1]), "+f"(d[2]), "+f"(d[3]) : "l"(da), "l"(db), "r"(scale_d));
}
__device__ __forceinline__ constexpr int jt_of(int sec, int c) { return c < 8 ? sec * 8 + c : 24 + sec * 2 + (c - 8); }

__device__ __forceinline__ bool elect() {
    uint32_t r;
    asm volatile("{\n.reg .pred p;\nelect.sync _|p, 0xffffffff;\nselp.u32 %0, 1, 0, p;\n}" : "=r"(r));
    return r != 0;
}
__device__ __forceinline__ uint32_t clock32() { uint32_t r; asm volatile("mov.u32 %0, %%clock;" : "=r"(r)); return r; }
#define BLOCK_SPLIT(v) asm volatile("{\n.reg .pred p;\nLAB_SPLIT:\nsetp.eq.u32 p, %0, 0;\n@p nanosleep.u32 1;\n@p bra LAB_SPLIT;\n}" :: "r"(v) : "memory")
__device__ __forceinline__ bool any(bool v) { return __any_sync(0xffffffffu, v); }
__device__ __forceinline__ bool retry(unsigned& spins) { __nanosleep(100); return ++spins < SPIN; }
__device__ __forceinline__ uint32_t opaque_tid() { uint32_t r; asm volatile("mov.u32 %0, %%tid.x;" : "=r"(r)); return r; }

__global__ void __cluster_dims__(2, 1, 1) __launch_bounds__(NTHREADS, 1)
fused_kernel(const __grid_constant__ Params P) {
    extern __shared__ __align__(1024) uint8_t smem[];
    const uint32_t sb = (uint32_t)__cvta_generic_to_shared(smem);
    const uint32_t warp = __shfl_sync(0xffffffffu, threadIdx.x >> 5, 0);
    const uint32_t rank = blockIdx.x & 1;
    uint32_t me;
    asm("mov.u32 %0, %%smid;" : "=r"(me));
    me = P.map[(P.by_sm ? me : blockIdx.x) >> 1];
    constexpr uint32_t sbd = 1024 >> 4;
    if ((sb & 0xFFFFFF) != 1024) __trap();
    if (me & 0x40) {
        __nanosleep(2000);
        return;
    }
    const uint32_t hg = me & 7, rb = ((me >> 2) & 14) | rank, fp = me >> 8;
    const uint32_t b = rb * 8 + hg;
    const uint32_t k0 = (((hg >> 2) ^ (rb >> 1)) & 1) * 320;

    if (warp < 2 && elect()) asm volatile("prefetch.tensormap [%0];" :: "l"(&P.tm[T_W + warp]) : "memory");
    TSINIT;
    TS(0); TSG(1);
    if (warp >= 8 && elect()) {
        const uint32_t bb = sb + B_Z - 256 + warp * 32;
        const int cnt = ((0x0FF00772u >> (4 * (warp - 8))) & 15) + 1;
        mbar_init(bb, cnt); mbar_init(bb + 8, cnt); mbar_init(bb + 16, cnt); mbar_init(bb + 24, cnt);
        if (warp == 11) { mbar_expect_tx(sb + B_H, 1024); mbar_expect_tx(sb + B_GU, 40960); }
        asm volatile("fence.mbarrier_init.release.cluster;" ::: "memory");
    }
    __syncwarp();
    cluster_arrive();

    if (warp < 8) {
        asm volatile("setmaxnreg.inc.sync.aligned.u32 208;");
        const uint32_t lane = opaque_tid() & 31, g = lane >> 2, t = lane & 3;
        const uint32_t p = warp >> 2, w = warp & 3;
        const uint32_t empty_cl = mapa(sb + B_EMPTY, lane & 1);
        uint8_t* const orow = P.scr + (rb * (8 * XB) + warp * 2560 + lane * 16);
        const uint32_t ta = sb + warp * 2560 + (lane & 15) * 160 + (lane >> 4) * 16;
        uint32_t A[7][20];
        TRD(r12); TRD(r26); TRD(r28); TRD(r32); TRD(r34); TRD(r61); TRD(r20); TRD(r21); TRD(r22); TRD(r42); TRD(r44);
        uint32_t par;
        uint8_t* const halo = orow + (hg * XB + (8 + p - warp) * 2560);
        uint8_t* const flag = P.scr + (G_FLAG + b * XB + w * 8 + p * 4);
        cluster_wait();
        {
            float acc[120];
            bool ok;
            uint32_t xr[5][4];
            float2 s0, s1;
            const uint32_t xa = sb + (warp * 16 + (lane & 15)) * 128 + (((lane >> 4) ^ (lane & 7)) << 4);
            mbar_wait(sb + B_FULL + 16, 0);
#pragma unroll
            for (uint32_t kb = 2; kb < 12; kb++) {
                const uint32_t s = kb & 3;
                const bool hold = kb == 12 - LEAD && p;
                if (hold) {
                    wgmma_wait<0>();
                    if (lane < 2) mbar_arrive_cl(empty_cl + 8 * ((11 - LEAD) & 3));
                    bar_sync(1, 256);
                }
                TS(kb);
                wgmma_fence();
                const uint32_t st = sbd + s * (ST >> 4);
#pragma unroll
                for (int ks = 0; ks < 4; ks++) {
                    const uint64_t da = mk(st + p * 512 + ks * 2 + 0x10000, HI128);
                    wgmma_n48_hi(acc, da, mk(st + (ST_BR >> 4) + (ks >> 1) * 192 + (ks & 1) * 32 + (64 << 16), HI32), ks || kb > 2);
                    wgmma_n192_lo(acc, da, mk(st + (ST_BM >> 4) + (ks >> 1) * 768 + (ks & 1) * 128 + (256 << 16), HI128), ks || kb > 2);
                    if (ks == 0) {
                        wgmma_commit();
                        wgmma_wait<1>();
                        if (!hold && kb > 2 && lane < 2) mbar_arrive_cl(empty_cl + 8 * ((kb - 1) & 3));
                    }
                    if (ks == 1) {
#pragma unroll
                        for (uint32_t j = 0; j < 5; j++)
                            if (((5 * hg + j) >> 2) == kb - 2 + (kb < 7 ? k0 >> 6 : -(k0 >> 6))) ldsm_x4(xr[j], (xa + s * ST) ^ (((hg + j) & 3) << 5));
                        if (w == 3 && kb < 7) stg128(halo + (kb - 2) * 512, 0u, 0u, 0u, 0u);
                        if (lane == 0 && kb == 2) stg32(flag, 0u);
                        if (kb < 11) ok = mbar_try(sb + B_FULL + 8 * ((kb + 1) & 3), ((kb - 1) >> 2) & 1);
                        if (kb == 11) {
                            ok = mbar_try(sb + B_PREP, 0);
                            s0 = lds64f(sb + M_ST + (warp * 16 + g) * 8); s1 = lds64f(sb + M_ST + (warp * 16 + g + 8) * 8);
                            par = lds32(sb + M_SEL + 8);
                        }
                    }
                }
                wgmma_commit();
                if (kb < 11 && !ok) mbar_wait(sb + B_FULL + 8 * ((kb + 1) & 3), ((kb - 1) >> 2) & 1);
            }
            if (!ok) {
                mbar_wait(sb + B_PREP, 0);
                s0 = lds64f(sb + M_ST + (warp * 16 + g) * 8); s1 = lds64f(sb + M_ST + (warp * 16 + g + 8) * 8);
                par = lds32(sb + M_SEL + 8);
            }
            {
                const uint32_t a0 = t ? 0u : __byte_perm(U(-s0.y), 0, 0x3232), a1 = t ? 0u : __byte_perm(U(-s1.y), 0, 0x3232);
                wgmma_fence();
                wgmma_rs_n48_hi(acc, a0, a1, 0u, 0u, mk(sbd + (M_CS >> 4) + 48, 2), 1);
                wgmma_rs_n192_lo(acc, a0, a1, 0u, 0u, mk(sbd + (M_CS >> 4), 2), 1);
                wgmma_commit();
            }
            if (!p) bar_arrive(1, 256);
            wgmma_wait<0>();
#pragma unroll
            for (int i = 0; i < 120; i++) asm volatile("" : "+f"(acc[i]) :: "memory");
            if (lane < 2) mbar_arrive_cl(empty_cl + 24);
            TR(r12);
            uint32_t Q[10], Ql[10], KX[10], VX[10], Y[20];
#define KI(c) ((c) == 2 ? 8 : (c) == 7 ? 9 : (c) - ((c) > 2) - ((c) > 7))
#define KY(c) Y[KI(c)]
#define VY(c) Y[10 + (c)]
            uint32_t Z[20];
            const bool start = w == 0 && rb == 0, remote = w == 0 && rb != 0;
            const uint32_t slot = sb + OFF_G + warp * 2560 + lane * 16;
            {
#pragma unroll
                for (int c = 0; c < 10; c++) {
                    const int jk = jt_of(1, c), jv = jt_of(2, c);
                    VY(c) = movm(pack_bf16(acc[4 * jv + 2] * s1.x, acc[4 * jv + 3] * s1.x));
                    KY(c) = pack_bf16(acc[4 * jk + 2] * s1.x, acc[4 * jk + 3] * s1.x);
                }
                if (w == 3) {
#pragma unroll
                    for (int j = 0; j < 5; j++) {
                        Y[4 * j] = (Y[4 * j] & ~0x10001u) | par;
                        stg128(halo + j * 512, Y[4 * j], Y[4 * j + 1], Y[4 * j + 2], Y[4 * j + 3]);
                    }
                } else {
                    mbar_wait(sb + B_EMPTY + 8, 1);
#pragma unroll
                    for (int j = 0; j < 5; j++) sts128(slot + 2560 + j * 512, Y[4 * j], Y[4 * j + 1], Y[4 * j + 2], Y[4 * j + 3]);
                }
                TR(r26);
#pragma unroll
                for (int c = 0; c < 10; c++) {
                    const int jk = jt_of(1, c), jv = jt_of(2, c);
                    KX[c] = pack_bf16(acc[4 * jk] * s0.x, acc[4 * jk + 1] * s0.x);
                    VX[c] = movm(pack_bf16(acc[4 * jv] * s0.x, acc[4 * jv + 1] * s0.x));
                    asm volatile("" : "+r"(KX[c]), "+r"(VX[c]));
                }
                BLOCK_SPLIT(par);
                bar_sync(2 + p, 128);
                TR(r28);
                if (remote) {
#pragma unroll
                    for (int j = 0; j < 5; j++) ldg128(halo - 8 * XB + j * 512, Z[4 * j], Z[4 * j + 1], Z[4 * j + 2], Z[4 * j + 3]);
                } else {
#pragma unroll
                    for (int j = 0; j < 5; j++) {
                        const uint4 v = lds128(slot + (w ? 0 : 2560) + j * 512);
                        Z[4 * j] = v.x; Z[4 * j + 1] = v.y; Z[4 * j + 2] = v.z; Z[4 * j + 3] = v.w;
                    }
                }
#pragma unroll
                for (int c = 0; c < 10; c++) {
                    const int jq = jt_of(0, c);
                    Ql[c] = pack_bf16(acc[4 * jq], acc[4 * jq + 1]);
                    Q[c] = pack_bf16(acc[4 * jq + 2], acc[4 * jq + 3]);
                    asm volatile("" : "+r"(Ql[c]), "+r"(Q[c]));
                }
            }
            auto unit = [&](const uint32_t (&q)[10], const uint32_t (&z)[20], const int c0, const uint32_t mx, const float sq, const float nz, const int h) {
                const uint32_t qa = t < 2 ? q[c0 + 2] : 0u, qb = t < 2 ? 0u : q[c0 + 2];
                float xa[4] = {0.f, 0.f, 0.f, 0.f}, za[4] = {0.f, 0.f, 0.f, 0.f}, xb[4], zb[4];
                mma1688(xa, qa, qb, KX[c0 + 2]);
                mma1688(za, qa, qb, z[KI(c0 + 2)]);
#pragma unroll
                for (int e = 0; e < 4; e++) { xb[e] = xa[e]; zb[e] = za[e]; }
                mma16816(xa, q[c0], q[c0 + 3], q[c0 + 1], q[c0 + 4], KX[c0], KX[c0 + 1]);
                mma16816(za, q[c0], q[c0 + 3], q[c0 + 1], q[c0 + 4], z[KI(c0)], z[KI(c0 + 1)]);
                mma16816(xb, q[c0], q[c0 + 3], q[c0 + 1], q[c0 + 4], KX[c0 + 3], KX[c0 + 4]);
                mma16816(zb, q[c0], q[c0 + 3], q[c0 + 1], q[c0 + 4], z[KI(c0 + 3)], z[KI(c0 + 4)]);
                const bool h0 = mx & 1u, h1 = (int)mx < 0;
                const float l00 = h0 ? xa[0] : za[0] + nz, l01 = h1 ? xa[1] : za[1] + nz;
                const float l10 = h0 ? xb[2] : zb[2] + nz, l11 = h1 ? xb[3] : zb[3] + nz;
                float m0 = fmaxf(l00, l01), m1 = fmaxf(l10, l11);
                m0 = fmaxf(m0, shx(m0, 1)); m1 = fmaxf(m1, shx(m1, 1));
                m0 = fmaxf(m0, shx(m0, 2)) * -sq; m1 = fmaxf(m1, shx(m1, 2)) * -sq;
                const uint32_t pa = pack_bf16(ex2(fmaf(l00, sq, m0)), ex2(fmaf(l01, sq, m0)));
                const uint32_t pb = pack_bf16(ex2(fmaf(l10, sq, m1)), ex2(fmaf(l11, sq, m1)));
                float dn[4] = {0.f, 0.f, 0.f, 0.f};
                mma1688(dn, pa, pb, 0x3F803F80u);
                const float i0 = rcp(dn[0]), i1 = rcp(dn[2]), i2 = t < 2 ? i0 : i1;
#pragma unroll
                for (int c = 0; c < 5; c++) {
                    float oc[4] = {0.f, 0.f, 0.f, 0.f};
                    mma16816(oc, pa & mx, pb & mx, pa & ~mx, pb & ~mx, VX[c0 + c], z[10 + c0 + c]);
                    const bool first = c < 2 || (c == 2 && t < 2);
                    const float iv = c < 2 ? i0 : (c > 2 ? i1 : i2);
                    A[0][2 * (c0 + c) + h] = pack_bf16((first ? oc[0] : oc[2]) * iv, (first ? oc[1] : oc[3]) * iv);
                }
            };
            const uint32_t mo = (2 * t > g ? 0xFFFFu : 0u) | (2 * t + 1 > g ? 0xFFFF0000u : 0u);
            constexpr float SC = 0.22360679774997896f * LOG2E;
            {
                unsigned spins = 0;
#pragma unroll 1
                while (remote && any((Z[0] & Z[4] & Z[8] & Z[12] & Z[16] & par) == 0u) && ++spins < SPIN) {
#pragma unroll
                    for (int j = 0; j < 5; j++) ldg128(halo - 8 * XB + j * 512, Z[4 * j], Z[4 * j + 1], Z[4 * j + 2], Z[4 * j + 3]);
                }
                TR(r32);
                const float nz = start ? -INFINITY : 0.f;
                unit(Q, Y, 0, mo, s1.x * SC, 0.f, 1);
                unit(Q, Y, 5, mo, s1.x * SC, 0.f, 1);
                unit(Ql, Z, 0, ~mo, s0.x * SC, nz, 0);
                unit(Ql, Z, 5, ~mo, s0.x * SC, nz, 0);
            }
#pragma unroll
            for (int j = 0; j < 5; j++) {
                A[0][4 * j] = (A[0][4 * j] & ~0x10001u) | par;
                stg128(orow + hg * XB + j * 512, A[0][4 * j], A[0][4 * j + 1], A[0][4 * j + 2], A[0][4 * j + 3]);
            }
            if (lane == 0) stg32(flag, par);
            TR(r34);
            if (p) bar_arrive(8, 384);
            BLOCK_SPLIT(par);
            {
                const float r0 = 0.5f * s0.x, r1 = 0.5f * s1.x, n0 = -r0 * s0.y, n1 = -r1 * s1.y;
#pragma unroll
                for (int j = 0; j < 5; j++) {
                    uint32_t gf[4];
#pragma unroll
                    for (int q = 0; q < 4; q++) {
                        const float v0 = fmaf(bflo(xr[j][q]), q & 1 ? r1 : r0, q & 1 ? n1 : n0), v1 = fmaf(bfhi(xr[j][q]), q & 1 ? r1 : r0, q & 1 ? n1 : n0);
                        gf[q] = pack_bf16(fmaf(v0, tanh_a(v0), v0), fmaf(v1, tanh_a(v1), v1));
                    }
                    stsm_x4(ta + OFF_G + j * 32, gf);
                    stsm_x4(ta + OFF_X + j * 32, xr[j]);
                }
            }
            TR(r61);
        }
        {
            float acc2[40];
            unsigned spins = 0;
            bool again, first = true;
            const uint8_t* src[7];
#pragma unroll
            for (uint32_t i = 0; i < 7; i++) { src[i] = orow + (i >= hg ? XB : 0u); asm volatile("" : "+l"(src[i])); }
            uint32_t a0 = ta + (hg & 1) * 32, a4 = ta + (~hg & 1) * 128;
            asm volatile("" : "+r"(a0), "+r"(a4));
            mbar_wait(sb + B_SEL, 0);
            const float2 sel = lds64f(sb + M_SEL);
            uint32_t routed = (U(sel.x) >> 4) == warp || (U(sel.y) >> 4) == warp;
            asm volatile("" : "+r"(routed));
            uint32_t xf[5][4], gf[5][4];
            BLOCK_SPLIT(par);
            TR(r20);
            if (p) bar_sync(9, 288); else bar_sync(5, 160);
#pragma unroll 1
            do {
#pragma unroll
                for (uint32_t i = 1; i < 7; i++)
#pragma unroll
                    for (int j = 0; j < 5; j++)
                        ldg128(src[i - 1] + (i - 1) * XB + j * 512, A[i][4 * j], A[i][4 * j + 1], A[i][4 * j + 2], A[i][4 * j + 3]);
                if (!p && first) bar_sync(8, 384);
                TR(r21);
#pragma unroll
                for (int i = 0; i < 7; i++) {
                    if (i == 5 && !p && first) bar_sync(6, 160);
                    if (i != 4 && i != 6) wgmma_fence();
#pragma unroll
                    for (int j = 0; j < 5; j++) {
                        wgmma_rs_n80(acc2, A[i][4 * j], A[i][4 * j + 1], A[i][4 * j + 2], A[i][4 * j + 3],
                                     mk(sbd + ((OFF_WO + i * WO_SLOT) >> 4) + j * 64 + (320 << 16), HI64), i || j);
                        if (i == 6 && j == CHKJ) {
                            uint32_t mn = par;
#pragma unroll
                            for (int q = 1; q < 8; q++) mn &= A[q % 7][0] & A[q % 7][4] & A[q % 7][8] & A[q % 7][12] & A[q % 7][16];
                            again = bar_or(2 + p, 128, mn == 0u && ++spins < SPIN);
                        }
                    }
                    if (i < 2 || i > 4) wgmma_commit();
                    if (i == SERAT && !p && first) bar_arrive(9, 288);
                    if (i == 0) TR(r22);
                    if (i == 1) {
                        wgmma_wait<1>();
#pragma unroll
                        for (int j = 0; j < 5; j++)
                            ldg128(src[6] + 6 * XB + j * 512, A[0][4 * j], A[0][4 * j + 1], A[0][4 * j + 2], A[0][4 * j + 3]);
                    }
                }
                first = false;
                if (again) {
                    wgmma_wait<0>();
#pragma unroll
                    for (int j = 0; j < 5; j++)
                        ldg128(orow + hg * XB + j * 512, A[0][4 * j], A[0][4 * j + 1], A[0][4 * j + 2], A[0][4 * j + 3]);
                }
            } while (again);
            wgmma_wait<1>();
            wgmma_fence();
#pragma unroll
            for (int j = 0; j < 5; j++) {
                wgmma_rs_n80(acc2, A[0][4 * j], A[0][4 * j + 1], A[0][4 * j + 2], A[0][4 * j + 3],
                             mk(sbd + ((OFF_WO + 7 * WO_SLOT) >> 4) + j * 64 + (320 << 16), HI64), 1);
#pragma unroll
                for (int c = 0; c < 5; c++) {
                    if (LDJ < 5 ? j == LDJ : j == c) {
                        if (LDJ == 5 || (LDJ && c == 0)) bar_arrive(10, 32);
                        ldsm_x4(xf[c], (c < 4 ? a0 + c * 32 : a4) + OFF_X);
                        ldsm_x4(gf[c], (c < 4 ? a0 + c * 32 : a4) + OFF_G);
                    }
                }
            }
            wgmma_commit();
            TR(r42);
            if (routed) {
                const float2 sel = lds64f(sb + M_SEL);
                const uint32_t row = warp * 16 + (lane & 15);
                const uint32_t go = row == U(sel.x) ? M_UPD - row * 160 : (row == U(sel.y) ? M_UPD + 160 - row * 160 : OFF_G);
                mbar_wait(sb + B_UPD, 0);
#pragma unroll
                for (int c = 0; c < 5; c++) ldsm_x4(gf[c], (c < 4 ? a0 + c * 32 : a4) + go);
            }
            wgmma_wait<0>();
#pragma unroll
            for (int i = 0; i < 40; i++) asm volatile("" : "+f"(acc2[i]) :: "memory");
            TR(r44);
#pragma unroll
            for (int c = 0; c < 5; c++) {
#pragma unroll
                for (int q = 0; q < 4; q++)
                    asm("fma.rn.bf16x2 %0, %1, %2, %0;" : "+r"(xf[c][q]) : "r"(pack_bf16(acc2[8 * c + 2 * q], acc2[8 * c + 2 * q + 1])), "r"(gf[c][q]));
                stsm_x4((c < 4 ? a0 + c * 32 : a4) + OFF_X, xf[c]);
            }
            fence_proxy_async_smem();
            __syncwarp();
            if (lane == 0) {
                tma_st(&P.tm[T_OUT], sb + OFF_X + warp * 2560, hg * 80, rb * 64 + 16 * w, p);
                asm volatile("cp.async.bulk.wait_group.read 0;" ::: "memory");
            }
        }
        TS(46);
        TRW(r12, 12); TRW(r26, 26); TRW(r28, 28); TRW(r32, 32); TRW(r34, 34); TRW(r61, 61); TRW(r20, 20); TRW(r21, 21); TRW(r22, 22); TRW(r42, 42); TRW(r44, 44);
    } else if (warp >= 12) {
        asm volatile("setmaxnreg.dec.sync.aligned.u32 24;");
        if (warp == 12) {
            uint32_t slot = clock32() + PACE0;
            if (elect()) {
                mbar_expect_tx(sb + B_FULL + 16, ST);
                tma(sb + 2 * ST, &P.tm[T_X], sb + B_FULL + 16, k0, rb * 64);
            }
            __syncwarp();
            cluster_wait();
            if (elect()) {
                TS(48);
#pragma unroll 1
                for (uint32_t kb = 0; kb < 10; kb++) {
                    const uint32_t s = (kb + 2) & 3;
                    const uint32_t st = sb + s * ST, fb = sb + B_FULL + 8 * s;
                    const uint32_t kc = kb * 64 + (kb < 5 ? k0 : -k0);
                    if (kb >= 4) {
                        mbar_wait(fb + 32, kb >> 3);
                        if (kb < 9) mbar_wait(sb + B_AX - 32 + 8 * kb, 0);
                    }
                    if (kb > 0) {
                        slot += PACE1;
#pragma unroll 1
                        while ((int)(clock32() - slot) < 0) { }
                        mbar_expect_tx(fb, ST);
                        tma(st, &P.tm[T_X], fb, kc, rb * 64);
                    }
                    tma_mc(st + ST_BM + rank * 12288, &P.tm[T_W], fb, hg * 80 + (hg & ODDX) * 16, kc + rank * 32);
                    tma_mc(st + ST_BR + rank * 3072, &P.tm[T_WR], fb, hg * 80 + 64 - (hg & ODDX) * 64, kc + rank * 32);
                }
                TS(49);
                mbar_wait(sb + B_EMPTY, 1);
                mbar_expect_tx(sb + B_X, 20480);
                tma(sb + OFF_DN, &P.tm[T_D], sb + B_X, 0, 32 * fp, 5 * rank);
                uint32_t wb = sb + B_WO - 8;
#pragma unroll 1
                for (uint32_t i = 0; i < 8; i++) {
                    if ((0x25 >> i) & 1) {
                        wb += 8;
                        mbar_wait(wb - (B_WO - B_EMPTY - 8), i == 0);
                        mbar_expect_tx(wb, i == 0 ? 2 * 12800 : 3 * 12800);
                    }
                    if (WOP) {
#pragma unroll 1
                        while ((int)(clock32() - slot) < 0) { }
                        slot = clock32() + WOP;
                    }
                    const uint32_t d = sb + OFF_WO + i * WO_SLOT;
                    const uint32_t kr = 80 * (i ? i - (i <= hg) : hg);
                    tma_mc(d + rank * 5120, &P.tm[T_WO], wb, hg * 80 + (hg & 1) * 16 + rank * 32, kr);
                    tma_mc(d + 10240 + rank * 2560, &P.tm[T_WOR], wb, hg * 80 + (~hg & 1) * 64, kr + rank * 40);
                }
                TS(50);
            }
        } else if (warp == 13) {
            const uint32_t t0 = clock32();
            if (elect()) {
#pragma unroll 1
                for (uint32_t i = 0; i < 3; i++) {
#pragma unroll 1
                    while (clock32() - t0 < PX0 + i * PX1) __nanosleep(20);
                    l2_prefetch(P.w + ((i + 2) * 245760 + b * 1920), 1920);
                    l2_prefetch(P.w + ((i + 7) * 245760 + b * 1920), 1920);
                }
#pragma unroll 1
                for (uint32_t i = 0; i < 14; i++) {
#pragma unroll 1
                    while (clock32() - t0 < GU0 + i * GU1) __nanosleep(20);
                    if (i < 10) l2_prefetch(P.wd + (i * 128 + b) * 1728, 1728);
                    else l2_prefetch(P.wo + ((i - 10) * 128 + b) * 1600, 1600);
                }
                TS(59);
            }
        } else if (warp == 15) {
            const uint32_t lane = opaque_tid() & 31;
            const uint8_t* fl = P.scr + (G_FLAG + (rb * 8 + (lane & 7)) * XB + (lane >> 3) * 8);
            cluster_wait();
            mbar_wait(sb + B_PREP, 0);
            const uint32_t par = lds32(sb + M_SEL + 8);
            mbar_wait(sb + B_WO, 0); mbar_wait(sb + B_WO + 8, 0);
            unsigned spins = 0;
            TS(23);
            uint2 f;
#pragma unroll 1
            do f = ldg64(fl); while (any(f.x != par) && ++spins < SPIN);
            bar_arrive(5, 160);
            TS(24);
            mbar_wait(sb + B_WO + 16, 0);
            bar_arrive(6, 160);
#pragma unroll 1
            while (any(f.y != par) && ++spins < SPIN) f.y = ldg32(fl + 4);
            bar_arrive(9, 288);
            TS(25);
        } else {
            uint32_t slot = clock32() + GT0;
            cluster_wait();
            if (elect()) {
#pragma unroll 1
                for (uint32_t i = 0; i < 20; i++) {
                    slot += GT1;
#pragma unroll 1
                    while ((int)(clock32() - slot) < 0) __nanosleep(20);
                    tma(sb + OFF_GU + i * 2048, &P.tm[T_GU], sb + B_GU, 32 * fp, rank * 320 + i * 16);
                }
            }
        }
    } else {
        asm volatile("setmaxnreg.dec.sync.aligned.u32 72;");
        const uint32_t at = opaque_tid() - 256, lane = at & 31, g = lane >> 2, t = lane & 3, c7 = lane & 7, aw = warp - 8;
        const uint32_t t0 = clock32();
        uint8_t* const yz = P.scr + (G_Y + b * 512 + at * 4);
        stg32(yz, 0u);
        __nanosleep(AUXS);
        const uint32_t epoch = ldg32(P.scr + G_EPOCH) + 1 + ldg32(yz), tag = (epoch & 15u) | 16u;
        const uint32_t empty_cl = mapa(sb + B_EMPTY, lane & 1);
        unsigned spins = 0;
        TRD(r51); TRD(r30); TRD(r52); TRD(r53); TRD(r54); TRD(r55); TRD(r20); TRD(r22);
        {
            const uint2 wv = __ldg(reinterpret_cast<const uint2*>(P.w_r + k0 * 2 + min(at, 79u) * 8));
            if (at < 80) sts64(sb + M_UPD + at * 8, wv.x, wv.y);
        }
        uint8_t* const stw = P.scr + (b * XB + G_ST + (lane & 4) * 64 + (at >> 3) * 16);
        uint8_t* const csw = P.scr + (b * XB + G_CS + at);
        uint8_t* const tpw = P.scr + (G_TOP + (hg >> 2) * XB + rb * 64 + aw * 16);
        const bool tpub = lane == 0 && (hg & 3) == 3;
        cluster_wait();
        bar_sync(4, 128);
        mbar_wait(sb + B_FULL + 16, 0);
        if (t == 0) { stg128(stw, 0u, 0u, 0u, 0u); stg32(csw, 0u); }
        if (tpub) stg128(tpw, 0u, 0u, 0u, 0u);

        uint32_t k1, sv;
        {
            const uint32_t xoff = (32 * (hg & 3) + (at >> 3)) * 128 + ((c7 ^ ((at >> 3) & 7)) << 4);
            const uint32_t jt = (rb >> 2) * 8 + rank * 4 + aw;
            const uint32_t coff = jt < 24 ? ST_BM + (jt >> 3) * 4096 + lane * 128 + (((jt ^ lane) & 7) << 4)
                                          : ST_BR + ((jt >> 1) & 3) * 1024 + lane * 32 + (((jt ^ g) & 1) << 4);
            float q[8], c8[8];
#pragma unroll
            for (int e = 0; e < 8; e++) q[e] = c8[e] = 0.f;
#pragma unroll 1
            for (uint32_t kb = 2; kb < 7; kb++) {
                const uint32_t st = sb + (kb & 3) * ST;
                const uint4 wv = lds128(sb + M_UPD - 256 + kb * 128 + c7 * 16);
                mbar_wait(sb + B_FULL + 8 * (kb & 3), kb == 6);
                const uint4 v = lds128(st + xoff), vn = lds128(st + xoff + 2048);
                const uint4 cv = lds128(st + coff), cn = lds128(st + coff + (jt < 24 ? 12288 : 3072));
                if (lane < 2) mbar_arrive_cl(empty_cl + (B_AX - B_EMPTY - 16) + 8 * kb + (cn.x & 0));
                const uint32_t u[4] = {v.x, v.y, v.z, v.w}, un[4] = {vn.x, vn.y, vn.z, vn.w}, ww[4] = {wv.x, wv.y, wv.z, wv.w};
                const uint32_t cc[4] = {cv.x, cv.y, cv.z, cv.w}, cd[4] = {cn.x, cn.y, cn.z, cn.w};
#pragma unroll
                for (int e = 0; e < 4; e++) {
                    const float a0 = bflo(u[e]), a1 = bfhi(u[e]), b0 = bflo(un[e]), b1 = bfhi(un[e]), w0 = bflo(ww[e]), w1 = bfhi(ww[e]);
                    q[0] += a0 + a1; q[4] += b0 + b1; q[3] += w0 + w1;
                    q[1] = fmaf(a0, a0, fmaf(a1, a1, q[1])); q[5] = fmaf(b0, b0, fmaf(b1, b1, q[5]));
                    q[2] = fmaf(a0, w0, fmaf(a1, w1, q[2])); q[6] = fmaf(b0, w0, fmaf(b1, w1, q[6]));
                    c8[2 * e] += bflo(cc[e]) + bflo(cd[e]); c8[2 * e + 1] += bfhi(cc[e]) + bfhi(cd[e]);
                }
            }
            TR(r51);
            q[7] = q[3];
#pragma unroll
            for (int e = 0; e < 4; e++) {
                q[e] = ((lane & 4) ? q[e + 4] : q[e]) + shx((lane & 4) ? q[e] : q[e + 4], 4);
                q[e] += shx(q[e], 1); q[e] += shx(q[e], 2);
            }
            const float mh = q[0] * (1.0f / 320);
            if (t == 0) stg128(stw, U(mh), U(fmaf(-mh, q[0], q[1])), U(q[2]), (U(q[3]) & ~31u) | tag);
#define TSTEP(H) { const bool up = (lane & (4 * H)) != 0; _Pragma("unroll") for (int e = 0; e < H; e++) { \
            const float send = up ? c8[e] : c8[e + H]; const float keep = up ? c8[e + H] : c8[e]; \
            c8[e] = keep + shx(send, 4 * H); } }
            TSTEP(4) TSTEP(2) TSTEP(1)
#undef TSTEP
            c8[0] += shx(c8[0], 1); c8[0] += shx(c8[0], 2);
            if (t == 0) stg32(csw, (U(c8[0]) & ~31u) | tag);
            TR(r30);
            const uint8_t* csp = P.scr + (G_CS + (aw * 32 + (lane >> 4) * 8 + hg) * XB + (lane & 15) * 8);
            const uint8_t* stp = P.scr + (G_ST + (rb * 8 + aw) * XB + lane * 16);
            uint32_t ra[4], rc[4];
            uint2 ca, cc;
#pragma unroll 1
            while (clock32() - t0 < EX1T) __nanosleep(20);
#pragma unroll 1
            do {
                ldg128(stp, ra[0], ra[1], ra[2], ra[3]);
                ldg128(stp + 4 * XB, rc[0], rc[1], rc[2], rc[3]);
                ca = ldg64(csp); cc = ldg64(csp + 16 * XB);
            } while (any((ra[3] ^ tag | rc[3] ^ tag) & 31u) && ++spins < SPIN);
            TR(r20);
            const float dm = 0.5f * (F(ra[0]) - F(rc[0])), m = bf16r(F(rc[0]) + dm);
            const float sd = bf16r(sqrt_a(bf16r(bf16r(fmaxf(fmaf(dm, dm, (F(ra[1]) + F(rc[1])) * (1.0f / DM)), 0.f)) + 1e-5f)));
            const float rs = rcp(sd);
            uint32_t w1, w2;
            if ((hg & 3) == 3) {
                k1 = pack_bf16(0.f, fmaf(-m, F(ra[3]) + F(rc[3]), F(ra[2]) + F(rc[2])) * rs);
                k1 ^= ((int)k1 >> 31) | 0x80000000u;
                k1 = (k1 & 0xFFFF0000u) | ((2047 - (rb * 128 + 2 * (at & 63) + (at >> 6))) << 5) | tag;
                w1 = redux_max(k1); w2 = redux_max(k1 == w1 ? 0u : k1);
                sv = U(m) | (U(sd) >> 16);
                const uint32_t v1 = redux_max(k1 == w1 ? sv : 0u), v2 = redux_max(k1 == w2 ? sv : 0u);
                if (lane == 0) stg128(tpw, w1, v1, w2, v2);
            }
            sts64(sb + M_ST + at * 8, U(rs), U(m));
            sts32(sb + M_SEL + 8, (tag & 1) ? 1u : 0x10000u);
#pragma unroll 1
            while (any((ca.x ^ tag | ca.y ^ tag | cc.x ^ tag | cc.y ^ tag) & 31u) && ++spins < SPIN) { ca = ldg64(csp); cc = ldg64(csp + 16 * XB); }
            {
                const float c0 = at < 120 ? F(ca.x) + F(cc.x) : 0.f, c1 = at < 120 ? F(ca.y) + F(cc.y) : 0.f;
                const uint32_t hi = pack_bf16(c0, c1);
                sts32(sb + M_CS + (at >> 2) * 32 + t * 4, hi);
                sts32(sb + M_CS + (at >> 2) * 32 + t * 4 + 16, pack_bf16(c0 - bflo(hi), c1 - bfhi(hi)));
                fence_proxy_async_smem();
                __syncwarp();
                if (lane < 2) mbar_arrive(sb + B_PREP);
            }
            TR(r52);
            if (aw == 0) {
                uint32_t ka[4], kb[4];
#pragma unroll 1
                while (clock32() - t0 < EX1T + EX2D) __nanosleep(20);
#pragma unroll 1
                do {
                    const uint8_t* tp = P.scr + (G_TOP + lane * 16);
                    uint32_t kc[4], kd[4];
                    ldg128(tp, ka[0], ka[1], ka[2], ka[3]);
                    ldg128(tp + 512, kb[0], kb[1], kb[2], kb[3]);
                    ldg128(tp + XB, kc[0], kc[1], kc[2], kc[3]);
                    ldg128(tp + XB + 512, kd[0], kd[1], kd[2], kd[3]);
                    const bool ba = (ka[0] ^ tag) & 31u, bb = (kb[0] ^ tag) & 31u;
#pragma unroll
                    for (int e = 0; e < 4; e++) { ka[e] = ba ? kc[e] : ka[e]; kb[e] = bb ? kd[e] : kb[e]; }
                } while (any((ka[0] ^ tag | kb[0] ^ tag) & 31u) && ++spins < SPIN);
                TR(r22);
                if (kb[0] > ka[0]) {
#pragma unroll
                    for (int e = 0; e < 4; e++) { const uint32_t x = ka[e]; ka[e] = kb[e]; kb[e] = x; }
                }
                if (kb[0] > ka[2]) { ka[2] = kb[0]; ka[3] = kb[1]; }
                w1 = redux_max(ka[0]);
                const uint32_t t1 = redux_max(ka[0] == w1 ? ka[1] : 0u);
                if (ka[0] == w1) { ka[0] = ka[2]; ka[1] = ka[3]; }
                w2 = redux_max(ka[0]);
                const uint32_t t3 = redux_max(ka[0] == w2 ? ka[1] : 0u);
                sts128(sb + M_TOP, w1, t1, w2, t3);
            }
            bar_sync(4, 128);
            const float2 tv = lds64f(sb + M_TOP + (lane & 1) * 8);
            k1 = U(tv.x);
            sv = U(tv.y);
        }
        TR(r53);
        const uint32_t tok = ~(k1 >> 5) & 2047;
        const unsigned owns = __ballot_sync(0xffffffffu, (tok >> 7) == rb) & 3u;
        if (at < 2) sts32(sb + M_SEL + at * 4, (tok >> 7) == rb ? (tok & 1) * 64 + ((tok & 127) >> 1) : ~0u);
        if ((at | b) == 0) *reinterpret_cast<uint32_t*>(P.scr + G_EPOCH) = epoch;
        __syncwarp();
        if (at == 0) mbar_arrive(sb + B_SEL);
        if (fp < NFFN / 2) {
            uint4 xv = __ldg(reinterpret_cast<const uint4*>(P.x + (tok * 1280 + rank * 640 + min(at >> 1, 39u) * 16)));
            const uint32_t m2 = __byte_perm(sv, 0, 0x3232);
            asm("sub.rn.bf16x2 %0, %0, %4;\nsub.rn.bf16x2 %1, %1, %4;\nsub.rn.bf16x2 %2, %2, %4;\nsub.rn.bf16x2 %3, %3, %4;"
                : "+r"(xv.x), "+r"(xv.y), "+r"(xv.z), "+r"(xv.w) : "r"(m2));
            mbar_wait(sb + B_X, 0);
            if (at < 80) sts128(sb + OFF_PART + at * 16, xv.x, xv.y, xv.z, xv.w);
            mbar_wait(sb + B_GU, 0);
            mbar_wait(sb + B_EMPTY + 24, 0);
            bar_sync(4, 128);
            float c[5][4];
#pragma unroll
            for (int i = 0; i < 5; i++) c[i][0] = c[i][1] = c[i][2] = c[i][3] = 0.f;
            const uint32_t mi = lane >> 3, kr = c7 + (mi >> 1) * 8;
            {
                const uint32_t wa = sb + OFF_GU + (aw >> 1) * 1024 + kr * 64 + ((((aw & 1) * 2 + (mi & 1)) ^ ((kr >> 1) & 3)) << 4);
#pragma unroll
                for (uint32_t i = 0; i < 10; i++) {
                    uint32_t xb[4], a0[4], a1[4];
                    ldsm_x4(xb, sb + OFF_PART + i * 128 + mi * 32 + (lane & 1) * 16);
                    ldsm_x4_t(a0, wa + i * 4096);
                    ldsm_x4_t(a1, wa + i * 4096 + 2048);
                    mma16816(c[(2 * i) & 3], a0[0], a0[1], a0[2], a0[3], xb[0], xb[1]);
                    mma16816(c[(2 * i + 1) & 3], a1[0], a1[1], a1[2], a1[3], xb[2], xb[3]);
                }
#pragma unroll
                for (int e = 0; e < 4; e++) { c[0][e] = (c[0][e] + c[1][e]) + (c[2][e] + c[3][e]); }
                const uint32_t rd = mapa(sb, rank ^ (t & 1));
                if (t < 2)
                    asm volatile("st.async.shared::cluster.mbarrier::complete_tx::bytes.v4.f32 [%0], {%1,%2,%3,%4}, [%5];"
                                 :: "r"(rd + (t ? OFF_PART + 1280 : M_UPD + 192) + aw * 128 + g * 16), "f"(c[0][0]), "f"(c[0][1]), "f"(c[0][2]), "f"(c[0][3]), "r"(rd + B_H) : "memory");
            }
            TR(r54);
            const float rs = rcp(bflo(sv));
            const uint32_t da = sb + OFF_DN + kr * 128 + (((2 * aw + (mi & 1)) ^ c7) << 4);
            uint8_t* yp = P.scr + (G_Y + (fp % 6) * 10240 + rank * 2560 + t * 512 + aw * 128 + g * 16);
#pragma unroll
            for (int i = 0; i < 5; i++) c[i][0] = c[i][1] = c[i][2] = c[i][3] = 0.f;
            mbar_wait(sb + B_H, 0);
#pragma unroll
            for (uint32_t ks = 0; ks < 2; ks++) {
                const uint32_t og = sb + ks * 128 + lane * 4 + P.up_first, ou = og ^ 256;
                const float gs = bf16r((F(lds32(og + M_UPD + 192)) + F(lds32(og + OFF_PART + 1280))) * rs);
                const float h = bf16r(gs * sigm(gs)) * bf16r((F(lds32(ou + M_UPD + 192)) + F(lds32(ou + OFF_PART + 1280))) * rs);
                const uint32_t hp = pack_bf16(h, __shfl_down_sync(0xffffffffu, h, 4));
                const uint32_t h0 = __shfl_sync(0xffffffffu, hp, t * 8 + (g & 1)), h1 = __shfl_sync(0xffffffffu, hp, t * 8 + (g & 1) + 2);
#pragma unroll
                for (uint32_t j = 0; j < 5; j++) {
                    uint32_t a[4];
                    ldsm_x4_t(a, da + j * 4096 + ks * 2048);
                    mma16816(c[j], a[0], a[1], a[2], a[3], h0, h1);
                }
            }
#pragma unroll
            for (int e = 0; e < 4; e++) {
                const float lo = (t & 1) ? c[1][e] : c[0][e], hi = (t & 1) ? c[3][e] : c[2][e];
                c[0][e] = (t & 2) ? hi : lo;
            }
            asm volatile("" : "+f"(c[0][0]), "+f"(c[4][0]) :: "memory");
            BLOCK_SPLIT(tag);
            bar_sync(8, 384);
            { red4(yp, c[0][0], c[0][2]); red4(yp + 5120, c[0][1], c[0][3]); }
            if (t == 0) { red4(yp + 2048, c[4][0], c[4][2]); red4(yp + 2048 + 5120, c[4][1], c[4][3]); }
            TR(r55);
        }
        else bar_arrive(8, 384);
        mbar_wait(sb + B_X, 0); mbar_wait(sb + B_GU, 0);
        TRW(r51, 51); TRW(r30, 30); TRW(r52, 52); TRW(r53, 53); TRW(r54, 54); TRW(r55, 55); TRW(r20, 20); TRW(r22, 22);
        if (owns) {
            const uint32_t u = min(at >> 1, 39u), col = (u >> 3) * 32 + (u & 7) * 2;
            const bool mine = (tok >> 7) == rb;
            k1 ^= ((~(int)k1) >> 31) | 0x80000000u;
            const float sg = bf16r(sigm(bfhi(k1))), rs = rcp(bflo(sv));
            uint32_t x0, x1, y0, y1, n0, n1;
            asm volatile("ld.global.nc.u16 %0, [%2];\nld.global.nc.u16 %1, [%2 + 16];" : "=r"(x0), "=r"(x1) : "l"(P.x + (tok * 1280 + hg * 160 + col)));
            const float a0 = (bflo(x0) - bfhi(sv)) * rs, a1 = (bflo(x1) - bfhi(sv)) * rs;
            bar_sync(4, 128);
#pragma unroll 1
            do {
                __nanosleep(YSL);
                uint32_t v[6][4];
#pragma unroll
                for (int r = 0; r < 6; r++) ldg128(P.scr + (G_Y + (at & 1) * 5120 + hg * 640 + u * 16) + r * 10240, v[r][0], v[r][1], v[r][2], v[r][3]);
                y0 = U(((F(v[0][0]) + F(v[1][0])) + (F(v[2][0]) + F(v[3][0]))) + (F(v[4][0]) + F(v[5][0])));
                y1 = U(((F(v[0][1]) + F(v[1][1])) + (F(v[2][1]) + F(v[3][1]))) + (F(v[4][1]) + F(v[5][1])));
                n0 = U(((F(v[0][2]) + F(v[1][2])) + (F(v[2][2]) + F(v[3][2]))) + (F(v[4][2]) + F(v[5][2])));
                n1 = U(((F(v[0][3]) + F(v[1][3])) + (F(v[2][3]) + F(v[3][3]))) + (F(v[4][3]) + F(v[5][3])));
            } while (any(mine && (F(n0) != NFFN / 2 || F(n1) != NFFN / 2)) && ++spins < SPIN);
            const float v0 = a0 + bf16r(bf16r(F(y0)) * sg), v1 = a1 + bf16r(bf16r(F(y1)) * sg);
            const uint32_t gp = pack_bf16(v0 * sigm(v0), v1 * sigm(v1));
            asm volatile("st.shared.u16 [%0], %1;\nst.shared.u16 [%0 + 16], %2;" :: "r"(sb + M_UPD + (at & 1) * 160 + col), "r"(gp), "r"(gp >> 16) : "memory");
            __syncwarp();
            if (lane < 2) mbar_arrive(sb + B_UPD);
            TS(56);
        }
    }
}

typedef CUresult (*EncodeFn)(CUtensorMap*, CUtensorMapDataType, cuuint32_t, void*, const cuuint64_t*, const cuuint64_t*,
                             const cuuint32_t*, const cuuint32_t*, CUtensorMapInterleave, CUtensorMapSwizzle,
                             CUtensorMapL2promotion, CUtensorMapFloatOOBfill);

bool encode(EncodeFn fn, CUtensorMap* tm, const void* ptr, cuuint64_t d0, cuuint64_t d1, cuuint64_t d2, cuuint64_t s1, cuuint64_t s2,
            cuuint32_t b0, cuuint32_t b1, cuuint32_t b2, CUtensorMapSwizzle sw) {
    const cuuint64_t dims[3] = {d0, d1, d2}, strides[2] = {s1, s2};
    const cuuint32_t box[3] = {b0, b1, b2}, es[3] = {1, 1, 1};
    return fn(tm, CU_TENSOR_MAP_DATA_TYPE_BFLOAT16, 3, const_cast<void*>(ptr), dims, strides, box, es,
              CU_TENSOR_MAP_INTERLEAVE_NONE, sw, CU_TENSOR_MAP_L2_PROMOTION_L2_128B,
              CU_TENSOR_MAP_FLOAT_OOB_FILL_NONE) == CUDA_SUCCESS;
}

}

extern "C" void kernel_launch(void* const* d_in, const int* in_sizes, int n_in, void* d_out, int out_size) {
    static Params P;
    static int grid = 0;
    static const void* cached[9] = {};
    bool same = cached[8] == d_out;
    for (int i = 0; i < 8; i++) same = same && cached[i] == d_in[i];
    if (!same) {
        const void *x = d_in[0], *wqkv = d_in[1], *wo = d_in[2], *wg = d_in[5], *wu = d_in[6], *wd = d_in[7];
        void* fnp = nullptr;
        cudaDriverEntryPointQueryResult qr;
        cudaGetDriverEntryPoint("cuTensorMapEncodeTiled", &fnp, cudaEnableDefault, &qr);
        EncodeFn fn = (EncodeFn)fnp;
        const CUtensorMapSwizzle S0 = CU_TENSOR_MAP_SWIZZLE_NONE, S32 = CU_TENSOR_MAP_SWIZZLE_32B, S64 = CU_TENSOR_MAP_SWIZZLE_64B,
                                 S128 = CU_TENSOR_MAP_SWIZZLE_128B;
        const bool ok = fn != nullptr &&
            encode(fn, &P.tm[T_X], x, 640, 1024, 2, 2560, 1280, 64, 64, 2, S128) &&
            encode(fn, &P.tm[T_OUT], d_out, 640, 1024, 2, 2560, 1280, 80, 16, 1, S0) &&
            encode(fn, &P.tm[T_W], wqkv, 640, 640, 3, 3840, 1280, 64, 32, 3, S128) &&
            encode(fn, &P.tm[T_WR], wqkv, 640, 640, 3, 3840, 1280, 16, 32, 3, S32) &&
            encode(fn, &P.tm[T_GU], wg < wu ? wg : wu, 1728, 640, 2, 3456, wg < wu ? (const char*)wu - (const char*)wg : (const char*)wg - (const char*)wu,
                   32, 16, 2, S64) &&
            encode(fn, &P.tm[T_D], wd, 64, 1728, 10, 1280, 128, 64, 32, 5, S128) &&
            encode(fn, &P.tm[T_WO], wo, 640, 640, 1, 1280, 1280 * 640, 32, 80, 1, S64) &&
            encode(fn, &P.tm[T_WOR], wo, 640, 640, 1, 1280, 1280 * 640, 16, 40, 1, S64);
        if (!ok) return;
        P.up_first = wg < wu ? 0 : 256;
        P.wo = (const uint8_t*)wo; P.wd = (const uint8_t*)wd;
        P.x = (const uint8_t*)x; P.w = (const uint8_t*)wqkv; P.w_r = (const uint8_t*)d_in[4];
        if (cudaGetSymbolAddress((void**)&P.scr, g_scr) != cudaSuccess) return;
        cudaFuncSetAttribute(fused_kernel, cudaFuncAttributeMaxDynamicSharedMemorySize, SMEM_BYTES);
        int ncl = 0, sms = 0, dev = 0;
        {
            cudaLaunchConfig_t cfg = {};
            cfg.gridDim = dim3(128); cfg.blockDim = dim3(NTHREADS); cfg.dynamicSmemBytes = SMEM_BYTES;
            cudaLaunchAttribute at[1];
            at[0].id = cudaLaunchAttributeClusterDimension;
            at[0].val.clusterDim.x = 2; at[0].val.clusterDim.y = 1; at[0].val.clusterDim.z = 1;
            cfg.attrs = at; cfg.numAttrs = 1;
            if (cudaOccupancyMaxActiveClusters(&ncl, fused_kernel, &cfg) != cudaSuccess || ncl < 64) return;
            cudaGetDevice(&dev);
            cudaDeviceGetAttribute(&sms, cudaDevAttrMultiProcessorCount, dev);
        }
        P.by_sm = sms == 132 && ncl == 66;
        grid = P.by_sm ? 132 : 128;
        static const int hg_of_pos[8] = {1, 5, 3, 0, 4, 7, 2, 6};
        int nf = 0;
        for (int t = 0; t < 66; t++) {
            int gpc, pos;
            if (!P.by_sm) { gpc = t >> 3; pos = t & 7; }
            else if (t < 32) { gpc = t & 7; pos = t >> 3; }
            else if (t < 60) { gpc = 1 + (t - 32) % 7; pos = 4 + (t - 32) / 7; }
            else if (t < 62) { gpc = 8; pos = 0; }
            else { gpc = 0; pos = t - 58; }
            const bool ffn = gpc < 8 && pos != 0 && !(pos == 1 && gpc < 2);
            P.map[t] = (uint16_t)(gpc * 8 + hg_of_pos[pos] + ((ffn ? nf++ : 127) << 8));
        }
        for (int i = 0; i < 8; i++) cached[i] = d_in[i];
        cached[8] = d_out;
    }
    fused_kernel<<<grid, NTHREADS, SMEM_BYTES>>>(P);
}
```

```cpp
#include <cuda_runtime.h>
#include <cuda_bf16.h>
#include <cuda.h>
#include <stdint.h>

namespace {

typedef __nv_bfloat16 bf16;

constexpr int SEQ = 2048, DM = 640;
constexpr int NTHREADS = 512;
constexpr int NFFN = 108;
#define LEAD 2
#define PACE0 250
#define PACE1 950
#define PX0 1500
#define PX1 500
#define GU0 6000
#define GU1 220
#define GT0 2300
#define GT1 430
#define WOP 150
#define AUXS 500
#define EX1T 8200
#define EX2D 2200
#define SERAT 2
#define CHKJ 2
#define LDJ 4
#define YSL 200
#define HGMAP 0x62740351u
#define TPUB 3
#define AHEAD 4
#define LDAT 1
#define ODDX 1

constexpr int ST = 47104;
constexpr int ST_BM = 16384, ST_BR = 40960;
constexpr int OFF_X = 0;
constexpr int OFF_DN = 20480;
constexpr int OFF_PART = 40960;
constexpr int OFF_G = 43008;
constexpr int OFF_WO = 63488;
constexpr int WO_SLOT = 15360;
constexpr int OFF_GU = 4 * ST;
constexpr int M_ST = OFF_GU + 40960;
constexpr int M_CS = M_ST + 1024;
constexpr int M_UPD = M_CS + 1024;
constexpr int M_TOP = M_UPD + 640;
constexpr int M_SEL = M_TOP + 64;
constexpr int B_Z = M_SEL + 16, B_G = B_Z + 8, B_AX = B_Z + 32, B_PREP = B_AX + 40, B_UPD = B_PREP + 8, B_GU = B_AX + 64, B_X = B_GU + 8, B_H = B_X + 8,
              B_SEL = B_H + 8, B_FULL = B_GU + 32, B_EMPTY = B_FULL + 32, B_HO = B_EMPTY + 32, B_WO = B_HO + 32;
constexpr int SMEM_BYTES = B_WO + 32;
static_assert(SMEM_BYTES <= 232448 && OFF_WO + 2 * WO_SLOT <= 2 * ST && OFF_WO + 5 * WO_SLOT <= 3 * ST && OFF_WO + 8 * WO_SLOT <= 4 * ST, "smem");

enum { T_X, T_W, T_WR, T_GU, T_D, T_WO, T_WOR, T_OUT, T_N };
struct Params {
    CUtensorMap tm[T_N];
    const uint8_t* x;
    const uint8_t* w_r;
    const uint8_t* w;
    const uint8_t* wo;
    const uint8_t* wd;
    uint8_t* scr;
    uint32_t up_first;
};

constexpr uint32_t XB = 27392;
constexpr uint32_t G_TOP = 25600;
constexpr uint32_t G_CS = G_TOP + 1024;
constexpr uint32_t G_ST = G_CS + 128;
constexpr uint32_t G_FLAG = G_ST + 512;
constexpr uint32_t G_Y = 128 * XB;
constexpr uint32_t G_EPOCH = G_Y + 128 * 512;
static_assert(G_FLAG + 128 == XB, "scratch");
__device__ __align__(1024) uint8_t g_scr[G_EPOCH + 1024];

#define TSINIT
#define TR(v)
#define TRD(v)
#define TRW(v, i)
#define TS(i)
#define TSG(i)
constexpr unsigned SPIN = 1u << 20;

__device__ __forceinline__ void mbar_init(uint32_t bar, int cnt) {
    asm volatile("mbarrier.init.shared::cta.b64 [%0], %1;" :: "r"(bar), "r"(cnt) : "memory");
}
__device__ __forceinline__ void mbar_expect_tx(uint32_t bar, int bytes) {
    asm volatile("mbarrier.arrive.expect_tx.shared::cta.b64 _, [%0], %1;" :: "r"(bar), "r"(bytes) : "memory");
}
__device__ __forceinline__ void mbar_arrive(uint32_t bar) {
    asm volatile("mbarrier.arrive.shared::cta.b64 _, [%0];" :: "r"(bar) : "memory");
}
__device__ __forceinline__ uint32_t mapa(uint32_t a, uint32_t cta) {
    uint32_t r;
    asm("mapa.shared::cluster.u32 %0, %1, %2;" : "=r"(r) : "r"(a), "r"(cta));
    return r;
}
__device__ __forceinline__ void mbar_arrive_cl(uint32_t cbar) {
    asm volatile("mbarrier.arrive.shared::cluster.b64 _, [%0];" :: "r"(cbar) : "memory");
}
__device__ __forceinline__ void mbar_wait(uint32_t bar, int parity) {
    asm volatile("{\n.reg .pred p;\nLAB_WAIT:\nmbarrier.try_wait.parity.shared::cta.b64 p, [%0], %1;\n@!p bra LAB_WAIT;\n}"
                 :: "r"(bar), "r"(parity) : "memory");
}
__device__ __forceinline__ bool mbar_try(uint32_t bar, int parity) {
    uint32_t r;
    asm volatile("{\n.reg .pred p;\nmbarrier.test_wait.parity.shared::cta.b64 p, [%1], %2;\nselp.u32 %0, 1, 0, p;\n}"
                 : "=r"(r) : "r"(bar), "r"(parity) : "memory");
    return r != 0;
}
__device__ __forceinline__ void tma(uint32_t dst, const CUtensorMap* tm, uint32_t bar, int c0, int c1, int c2 = 0) {
    asm volatile("cp.async.bulk.tensor.3d.shared::cluster.global.mbarrier::complete_tx::bytes [%0], [%1, {%3, %4, %5}], [%2];"
                 :: "r"(dst), "l"(tm), "r"(bar), "r"(c0), "r"(c1), "r"(c2) : "memory");
}
__device__ __forceinline__ void tma_mc(uint32_t dst, const CUtensorMap* tm, uint32_t bar, int c0, int c1) {
    asm volatile("cp.async.bulk.tensor.3d.shared::cluster.global.mbarrier::complete_tx::bytes.multicast::cluster [%0], [%1, {%3, %4, %5}], [%2], %6;"
                 :: "r"(dst), "l"(tm), "r"(bar), "r"(c0), "r"(c1), "r"(0), "h"((uint16_t)3) : "memory");
}
__device__ __forceinline__ void tma_st(const CUtensorMap* tm, uint32_t src, int c0, int c1, int c2) {
    asm volatile("cp.async.bulk.tensor.3d.global.shared::cta.bulk_group [%0, {%2, %3, %4}], [%1];\ncp.async.bulk.commit_group;"
                 :: "l"(tm), "r"(src), "r"(c0), "r"(c1), "r"(c2) : "memory");
}
__device__ __forceinline__ void l2_prefetch(const void* p, int bytes) {
    asm volatile("cp.async.bulk.prefetch.L2.global [%0], %1;" :: "l"(p), "r"(bytes) : "memory");
}
__device__ __forceinline__ void cluster_arrive() { asm volatile("barrier.cluster.arrive.relaxed.aligned;" ::: "memory"); }
__device__ __forceinline__ void cluster_wait() { asm volatile("barrier.cluster.wait.aligned;" ::: "memory"); }
__device__ __forceinline__ void bar_sync(int id, int n) { asm volatile("bar.sync %0, %1;" :: "r"(id), "r"(n) : "memory"); }
__device__ __forceinline__ void bar_arrive(int id, int n) { asm volatile("bar.arrive %0, %1;" :: "r"(id), "r"(n) : "memory"); }
__device__ __forceinline__ bool bar_or(int id, int n, bool v) {
    uint32_t r;
    asm volatile("{\n.reg .pred p, q;\nsetp.ne.u32 p, %3, 0;\nbar.red.or.pred q, %1, %2, p;\nselp.u32 %0, 1, 0, q;\n}"
                 : "=r"(r) : "r"(id), "r"(n), "r"((uint32_t)v) : "memory");
    return r != 0;
}
__device__ __forceinline__ void fence_proxy_async_smem() { asm volatile("fence.proxy.async.shared::cta;" ::: "memory"); }
__device__ __forceinline__ void stg128(void* p, uint32_t a, uint32_t b, uint32_t c, uint32_t d) {
    asm volatile("{\n.reg .b64 l, h;\n.reg .b128 q;\nmov.b64 l, {%1, %2};\nmov.b64 h, {%3, %4};\nmov.b128 q, {l, h};\n"
                 "st.relaxed.gpu.global.b128 [%0], q;\n}" :: "l"(p), "r"(a), "r"(b), "r"(c), "r"(d) : "memory");
}
__device__ __forceinline__ void ldg128(const void* p, uint32_t& a, uint32_t& b, uint32_t& c, uint32_t& d) {
    asm volatile("{\n.reg .b64 l, h;\n.reg .b128 q;\nld.relaxed.gpu.global.b128 q, [%4];\nmov.b128 {l, h}, q;\n"
                 "mov.b64 {%0, %1}, l;\nmov.b64 {%2, %3}, h;\n}" : "=r"(a), "=r"(b), "=r"(c), "=r"(d) : "l"(p) : "memory");
}
__device__ __forceinline__ void stg64(void* p, uint32_t a, uint32_t b) {
    asm volatile("{\n.reg .b64 l;\nmov.b64 l, {%1, %2};\nst.relaxed.gpu.global.b64 [%0], l;\n}" :: "l"(p), "r"(a), "r"(b) : "memory");
}
__device__ __forceinline__ void red4(void* p, float a, float b) {
    asm volatile("red.relaxed.gpu.global.add.v4.f32 [%0], {%1, %2, %3, %3};" :: "l"(p), "f"(a), "f"(b), "f"(1.0f) : "memory");
}
__device__ __forceinline__ void stg32(void* p, uint32_t a) {
    asm volatile("st.relaxed.gpu.global.u32 [%0], %1;" :: "l"(p), "r"(a) : "memory");
}
__device__ __forceinline__ uint2 ldg64(const void* p) {
    uint2 v;
    asm volatile("{\n.reg .b64 l;\nld.relaxed.gpu.global.b64 l, [%2];\nmov.b64 {%0, %1}, l;\n}" : "=r"(v.x), "=r"(v.y) : "l"(p) : "memory");
    return v;
}
__device__ __forceinline__ unsigned ldg32(const void* p) {
    unsigned v;
    asm volatile("ld.relaxed.gpu.global.u32 %0, [%1];" : "=r"(v) : "l"(p) : "memory");
    return v;
}
__device__ __forceinline__ void ldsm_x4(uint32_t (&r)[4], uint32_t a) {
    asm volatile("ldmatrix.sync.aligned.m8n8.x4.shared.b16 {%0,%1,%2,%3}, [%4];"
                 : "=r"(r[0]), "=r"(r[1]), "=r"(r[2]), "=r"(r[3]) : "r"(a));
}
__device__ __forceinline__ void ldsm_x4_t(uint32_t (&r)[4], uint32_t a) {
    asm volatile("ldmatrix.sync.aligned.m8n8.x4.trans.shared.b16 {%0,%1,%2,%3}, [%4];"
                 : "=r"(r[0]), "=r"(r[1]), "=r"(r[2]), "=r"(r[3]) : "r"(a));
}
__device__ __forceinline__ void stsm_x4(uint32_t a, const uint32_t (&r)[4]) {
    asm volatile("stmatrix.sync.aligned.m8n8.x4.shared.b16 [%0], {%1,%2,%3,%4};"
                 :: "r"(a), "r"(r[0]), "r"(r[1]), "r"(r[2]), "r"(r[3]));
}
__device__ __forceinline__ uint32_t movm(uint32_t a) {
    uint32_t d;
    asm("movmatrix.sync.aligned.m8n8.trans.b16 %0, %1;" : "=r"(d) : "r"(a));
    return d;
}
__device__ __forceinline__ void mma16816(float (&c)[4], uint32_t a0, uint32_t a1, uint32_t a2, uint32_t a3, uint32_t b0, uint32_t b1) {
    asm("mma.sync.aligned.m16n8k16.row.col.f32.bf16.bf16.f32 {%0,%1,%2,%3}, {%4,%5,%6,%7}, {%8,%9}, {%0,%1,%2,%3};"
        : "+f"(c[0]), "+f"(c[1]), "+f"(c[2]), "+f"(c[3]) : "r"(a0), "r"(a1), "r"(a2), "r"(a3), "r"(b0), "r"(b1));
}
__device__ __forceinline__ void mma1688(float (&c)[4], uint32_t a0, uint32_t a1, uint32_t b0) {
    asm("mma.sync.aligned.m16n8k8.row.col.f32.bf16.bf16.f32 {%0,%1,%2,%3}, {%4,%5}, {%6}, {%0,%1,%2,%3};"
        : "+f"(c[0]), "+f"(c[1]), "+f"(c[2]), "+f"(c[3]) : "r"(a0), "r"(a1), "r"(b0));
}
__device__ __forceinline__ void wgmma_fence() { asm volatile("wgmma.fence.sync.aligned;" ::: "memory"); }
__device__ __forceinline__ void wgmma_commit() { asm volatile("wgmma.commit_group.sync.aligned;" ::: "memory"); }
template <int N> __device__ __forceinline__ void wgmma_wait() { asm volatile("wgmma.wait_group.sync.aligned %0;" :: "n"(N) : "memory"); }
__device__ __forceinline__ uint64_t mk(uint32_t lo, uint32_t hi) { return (uint64_t)lo | ((uint64_t)hi << 32); }
constexpr uint32_t HI128 = (1024 >> 4) | (1u << 30), HI64 = (512 >> 4) | (2u << 30), HI32 = (256 >> 4) | (3u << 30);
__device__ __forceinline__ uint32_t pack_bf16(float lo, float hi) {
    uint32_t r;
    asm("cvt.rn.bf16x2.f32 %0, %1, %2;" : "=r"(r) : "f"(hi), "f"(lo));
    return r;
}
__device__ __forceinline__ float bflo(uint32_t u) { return __uint_as_float(u << 16); }
__device__ __forceinline__ float bfhi(uint32_t u) { return __uint_as_float(u & 0xFFFF0000u); }
__device__ __forceinline__ float bf16r(float v) { return __uint_as_float(pack_bf16(0.f, v)); }
__device__ __forceinline__ float ex2(float v) { float r; asm("ex2.approx.ftz.f32 %0, %1;" : "=f"(r) : "f"(v)); return r; }
__device__ __forceinline__ float rcp(float v) { float r; asm("rcp.approx.ftz.f32 %0, %1;" : "=f"(r) : "f"(v)); return r; }
__device__ __forceinline__ float sqrt_a(float v) { float r; asm("sqrt.approx.ftz.f32 %0, %1;" : "=f"(r) : "f"(v)); return r; }
__device__ __forceinline__ float tanh_a(float v) { float r; asm("tanh.approx.f32 %0, %1;" : "=f"(r) : "f"(v)); return r; }
constexpr float LOG2E = 1.4426950408889634f;
__device__ __forceinline__ float sigm(float v) { return rcp(1.0f + ex2(-LOG2E * v)); }
__device__ __forceinline__ uint4 lds128(uint32_t a) {
    uint4 v;
    asm volatile("ld.shared.v4.u32 {%0,%1,%2,%3}, [%4];" : "=r"(v.x), "=r"(v.y), "=r"(v.z), "=r"(v.w) : "r"(a));
    return v;
}
__device__ __forceinline__ float4 lds128f(uint32_t a) {
    float4 v;
    asm volatile("ld.shared.v4.f32 {%0,%1,%2,%3}, [%4];" : "=f"(v.x), "=f"(v.y), "=f"(v.z), "=f"(v.w) : "r"(a));
    return v;
}
__device__ __forceinline__ float2 lds64f(uint32_t a) {
    float2 v;
    asm volatile("ld.shared.v2.f32 {%0,%1}, [%2];" : "=f"(v.x), "=f"(v.y) : "r"(a));
    return v;
}
__device__ __forceinline__ uint32_t lds32(uint32_t a) {
    uint32_t v;
    asm volatile("ld.shared.u32 %0, [%1];" : "=r"(v) : "r"(a));
    return v;
}
__device__ __forceinline__ void sts128(uint32_t a, uint32_t x, uint32_t y, uint32_t z, uint32_t w) {
    asm volatile("st.shared.v4.u32 [%0], {%1,%2,%3,%4};" :: "r"(a), "r"(x), "r"(y), "r"(z), "r"(w) : "memory");
}
__device__ __forceinline__ void sts64(uint32_t a, uint32_t x, uint32_t y) {
    asm volatile("st.shared.v2.u32 [%0], {%1,%2};" :: "r"(a), "r"(x), "r"(y) : "memory");
}
__device__ __forceinline__ void sts32(uint32_t a, uint32_t x) { asm volatile("st.shared.u32 [%0], %1;" :: "r"(a), "r"(x) : "memory"); }
__device__ __forceinline__ unsigned redux_max(unsigned v) {
    unsigned r;
    asm volatile("redux.sync.max.u32 %0, %1, 0xffffffff;" : "=r"(r) : "r"(v));
    return r;
}
__device__ __forceinline__ float shx(float v, int o) { return __shfl_xor_sync(0xffffffffu, v, o); }
__device__ __forceinline__ uint32_t U(float v) { return __float_as_uint(v); }
__device__ __forceinline__ float F(uint32_t v) { return __uint_as_float(v); }

__device__ __forceinline__ void wgmma_n192_lo(float (&d)[120], uint64_t da, uint64_t db, int scale_d) {
    asm volatile("{\n.reg .pred p;\nsetp.ne.b32 p, %98, 0;\n"
        "wgmma.mma_async.sync.aligned.m64n192k16.f32.bf16.bf16 "
        "{%0, %1, %2, %3, %4, %5, %6, %7, %8, %9, %10, %11, %12, %13, %14, %15, "
        "%16, %17, %18, %19, %20, %21, %22, %23, %24, %25, %26, %27, %28, %29, %30, %31, "
        "%32, %33, %34, %35, %36, %37, %38, %39, %40, %41, %42, %43, %44, %45, %46, %47, "
        "%48, %49, %50, %51, %52, %53, %54, %55, %56, %57, %58, %59, %60, %61, %62, %63, "
        "%64, %65, %66, %67, %68, %69, %70, %71, %72, %73, %74, %75, %76, %77, %78, %79, "
        "%80, %81, %82, %83, %84, %85, %86, %87, %88, %89, %90, %91, %92, %93, %94, %95}, "
        "%96, %97, p, 1, 1, 0, 1;\n}\n"
        : "+f"(d[0]), "+f"(d[1]), "+f"(d[2]), "+f"(d[3]), "+f"(d[4]), "+f"(d[5]), "+f"(d[6]), "+f"(d[7]),
          "+f"(d[8]), "+f"(d[9]), "+f"(d[10]), "+f"(d[11]), "+f"(d[12]), "+f"(d[13]), "+f"(d[14]), "+f"(d[15]),
          "+f"(d[16]), "+f"(d[17]), "+f"(d[18]), "+f"(d[19]), "+f"(d[20]), "+f"(d[21]), "+f"(d[22]), "+f"(d[23]),
          "+f"(d[24]), "+f"(d[25]), "+f"(d[26]), "+f"(d[27]), "+f"(d[28]), "+f"(d[29]), "+f"(d[30]), "+f"(d[31]),
          "+f"(d[32]), "+f"(d[33]), "+f"(d[34]), "+f"(d[35]), "+f"(d[36]), "+f"(d[37]), "+f"(d[38]), "+f"(d[39]),
          "+f"(d[40]), "+f"(d[41]), "+f"(d[42]), "+f"(d[43]), "+f"(d[44]), "+f"(d[45]), "+f"(d[46]), "+f"(d[47]),
          "+f"(d[48]), "+f"(d[49]), "+f"(d[50]), "+f"(d[51]), "+f"(d[52]), "+f"(d[53]), "+f"(d[54]), "+f"(d[55]),
          "+f"(d[56]), "+f"(d[57]), "+f"(d[58]), "+f"(d[59]), "+f"(d[60]), "+f"(d[61]), "+f"(d[62]), "+f"(d[63]),
          "+f"(d[64]), "+f"(d[65]), "+f"(d[66]), "+f"(d[67]), "+f"(d[68]), "+f"(d[69]), "+f"(d[70]), "+f"(d[71]),
          "+f"(d[72]), "+f"(d[73]), "+f"(d[74]), "+f"(d[75]), "+f"(d[76]), "+f"(d[77]), "+f"(d[78]), "+f"(d[79]),
          "+f"(d[80]), "+f"(d[81]), "+f"(d[82]), "+f"(d[83]), "+f"(d[84]), "+f"(d[85]), "+f"(d[86]), "+f"(d[87]),
          "+f"(d[88]), "+f"(d[89]), "+f"(d[90]), "+f"(d[91]), "+f"(d[92]), "+f"(d[93]), "+f"(d[94]), "+f"(d[95])
        : "l"(da), "l"(db), "r"(scale_d));
}
__device__ __forceinline__ void wgmma_n48_hi(float (&d)[120], uint64_t da, uint64_t db, int scale_d) {
    asm volatile("{\n.reg .pred p;\nsetp.ne.b32 p, %26, 0;\n"
        "wgmma.mma_async.sync.aligned.m64n48k16.f32.bf16.bf16 "
        "{%0, %1, %2, %3, %4, %5, %6, %7, %8, %9, %10, %11, %12, %13, %14, %15, "
        "%16, %17, %18, %19, %20, %21, %22, %23}, "
        "%24, %25, p, 1, 1, 0, 1;\n}\n"
        : "+f"(d[96]), "+f"(d[97]), "+f"(d[98]), "+f"(d[99]), "+f"(d[100]), "+f"(d[101]), "+f"(d[102]), "+f"(d[103]),
          "+f"(d[104]), "+f"(d[105]), "+f"(d[106]), "+f"(d[107]), "+f"(d[108]), "+f"(d[109]), "+f"(d[110]), "+f"(d[111]),
          "+f"(d[112]), "+f"(d[113]), "+f"(d[114]), "+f"(d[115]), "+f"(d[116]), "+f"(d[117]), "+f"(d[118]), "+f"(d[119])
        : "l"(da), "l"(db), "r"(scale_d));
}
__device__ __forceinline__ void wgmma_rs_n80(float (&d)[40], uint32_t a0, uint32_t a1, uint32_t a2, uint32_t a3, uint64_t db, int scale_d) {
    asm volatile("{\n.reg .pred p;\nsetp.ne.b32 p, %45, 0;\n"
        "wgmma.mma_async.sync.aligned.m64n80k16.f32.bf16.bf16 "
        "{%0, %1, %2, %3, %4, %5, %6, %7, %8, %9, %10, %11, %12, %13, %14, %15, "
        "%16, %17, %18, %19, %20, %21, %22, %23, %24, %25, %26, %27, %28, %29, %30, %31, "
        "%32, %33, %34, %35, %36, %37, %38, %39}, "
        "{%40, %41, %42, %43}, %44, p, 1, 1, 1;\n}\n"
        : "+f"(d[0]), "+f"(d[1]), "+f"(d[2]), "+f"(d[3]), "+f"(d[4]), "+f"(d[5]), "+f"(d[6]), "+f"(d[7]),
          "+f"(d[8]), "+f"(d[9]), "+f"(d[10]), "+f"(d[11]), "+f"(d[12]), "+f"(d[13]), "+f"(d[14]), "+f"(d[15]),
          "+f"(d[16]), "+f"(d[17]), "+f"(d[18]), "+f"(d[19]), "+f"(d[20]), "+f"(d[21]), "+f"(d[22]), "+f"(d[23]),
          "+f"(d[24]), "+f"(d[25]), "+f"(d[26]), "+f"(d[27]), "+f"(d[28]), "+f"(d[29]), "+f"(d[30]), "+f"(d[31]),
          "+f"(d[32]), "+f"(d[33]), "+f"(d[34]), "+f"(d[35]), "+f"(d[36]), "+f"(d[37]), "+f"(d[38]), "+f"(d[39])
        : "r"(a0), "r"(a1), "r"(a2), "r"(a3), "l"(db), "r"(scale_d));
}
__device__ __forceinline__ void wgmma_rs_n192_lo(float (&d)[120], uint32_t a0, uint32_t a1, uint32_t a2, uint32_t a3, uint64_t db, int scale_d) {
    asm volatile("{\n.reg .pred p;\nsetp.ne.b32 p, %101, 0;\n"
        "wgmma.mma_async.sync.aligned.m64n192k16.f32.bf16.bf16 "
        "{%0, %1, %2, %3, %4, %5, %6, %7, %8, %9, %10, %11, %12, %13, %14, %15, "
        "%16, %17, %18, %19, %20, %21, %22, %23, %24, %25, %26, %27, %28, %29, %30, %31, "
        "%32, %33, %34, %35, %36, %37, %38, %39, %40, %41, %42, %43, %44, %45, %46, %47, "
        "%48, %49, %50, %51, %52, %53, %54, %55, %56, %57, %58, %59, %60, %61, %62, %63, "
        "%64, %65, %66, %67, %68, %69, %70, %71, %72, %73, %74, %75, %76, %77, %78, %79, "
        "%80, %81, %82, %83, %84, %85, %86, %87, %88, %89, %90, %91, %92, %93, %94, %95}, "
        "{%96, %97, %98, %99}, %100, p, 1, 1, 1;\n}\n"
        : "+f"(d[0]), "+f"(d[1]), "+f"(d[2]), "+f"(d[3]), "+f"(d[4]), "+f"(d[5]), "+f"(d[6]), "+f"(d[7]),
          "+f"(d[8]), "+f"(d[9]), "+f"(d[10]), "+f"(d[11]), "+f"(d[12]), "+f"(d[13]), "+f"(d[14]), "+f"(d[15]),
          "+f"(d[16]), "+f"(d[17]), "+f"(d[18]), "+f"(d[19]), "+f"(d[20]), "+f"(d[21]), "+f"(d[22]), "+f"(d[23]),
          "+f"(d[24]), "+f"(d[25]), "+f"(d[26]), "+f"(d[27]), "+f"(d[28]), "+f"(d[29]), "+f"(d[30]), "+f"(d[31]),
          "+f"(d[32]), "+f"(d[33]), "+f"(d[34]), "+f"(d[35]), "+f"(d[36]), "+f"(d[37]), "+f"(d[38]), "+f"(d[39]),
          "+f"(d[40]), "+f"(d[41]), "+f"(d[42]), "+f"(d[43]), "+f"(d[44]), "+f"(d[45]), "+f"(d[46]), "+f"(d[47]),
          "+f"(d[48]), "+f"(d[49]), "+f"(d[50]), "+f"(d[51]), "+f"(d[52]), "+f"(d[53]), "+f"(d[54]), "+f"(d[55]),
          "+f"(d[56]), "+f"(d[57]), "+f"(d[58]), "+f"(d[59]), "+f"(d[60]), "+f"(d[61]), "+f"(d[62]), "+f"(d[63]),
          "+f"(d[64]), "+f"(d[65]), "+f"(d[66]), "+f"(d[67]), "+f"(d[68]), "+f"(d[69]), "+f"(d[70]), "+f"(d[71]),
          "+f"(d[72]), "+f"(d[73]), "+f"(d[74]), "+f"(d[75]), "+f"(d[76]), "+f"(d[77]), "+f"(d[78]), "+f"(d[79]),
          "+f"(d[80]), "+f"(d[81]), "+f"(d[82]), "+f"(d[83]), "+f"(d[84]), "+f"(d[85]), "+f"(d[86]), "+f"(d[87]),
          "+f"(d[88]), "+f"(d[89]), "+f"(d[90]), "+f"(d[91]), "+f"(d[92]), "+f"(d[93]), "+f"(d[94]), "+f"(d[95])
        : "r"(a0), "r"(a1), "r"(a2), "r"(a3), "l"(db), "r"(scale_d));
}
__device__ __forceinline__ void wgmma_rs_n48_hi(float (&d)[120], uint32_t a0, uint32_t a1, uint32_t a2, uint32_t a3, uint64_t db, int scale_d) {
    asm volatile("{\n.reg .pred p;\nsetp.ne.b32 p, %29, 0;\n"
        "wgmma.mma_async.sync.aligned.m64n48k16.f32.bf16.bf16 "
        "{%0, %1, %2, %3, %4, %5, %6, %7, %8, %9, %10, %11, %12, %13, %14, %15, "
        "%16, %17, %18, %19, %20, %21, %22, %23}, "
        "{%24, %25, %26, %27}, %28, p, 1, 1, 1;\n}\n"
        : "+f"(d[96]), "+f"(d[97]), "+f"(d[98]), "+f"(d[99]), "+f"(d[100]), "+f"(d[101]), "+f"(d[102]), "+f"(d[103]),
          "+f"(d[104]), "+f"(d[105]), "+f"(d[106]), "+f"(d[107]), "+f"(d[108]), "+f"(d[109]), "+f"(d[110]), "+f"(d[111]),
          "+f"(d[112]), "+f"(d[113]), "+f"(d[114]), "+f"(d[115]), "+f"(d[116]), "+f"(d[117]), "+f"(d[118]), "+f"(d[119])
        : "r"(a0), "r"(a1), "r"(a2), "r"(a3), "l"(db), "r"(scale_d));
}
__device__ __forceinline__ void wgmma_n8(float (&d)[4], uint64_t da, uint64_t db, int scale_d) {
    asm volatile("{\n.reg .pred p;\nsetp.ne.b32 p, %6, 0;\n"
                 "wgmma.mma_async.sync.aligned.m64n8k16.f32.bf16.bf16 {%0, %1, %2, %3}, %4, %5, p, 1, 1, 1, 0;\n}\n"
                 : "+f"(d[0]), "+f"(d[1]), "+f"(d[2]), "+f"(d[3]) : "l"(da), "l"(db), "r"(scale_d));
}
__device__ __forceinline__ constexpr int jt_of(int sec, int c, bool odd) {
    return odd ? (c >= 2 ? sec * 8 + c - 2 : 24 + sec * 2 + c) : (c < 8 ? sec * 8 + c : 24 + sec * 2 + (c - 8));
}
#define BOTH(...) if (hg & ODDX) { constexpr bool odd = true; __VA_ARGS__ } else { constexpr bool odd = false; __VA_ARGS__ }

__device__ __forceinline__ bool elect() {
    uint32_t r;
    asm volatile("{\n.reg .pred p;\nelect.sync _|p, 0xffffffff;\nselp.u32 %0, 1, 0, p;\n}" : "=r"(r));
    return r != 0;
}
__device__ __forceinline__ uint32_t clock32() { uint32_t r; asm volatile("mov.u32 %0, %%clock;" : "=r"(r)); return r; }
#define BLOCK_SPLIT(v) asm volatile("{\n.reg .pred p;\nLAB_SPLIT:\nsetp.eq.u32 p, %0, 0;\n@p nanosleep.u32 1;\n@p bra LAB_SPLIT;\n}" :: "r"(v) : "memory")
__device__ __forceinline__ bool any(bool v) { return __any_sync(0xffffffffu, v); }
__device__ __forceinline__ bool retry(unsigned& spins) { __nanosleep(100); return ++spins < SPIN; }
__device__ __forceinline__ uint32_t opaque_tid() { uint32_t r; asm volatile("mov.u32 %0, %%tid.x;" : "=r"(r)); return r; }

template <bool BY_SM>
__global__ void __cluster_dims__(2, 1, 1) __launch_bounds__(NTHREADS, 1)
fused_kernel(const __grid_constant__ Params P) {
    extern __shared__ __align__(1024) uint8_t smem[];
    const uint32_t sb = (uint32_t)__cvta_generic_to_shared(smem);
    const uint32_t warp = __shfl_sync(0xffffffffu, threadIdx.x >> 5, 0);
    const uint32_t rank = blockIdx.x & 1;
    constexpr uint32_t sbd = 1024 >> 4;
    const uint32_t t0 = clock32();
    if (warp >= 8 && elect()) {
        const uint32_t bb = sb + B_Z - 256 + (warp ^ 1) * 32;
        const int cnt = ((0xF00F7027u >> (4 * (warp - 8))) & 15) + 1;
        mbar_init(bb, cnt); mbar_init(bb + 8, cnt); mbar_init(bb + 16, cnt); mbar_init(bb + 24, cnt);
        if (warp == 10) { mbar_expect_tx(sb + B_H, 1024); mbar_expect_tx(sb + B_GU, 40960); }
        if (warp == 13) mbar_expect_tx(sb + B_FULL + 16, ST);
        asm volatile("fence.mbarrier_init.release.cluster;" ::: "memory");
    }
    __syncwarp();
    cluster_arrive();
    if (warp < 3 && elect()) asm volatile("prefetch.tensormap [%0];" :: "l"(&P.tm[warp]) : "memory");
    if ((sb & 0xFFFFFF) != 1024) __trap();
    uint32_t gpc = blockIdx.x >> 4, pos = (blockIdx.x >> 1) & 7;
    if (BY_SM) {
        uint32_t tpc;
        asm("mov.u32 %0, %%smid;" : "=r"(tpc));
        tpc >>= 1;
        if (tpc - 60 < 2) {
            __nanosleep(2000);
            return;
        }
        const uint32_t q = ((tpc - 32) * 37) >> 8;
        gpc = tpc < 32 ? tpc & 7 : (tpc < 60 ? tpc - 31 - 7 * q : 0);
        pos = tpc < 32 ? tpc >> 3 : (tpc < 60 ? 4 + q : tpc - 58);
    }
    const uint32_t hg = (HGMAP >> (4 * pos)) & 7, rb = gpc * 2 + rank, fp = 8 * pos + gpc - 10;
    const uint32_t b = rb * 8 + hg;
    const uint32_t k0 = (((hg >> 2) ^ (rb >> 1)) & 1) * 320;

    if (warp == 13 && elect()) tma(sb + 2 * ST, &P.tm[T_X], sb + B_FULL + 16, k0, rb * 64);
    if (warp == 12) {
        cluster_wait();
        if (elect()) {
            tma_mc(sb + 2 * ST + ST_BM + rank * 12288, &P.tm[T_W], sb + B_FULL + 16, hg * 80 + (hg & ODDX) * 16, k0 + rank * 32);
            tma_mc(sb + 2 * ST + ST_BR + rank * 3072, &P.tm[T_WR], sb + B_FULL + 16, hg * 80 + 64 - (hg & ODDX) * 64, k0 + rank * 32);
        }
        __syncwarp();
    }

    if (warp < 8) {
        asm volatile("setmaxnreg.inc.sync.aligned.u32 208;");
        const uint32_t lane = opaque_tid() & 31, g = lane >> 2, t = lane & 3;
        const uint32_t p = warp >> 2, w = warp & 3;
        const uint32_t empty_cl = mapa(sb + B_EMPTY, lane & 1);
        uint8_t* const orow = P.scr + (rb * (8 * XB) + warp * 2560 + lane * 16);
        const uint32_t ta = sb + warp * 2560 + (lane & 15) * 160 + (lane >> 4) * 16;
        uint32_t A[7][20];
        TRD(r12); TRD(r32); TRD(r34); TRD(r22); TRD(r44);
        uint32_t par;
        uint8_t* const halo = orow + (hg * XB + (8 + p - warp) * 2560);
        uint8_t* const flag = P.scr + (G_FLAG + b * XB + w * 8 + p * 4);
        cluster_wait();
        {
            float acc[120];
            bool ok;
            uint32_t xr[5][4];
            float2 s0, s1;
            const uint32_t xa = sb + (warp * 16 + (lane & 15)) * 128 + (((lane >> 4) ^ (lane & 7)) << 4);
            mbar_wait(sb + B_FULL + 16, 0);
#pragma unroll
            for (uint32_t kb = 2; kb < 12; kb++) {
                const uint32_t s = kb & 3;
                const bool hold = kb == 12 - LEAD && p;
                if (hold) {
                    wgmma_wait<0>();
                    if (lane < 2) mbar_arrive_cl(empty_cl + 8 * ((11 - LEAD) & 3));
                    bar_sync(1, 256);
                }
                wgmma_fence();
                const uint32_t st = sbd + s * (ST >> 4);
#pragma unroll
                for (int ks = 0; ks < 4; ks++) {
                    const uint64_t da = mk(st + p * 512 + ks * 2 + 0x10000, HI128);
                    wgmma_n48_hi(acc, da, mk(st + (ST_BR >> 4) + (ks >> 1) * 192 + (ks & 1) * 32 + (64 << 16), HI32), ks || kb > 2);
                    wgmma_n192_lo(acc, da, mk(st + (ST_BM >> 4) + (ks >> 1) * 768 + (ks & 1) * 128 + (256 << 16), HI128), ks || kb > 2);
                    if (ks == 0) {
                        wgmma_commit();
                        wgmma_wait<1>();
                        if (!hold && kb > 2 && lane < 2) mbar_arrive_cl(empty_cl + 8 * ((kb - 1) & 3));
                    }
                    if (ks == 1) {
#pragma unroll
                        for (uint32_t j = 0; j < 5; j++)
                            if (((5 * hg + j) >> 2) == kb - 2 + (kb < 7 ? k0 >> 6 : -(k0 >> 6))) ldsm_x4(xr[j], (xa + s * ST) ^ (((hg + j) & 3) << 5));
                        if (w == 3 && kb < 7) stg128(halo + (kb - 2) * 512, 0u, 0u, 0u, 0u);
                        if (lane == 0 && kb == 2) stg32(flag, 0u);
                        if (kb < 11) ok = mbar_try(sb + B_FULL + 8 * ((kb + 1) & 3), ((kb - 1) >> 2) & 1);
                        if (kb == 11) {
                            ok = mbar_try(sb + B_PREP, 0);
                            s0 = lds64f(sb + M_ST + (warp * 16 + g) * 8); s1 = lds64f(sb + M_ST + (warp * 16 + g + 8) * 8);
                            par = lds32(sb + M_SEL + 8);
                        }
                    }
                }
                wgmma_commit();
                if (kb < 11 && !ok) mbar_wait(sb + B_FULL + 8 * ((kb + 1) & 3), ((kb - 1) >> 2) & 1);
            }
            if (!ok) {
                mbar_wait(sb + B_PREP, 0);
                s0 = lds64f(sb + M_ST + (warp * 16 + g) * 8); s1 = lds64f(sb + M_ST + (warp * 16 + g + 8) * 8);
                par = lds32(sb + M_SEL + 8);
            }
            {
                const uint32_t a0 = t ? 0u : __byte_perm(U(-s0.y), 0, 0x3232), a1 = t ? 0u : __byte_perm(U(-s1.y), 0, 0x3232);
                wgmma_fence();
                wgmma_rs_n48_hi(acc, a0, a1, 0u, 0u, mk(sbd + (M_CS >> 4) + 48, 2), 1);
                wgmma_rs_n192_lo(acc, a0, a1, 0u, 0u, mk(sbd + (M_CS >> 4), 2), 1);
                wgmma_commit();
            }
            if (!p) bar_arrive(1, 256);
            wgmma_wait<0>();
#pragma unroll
            for (int i = 0; i < 120; i++) asm volatile("" : "+f"(acc[i]) :: "memory");
            if (lane < 2) mbar_arrive_cl(empty_cl + 24);
            TR(r12);
            uint32_t Q[10], Ql[10], KX[10], VX[10], Y[20];
#define KI(c) ((c) == 2 ? 8 : (c) == 7 ? 9 : (c) - ((c) > 2) - ((c) > 7))
#define KY(c) Y[KI(c)]
#define VY(c) Y[10 + (c)]
            uint32_t Z[20];
            const bool start = w == 0 && rb == 0, remote = w == 0 && rb != 0;
            const uint32_t slot = sb + OFF_G + warp * 2560 + lane * 16;
            {
                BOTH(_Pragma("unroll") for (int c = 0; c < 10; c++) {
                    const int jk = jt_of(1, c, odd), jv = jt_of(2, c, odd);
                    VY(c) = movm(pack_bf16(acc[4 * jv + 2] * s1.x, acc[4 * jv + 3] * s1.x));
                    KY(c) = pack_bf16(acc[4 * jk + 2] * s1.x, acc[4 * jk + 3] * s1.x);
                    asm volatile("" : "+r"(KY(c)), "+r"(VY(c)));
                })
                if (w == 3) {
#pragma unroll
                    for (int j = 0; j < 5; j++) {
                        Y[4 * j] = (Y[4 * j] & ~0x10001u) | par;
                        stg128(halo + j * 512, Y[4 * j], Y[4 * j + 1], Y[4 * j + 2], Y[4 * j + 3]);
                    }
                } else {
                    mbar_wait(sb + B_EMPTY + 8, 1);
#pragma unroll
                    for (int j = 0; j < 5; j++) sts128(slot + 2560 + j * 512, Y[4 * j], Y[4 * j + 1], Y[4 * j + 2], Y[4 * j + 3]);
                }
                BOTH(_Pragma("unroll") for (int c = 0; c < 10; c++) {
                    const int jk = jt_of(1, c, odd), jv = jt_of(2, c, odd);
                    KX[c] = pack_bf16(acc[4 * jk] * s0.x, acc[4 * jk + 1] * s0.x);
                    VX[c] = movm(pack_bf16(acc[4 * jv] * s0.x, acc[4 * jv + 1] * s0.x));
                    asm volatile("" : "+r"(KX[c]), "+r"(VX[c]));
                })
                BLOCK_SPLIT(par);
                bar_sync(2 + p, 128);
                if (remote) {
#pragma unroll
                    for (int j = 0; j < 5; j++) ldg128(halo - 8 * XB + j * 512, Z[4 * j], Z[4 * j + 1], Z[4 * j + 2], Z[4 * j + 3]);
                } else {
#pragma unroll
                    for (int j = 0; j < 5; j++) {
                        const uint4 v = lds128(slot + (w ? 0 : 2560) + j * 512);
                        Z[4 * j] = v.x; Z[4 * j + 1] = v.y; Z[4 * j + 2] = v.z; Z[4 * j + 3] = v.w;
                    }
                }
                BOTH(_Pragma("unroll") for (int c = 0; c < 10; c++) {
                    const int jq = jt_of(0, c, odd);
                    Ql[c] = pack_bf16(acc[4 * jq], acc[4 * jq + 1]);
                    Q[c] = pack_bf16(acc[4 * jq + 2], acc[4 * jq + 3]);
                    asm volatile("" : "+r"(Ql[c]), "+r"(Q[c]));
                })
            }
            auto unit = [&](const uint32_t (&q)[10], const uint32_t (&z)[20], const int c0, const uint32_t mx, const float sq, const float nz, const int h) {
                const uint32_t qa = t < 2 ? q[c0 + 2] : 0u, qb = t < 2 ? 0u : q[c0 + 2];
                float xa[4] = {0.f, 0.f, 0.f, 0.f}, za[4] = {0.f, 0.f, 0.f, 0.f}, xb[4], zb[4];
                mma1688(xa, qa, qb, KX[c0 + 2]);
                mma1688(za, qa, qb, z[KI(c0 + 2)]);
#pragma unroll
                for (int e = 0; e < 4; e++) { xb[e] = xa[e]; zb[e] = za[e]; }
                mma16816(xa, q[c0], q[c0 + 3], q[c0 + 1], q[c0 + 4], KX[c0], KX[c0 + 1]);
                mma16816(za, q[c0], q[c0 + 3], q[c0 + 1], q[c0 + 4], z[KI(c0)], z[KI(c0 + 1)]);
                mma16816(xb, q[c0], q[c0 + 3], q[c0 + 1], q[c0 + 4], KX[c0 + 3], KX[c0 + 4]);
                mma16816(zb, q[c0], q[c0 + 3], q[c0 + 1], q[c0 + 4], z[KI(c0 + 3)], z[KI(c0 + 4)]);
                const bool h0 = mx & 1u, h1 = (int)mx < 0;
                const float l00 = h0 ? xa[0] : za[0] + nz, l01 = h1 ? xa[1] : za[1] + nz;
                const float l10 = h0 ? xb[2] : zb[2] + nz, l11 = h1 ? xb[3] : zb[3] + nz;
                float m0 = fmaxf(l00, l01), m1 = fmaxf(l10, l11);
                m0 = fmaxf(m0, shx(m0, 1)); m1 = fmaxf(m1, shx(m1, 1));
                m0 = fmaxf(m0, shx(m0, 2)) * -sq; m1 = fmaxf(m1, shx(m1, 2)) * -sq;
                const uint32_t pa = pack_bf16(ex2(fmaf(l00, sq, m0)), ex2(fmaf(l01, sq, m0)));
                const uint32_t pb = pack_bf16(ex2(fmaf(l10, sq, m1)), ex2(fmaf(l11, sq, m1)));
                float dn[4] = {0.f, 0.f, 0.f, 0.f};
                mma1688(dn, pa, pb, 0x3F803F80u);
                const float i0 = rcp(dn[0]), i1 = rcp(dn[2]), i2 = t < 2 ? i0 : i1;
#pragma unroll
                for (int c = 0; c < 5; c++) {
                    float oc[4] = {0.f, 0.f, 0.f, 0.f};
                    mma16816(oc, pa & mx, pb & mx, pa & ~mx, pb & ~mx, VX[c0 + c], z[10 + c0 + c]);
                    const bool first = c < 2 || (c == 2 && t < 2);
                    const float iv = c < 2 ? i0 : (c > 2 ? i1 : i2);
                    A[0][2 * (c0 + c) + h] = pack_bf16((first ? oc[0] : oc[2]) * iv, (first ? oc[1] : oc[3]) * iv);
                }
            };
            const uint32_t mo = (2 * t > g ? 0xFFFFu : 0u) | (2 * t + 1 > g ? 0xFFFF0000u : 0u);
            constexpr float SC = 0.22360679774997896f * LOG2E;
            {
                unsigned spins = 0;
#pragma unroll 1
                while (remote && any((Z[0] & Z[4] & Z[8] & Z[12] & Z[16] & par) == 0u) && ++spins < SPIN) {
#pragma unroll
                    for (int j = 0; j < 5; j++) ldg128(halo - 8 * XB + j * 512, Z[4 * j], Z[4 * j + 1], Z[4 * j + 2], Z[4 * j + 3]);
                }
                TR(r32);
                const float nz = start ? -INFINITY : 0.f;
                unit(Q, Y, 0, mo, s1.x * SC, 0.f, 1);
                unit(Q, Y, 5, mo, s1.x * SC, 0.f, 1);
                unit(Ql, Z, 0, ~mo, s0.x * SC, nz, 0);
                unit(Ql, Z, 5, ~mo, s0.x * SC, nz, 0);
            }
#pragma unroll
            for (int j = 0; j < 5; j++) {
                A[0][4 * j] = (A[0][4 * j] & ~0x10001u) | par;
                stg128(orow + hg * XB + j * 512, A[0][4 * j], A[0][4 * j + 1], A[0][4 * j + 2], A[0][4 * j + 3]);
            }
            if (lane == 0) stg32(flag, par);
            TR(r34);
            if (p) bar_arrive(8, 384);
            BLOCK_SPLIT(par);
            {
                const float r0 = 0.5f * s0.x, r1 = 0.5f * s1.x, n0 = -r0 * s0.y, n1 = -r1 * s1.y;
#pragma unroll
                for (int j = 0; j < 5; j++) {
                    uint32_t gf[4];
#pragma unroll
                    for (int q = 0; q < 4; q++) {
                        const float v0 = fmaf(bflo(xr[j][q]), q & 1 ? r1 : r0, q & 1 ? n1 : n0), v1 = fmaf(bfhi(xr[j][q]), q & 1 ? r1 : r0, q & 1 ? n1 : n0);
                        gf[q] = pack_bf16(fmaf(v0, tanh_a(v0), v0), fmaf(v1, tanh_a(v1), v1));
                    }
                    stsm_x4(ta + OFF_G + j * 32, gf);
                    stsm_x4(ta + OFF_X + j * 32, xr[j]);
                }
            }
        }
        {
            float acc2[40];
            unsigned spins = 0;
            bool again, first = true;
            const uint8_t* src[7];
#pragma unroll
            for (uint32_t i = 0; i < 7; i++) { src[i] = orow + (i >= hg ? XB : 0u); asm volatile("" : "+l"(src[i])); }
            uint32_t a0 = ta + (hg & 1) * 32, a4 = ta + (~hg & 1) * 128;
            asm volatile("" : "+r"(a0), "+r"(a4));
            mbar_wait(sb + B_SEL, 0);
            const float2 sel = lds64f(sb + M_SEL);
            uint32_t routed = (U(sel.x) >> 4) == warp || (U(sel.y) >> 4) == warp;
            asm volatile("" : "+r"(routed));
            uint32_t xf[5][4], gf[5][4];
            BLOCK_SPLIT(par);
            if (p) bar_sync(9, 288); else bar_sync(5, 160);
#pragma unroll 1
            do {
#pragma unroll
                for (uint32_t i = 1; i <= AHEAD; i++)
#pragma unroll
                    for (int j = 0; j < 5; j++)
                        ldg128(src[i - 1] + (i - 1) * XB + j * 512, A[i][4 * j], A[i][4 * j + 1], A[i][4 * j + 2], A[i][4 * j + 3]);
                if (!p && first) bar_sync(8, 384);
#pragma unroll
                for (int i = 0; i < 7; i++) {
                    if (i == 5 && !p && first) bar_sync(6, 160);
                    if (AHEAD < 6 || (i != 4 && i != 6)) wgmma_fence();
#pragma unroll
                    for (int j = 0; j < 5; j++) {
                        wgmma_rs_n80(acc2, A[i][4 * j], A[i][4 * j + 1], A[i][4 * j + 2], A[i][4 * j + 3],
                                     mk(sbd + ((OFF_WO + i * WO_SLOT) >> 4) + j * 64 + (320 << 16), HI64), i || j);
                        if (j == LDAT && i >= 1 && i + AHEAD <= 7) {
                            if (AHEAD < 6) bar_arrive(10, 32);
                            const int n = (i + AHEAD) % 7;
#pragma unroll
                            for (int q = 0; q < 5; q++)
                                ldg128(src[(n + 6) % 7] + ((n + 6) % 7) * XB + q * 512, A[n][4 * q], A[n][4 * q + 1], A[n][4 * q + 2], A[n][4 * q + 3]);
                            if (AHEAD < 6) bar_arrive(10, 32);
                        }
                        if (i == 6 && j == CHKJ) {
                            uint32_t mn = par;
#pragma unroll
                            for (int q = 1; q < 8; q++) mn &= A[q % 7][0] & A[q % 7][4] & A[q % 7][8] & A[q % 7][12] & A[q % 7][16];
                            again = bar_or(2 + p, 128, mn == 0u && ++spins < SPIN);
                        }
                    }
                    if (i < 2 || i > 4) wgmma_commit();
                    if (i == SERAT && !p && first) bar_arrive(9, 288);
                    if (i == 0) TR(r22);
                    if (i == 1) wgmma_wait<1>();
                }
                first = false;
                if (again) {
                    wgmma_wait<0>();
#pragma unroll
                    for (int j = 0; j < 5; j++)
                        ldg128(orow + hg * XB + j * 512, A[0][4 * j], A[0][4 * j + 1], A[0][4 * j + 2], A[0][4 * j + 3]);
                }
            } while (again);
            wgmma_wait<1>();
            wgmma_fence();
#pragma unroll
            for (int j = 0; j < 5; j++) {
                wgmma_rs_n80(acc2, A[0][4 * j], A[0][4 * j + 1], A[0][4 * j + 2], A[0][4 * j + 3],
                             mk(sbd + ((OFF_WO + 7 * WO_SLOT) >> 4) + j * 64 + (320 << 16), HI64), 1);
#pragma unroll
                for (int c = 0; c < 5; c++) {
                    if (LDJ < 5 ? j == LDJ : j == c) {
                        if (LDJ == 5 || (LDJ && c == 0)) bar_arrive(10, 32);
                        ldsm_x4(xf[c], (c < 4 ? a0 + c * 32 : a4) + OFF_X);
                        ldsm_x4(gf[c], (c < 4 ? a0 + c * 32 : a4) + OFF_G);
                    }
                }
            }
            wgmma_commit();
            if (routed) {
                const float2 sel = lds64f(sb + M_SEL);
                const uint32_t row = warp * 16 + (lane & 15);
                const uint32_t go = row == U(sel.x) ? M_UPD - row * 160 : (row == U(sel.y) ? M_UPD + 160 - row * 160 : OFF_G);
                mbar_wait(sb + B_UPD, 0);
#pragma unroll
                for (int c = 0; c < 5; c++) ldsm_x4(gf[c], (c < 4 ? a0 + c * 32 : a4) + go);
            }
            wgmma_wait<0>();
#pragma unroll
            for (int i = 0; i < 40; i++) asm volatile("" : "+f"(acc2[i]) :: "memory");
            TR(r44);
#pragma unroll
            for (int c = 0; c < 5; c++) {
#pragma unroll
                for (int q = 0; q < 4; q++)
                    asm("fma.rn.bf16x2 %0, %1, %2, %0;" : "+r"(xf[c][q]) : "r"(pack_bf16(acc2[8 * c + 2 * q], acc2[8 * c + 2 * q + 1])), "r"(gf[c][q]));
                stsm_x4((c < 4 ? a0 + c * 32 : a4) + OFF_X, xf[c]);
            }
            fence_proxy_async_smem();
            __syncwarp();
            if (lane == 0) {
                tma_st(&P.tm[T_OUT], sb + OFF_X + warp * 2560, hg * 80, rb * 64 + 16 * w, p);
                asm volatile("cp.async.bulk.wait_group.read 0;" ::: "memory");
            }
        }
        TS(46);
        TRW(r12, 12); TRW(r32, 32); TRW(r34, 34); TRW(r22, 22); TRW(r44, 44);
    } else if (warp >= 12) {
        asm volatile("setmaxnreg.dec.sync.aligned.u32 24;");
        if (warp == 12) {
            uint32_t slot = t0 + PACE0;
            if (elect()) {
                TS(48);
#pragma unroll 1
                for (uint32_t kb = 1; kb < 10; kb++) {
                    const uint32_t s = (kb + 2) & 3;
                    const uint32_t st = sb + s * ST, fb = sb + B_FULL + 8 * s;
                    const uint32_t kc = kb * 64 + (kb < 5 ? k0 : -k0);
                    if (kb >= 4) {
                        mbar_wait(fb + 32, kb >> 3);
                        if (kb < 9) mbar_wait(sb + B_AX - 32 + 8 * kb, 0);
                    }
                    {
                        slot += PACE1;
#pragma unroll 1
                        while ((int)(clock32() - slot) < 0) { }
                        mbar_expect_tx(fb, ST);
                        tma(st, &P.tm[T_X], fb, kc, rb * 64);
                    }
                    tma_mc(st + ST_BM + rank * 12288, &P.tm[T_W], fb, hg * 80 + (hg & ODDX) * 16, kc + rank * 32);
                    tma_mc(st + ST_BR + rank * 3072, &P.tm[T_WR], fb, hg * 80 + 64 - (hg & ODDX) * 64, kc + rank * 32);
                }
                TS(49);
                mbar_wait(sb + B_EMPTY, 1);
                mbar_expect_tx(sb + B_X, 20480);
                tma(sb + OFF_DN, &P.tm[T_D], sb + B_X, 0, 32 * fp, 5 * rank);
                uint32_t wb = sb + B_WO - 8;
#pragma unroll 1
                for (uint32_t i = 0; i < 8; i++) {
                    if ((0x25 >> i) & 1) {
                        wb += 8;
                        mbar_wait(wb - (B_WO - B_EMPTY - 8), i == 0);
                        mbar_expect_tx(wb, i == 0 ? 2 * 12800 : 3 * 12800);
                    }
                    if (WOP) {
#pragma unroll 1
                        while ((int)(clock32() - slot) < 0) { }
                        slot = clock32() + WOP;
                    }
                    const uint32_t d = sb + OFF_WO + i * WO_SLOT;
                    const uint32_t kr = 80 * (i ? i - (i <= hg) : hg);
                    tma_mc(d + rank * 5120, &P.tm[T_WO], wb, hg * 80 + (hg & 1) * 16 + rank * 32, kr);
                    tma_mc(d + 10240 + rank * 2560, &P.tm[T_WOR], wb, hg * 80 + (~hg & 1) * 64, kr + rank * 40);
                }
                TS(50);
            }
        } else if (warp == 13) {
            if (elect()) {
#pragma unroll 1
                for (uint32_t i = 0; i < 3; i++) {
#pragma unroll 1
                    while (clock32() - t0 < PX0 + i * PX1) __nanosleep(20);
                    l2_prefetch(P.w + ((i + 2) * 245760 + b * 1920), 1920);
                    l2_prefetch(P.w + ((i + 7) * 245760 + b * 1920), 1920);
                }
#pragma unroll 1
                for (uint32_t i = 0; i < 14; i++) {
#pragma unroll 1
                    while (clock32() - t0 < GU0 + i * GU1) __nanosleep(20);
                    if (i < 10) l2_prefetch(P.wd + (i * 128 + b) * 1728, 1728);
                    else l2_prefetch(P.wo + ((i - 10) * 128 + b) * 1600, 1600);
                }
                TS(59);
            }
        } else if (warp == 15) {
            const uint32_t lane = opaque_tid() & 31;
            const uint8_t* fl = P.scr + (G_FLAG + (rb * 8 + (lane & 7)) * XB + (lane >> 3) * 8);
            cluster_wait();
            mbar_wait(sb + B_PREP, 0);
            const uint32_t par = lds32(sb + M_SEL + 8);
            mbar_wait(sb + B_WO, 0); mbar_wait(sb + B_WO + 8, 0);
            unsigned spins = 0;
            TS(23);
            uint2 f;
#pragma unroll 1
            do f = ldg64(fl); while (any(f.x != par) && ++spins < SPIN);
            bar_arrive(5, 160);
            TS(24);
            mbar_wait(sb + B_WO + 16, 0);
            bar_arrive(6, 160);
#pragma unroll 1
            while (any(f.y != par) && ++spins < SPIN) f.y = ldg32(fl + 4);
            bar_arrive(9, 288);
            TS(25);
        } else {
            uint32_t slot = t0 + GT0;
            cluster_wait();
            if (elect()) {
#pragma unroll 1
                for (uint32_t i = 0; i < 20; i++) {
                    slot += GT1;
#pragma unroll 1
                    while ((int)(clock32() - slot) < 0) __nanosleep(20);
                    tma(sb + OFF_GU + i * 2048, &P.tm[T_GU], sb + B_GU, 32 * fp, rank * 320 + i * 16);
                }
            }
        }
    } else {
        asm volatile("setmaxnreg.dec.sync.aligned.u32 72;");
        const uint32_t at = opaque_tid() - 256, lane = at & 31, g = lane >> 2, t = lane & 3, c7 = lane & 7, aw = warp - 8;
        uint8_t* const yz = P.scr + (G_Y + b * 512 + at * 4);
        stg32(yz, 0u);
        __nanosleep(AUXS);
        const uint32_t epoch = ldg32(P.scr + G_EPOCH) + 1 + ldg32(yz), tag = (epoch & 15u) | 16u;
        const uint32_t empty_cl = mapa(sb + B_EMPTY, lane & 1);
        unsigned spins = 0;
        TRD(r51); TRD(r30); TRD(r52); TRD(r53); TRD(r54); TRD(r55); TRD(r20); TRD(r22);
        {
            const uint2 wv = __ldg(reinterpret_cast<const uint2*>(P.w_r + k0 * 2 + min(at, 79u) * 8));
            if (at < 80) sts64(sb + M_UPD + at * 8, wv.x, wv.y);
        }
        uint8_t* const stw = P.scr + (b * XB + G_ST + (lane & 4) * 64 + (at >> 3) * 16);
        uint8_t* const csw = P.scr + (b * XB + G_CS + at);
        uint8_t* const tpw = P.scr + (G_TOP + (hg >> 2) * XB + rb * 64 + aw * 16);
        const bool tpub = lane == 0 && (hg & 3) == TPUB;
        cluster_wait();
        bar_sync(4, 128);
        mbar_wait(sb + B_FULL + 16, 0);
        if (t == 0) { stg128(stw, 0u, 0u, 0u, 0u); stg32(csw, 0u); }
        if (tpub) stg128(tpw, 0u, 0u, 0u, 0u);

        uint32_t k1, sv;
        {
            const uint32_t xoff = (32 * (hg & 3) + (at >> 3)) * 128 + ((c7 ^ ((at >> 3) & 7)) << 4);
            const uint32_t jt = (rb >> 2) * 8 + rank * 4 + aw;
            const uint32_t coff = jt < 24 ? ST_BM + (jt >> 3) * 4096 + lane * 128 + (((jt ^ lane) & 7) << 4)
                                          : ST_BR + ((jt >> 1) & 3) * 1024 + lane * 32 + (((jt ^ g) & 1) << 4);
            float q[8], c8[8];
#pragma unroll
            for (int e = 0; e < 8; e++) q[e] = c8[e] = 0.f;
#pragma unroll 1
            for (uint32_t kb = 2; kb < 7; kb++) {
                const uint32_t st = sb + (kb & 3) * ST;
                const uint4 wv = lds128(sb + M_UPD - 256 + kb * 128 + c7 * 16);
                mbar_wait(sb + B_FULL + 8 * (kb & 3), kb == 6);
                const uint4 v = lds128(st + xoff), vn = lds128(st + xoff + 2048);
                const uint4 cv = lds128(st + coff), cn = lds128(st + coff + (jt < 24 ? 12288 : 3072));
                if (lane < 2) mbar_arrive_cl(empty_cl + (B_AX - B_EMPTY - 16) + 8 * kb + (cn.x & 0));
                const uint32_t u[4] = {v.x, v.y, v.z, v.w}, un[4] = {vn.x, vn.y, vn.z, vn.w}, ww[4] = {wv.x, wv.y, wv.z, wv.w};
                const uint32_t cc[4] = {cv.x, cv.y, cv.z, cv.w}, cd[4] = {cn.x, cn.y, cn.z, cn.w};
#pragma unroll
                for (int e = 0; e < 4; e++) {
                    const float a0 = bflo(u[e]), a1 = bfhi(u[e]), b0 = bflo(un[e]), b1 = bfhi(un[e]), w0 = bflo(ww[e]), w1 = bfhi(ww[e]);
                    q[0] += a0 + a1; q[4] += b0 + b1; q[3] += w0 + w1;
                    q[1] = fmaf(a0, a0, fmaf(a1, a1, q[1])); q[5] = fmaf(b0, b0, fmaf(b1, b1, q[5]));
                    q[2] = fmaf(a0, w0, fmaf(a1, w1, q[2])); q[6] = fmaf(b0, w0, fmaf(b1, w1, q[6]));
                    c8[2 * e] += bflo(cc[e]) + bflo(cd[e]); c8[2 * e + 1] += bfhi(cc[e]) + bfhi(cd[e]);
                }
            }
            TR(r51);
            q[7] = q[3];
#pragma unroll
            for (int e = 0; e < 4; e++) {
                q[e] = ((lane & 4) ? q[e + 4] : q[e]) + shx((lane & 4) ? q[e] : q[e + 4], 4);
                q[e] += shx(q[e], 1); q[e] += shx(q[e], 2);
            }
            const float mh = q[0] * (1.0f / 320);
            if (t == 0) stg128(stw, U(mh), U(fmaf(-mh, q[0], q[1])), U(q[2]), (U(q[3]) & ~31u) | tag);
#define TSTEP(H) { const bool up = (lane & (4 * H)) != 0; _Pragma("unroll") for (int e = 0; e < H; e++) { \
            const float send = up ? c8[e] : c8[e + H]; const float keep = up ? c8[e + H] : c8[e]; \
            c8[e] = keep + shx(send, 4 * H); } }
            TSTEP(4) TSTEP(2) TSTEP(1)
#undef TSTEP
            c8[0] += shx(c8[0], 1); c8[0] += shx(c8[0], 2);
            if (t == 0) stg32(csw, (U(c8[0]) & ~31u) | tag);
            TR(r30);
            const uint8_t* csp = P.scr + (G_CS + (aw * 32 + (lane >> 4) * 8 + hg) * XB + (lane & 15) * 8);
            const uint8_t* stp = P.scr + (G_ST + (rb * 8 + aw) * XB + lane * 16);
            uint32_t ra[4], rc[4];
            uint2 ca, cc;
#pragma unroll 1
            while (clock32() - t0 < EX1T) __nanosleep(20);
#pragma unroll 1
            do {
                ldg128(stp, ra[0], ra[1], ra[2], ra[3]);
                ldg128(stp + 4 * XB, rc[0], rc[1], rc[2], rc[3]);
                ca = ldg64(csp); cc = ldg64(csp + 16 * XB);
            } while (any((ra[3] ^ tag | rc[3] ^ tag) & 31u) && ++spins < SPIN);
            TR(r20);
            const float dm = 0.5f * (F(ra[0]) - F(rc[0])), m = bf16r(F(rc[0]) + dm);
            const float sd = bf16r(sqrt_a(bf16r(bf16r(fmaxf(fmaf(dm, dm, (F(ra[1]) + F(rc[1])) * (1.0f / DM)), 0.f)) + 1e-5f)));
            const float rs = rcp(sd);
            uint32_t w1, w2;
            if ((hg & 3) == TPUB) {
                k1 = pack_bf16(0.f, fmaf(-m, F(ra[3]) + F(rc[3]), F(ra[2]) + F(rc[2])) * rs);
                k1 ^= ((int)k1 >> 31) | 0x80000000u;
                k1 = (k1 & 0xFFFF0000u) | ((2047 - (rb * 128 + 2 * (at & 63) + (at >> 6))) << 5) | tag;
                w1 = redux_max(k1); w2 = redux_max(k1 == w1 ? 0u : k1);
                sv = U(m) | (U(sd) >> 16);
                const uint32_t v1 = redux_max(k1 == w1 ? sv : 0u), v2 = redux_max(k1 == w2 ? sv : 0u);
                if (lane == 0) stg128(tpw, w1, v1, w2, v2);
            }
            sts64(sb + M_ST + at * 8, U(rs), U(m));
            sts32(sb + M_SEL + 8, (tag & 1) ? 1u : 0x10000u);
#pragma unroll 1
            while (any((ca.x ^ tag | ca.y ^ tag | cc.x ^ tag | cc.y ^ tag) & 31u) && ++spins < SPIN) { ca = ldg64(csp); cc = ldg64(csp + 16 * XB); }
            {
                const float c0 = at < 120 ? F(ca.x) + F(cc.x) : 0.f, c1 = at < 120 ? F(ca.y) + F(cc.y) : 0.f;
                const uint32_t hi = pack_bf16(c0, c1);
                sts32(sb + M_CS + (at >> 2) * 32 + t * 4, hi);
                sts32(sb + M_CS + (at >> 2) * 32 + t * 4 + 16, pack_bf16(c0 - bflo(hi), c1 - bfhi(hi)));
                fence_proxy_async_smem();
                __syncwarp();
                if (lane < 2) mbar_arrive(sb + B_PREP);
            }
            TR(r52);
            if (aw == 0) {
                uint32_t ka[4], kb[4];
#pragma unroll 1
                while (clock32() - t0 < EX1T + EX2D) __nanosleep(20);
#pragma unroll 1
                do {
                    const uint8_t* tp = P.scr + (G_TOP + lane * 16);
                    uint32_t kc[4], kd[4];
                    ldg128(tp, ka[0], ka[1], ka[2], ka[3]);
                    ldg128(tp + 512, kb[0], kb[1], kb[2], kb[3]);
                    ldg128(tp + XB, kc[0], kc[1], kc[2], kc[3]);
                    ldg128(tp + XB + 512, kd[0], kd[1], kd[2], kd[3]);
                    const bool ba = (ka[0] ^ tag) & 31u, bb = (kb[0] ^ tag) & 31u;
#pragma unroll
                    for (int e = 0; e < 4; e++) { ka[e] = ba ? kc[e] : ka[e]; kb[e] = bb ? kd[e] : kb[e]; }
                } while (any((ka[0] ^ tag | kb[0] ^ tag) & 31u) && ++spins < SPIN);
                TR(r22);
                if (kb[0] > ka[0]) {
#pragma unroll
                    for (int e = 0; e < 4; e++) { const uint32_t x = ka[e]; ka[e] = kb[e]; kb[e] = x; }
                }
                if (kb[0] > ka[2]) { ka[2] = kb[0]; ka[3] = kb[1]; }
                w1 = redux_max(ka[0]);
                const uint32_t t1 = redux_max(ka[0] == w1 ? ka[1] : 0u);
                if (ka[0] == w1) { ka[0] = ka[2]; ka[1] = ka[3]; }
                w2 = redux_max(ka[0]);
                const uint32_t t3 = redux_max(ka[0] == w2 ? ka[1] : 0u);
                sts128(sb + M_TOP, w1, t1, w2, t3);
            }
            bar_sync(4, 128);
            const float2 tv = lds64f(sb + M_TOP + (lane & 1) * 8);
            k1 = U(tv.x);
            sv = U(tv.y);
        }
        TR(r53);
        const uint32_t tok = ~(k1 >> 5) & 2047;
        const unsigned owns = __ballot_sync(0xffffffffu, (tok >> 7) == rb) & 3u;
        if (at < 2) sts32(sb + M_SEL + at * 4, (tok >> 7) == rb ? (tok & 1) * 64 + ((tok & 127) >> 1) : ~0u);
        if ((at | b) == 0) *reinterpret_cast<uint32_t*>(P.scr + G_EPOCH) = epoch;
        __syncwarp();
        if (at == 0) mbar_arrive(sb + B_SEL);
        if (fp < NFFN / 2) {
            uint4 xv = __ldg(reinterpret_cast<const uint4*>(P.x + (tok * 1280 + rank * 640 + min(at >> 1, 39u) * 16)));
            const uint32_t m2 = __byte_perm(sv, 0, 0x3232);
            asm("sub.rn.bf16x2 %0, %0, %4;\nsub.rn.bf16x2 %1, %1, %4;\nsub.rn.bf16x2 %2, %2, %4;\nsub.rn.bf16x2 %3, %3, %4;"
                : "+r"(xv.x), "+r"(xv.y), "+r"(xv.z), "+r"(xv.w) : "r"(m2));
            mbar_wait(sb + B_X, 0);
            if (at < 80) sts128(sb + OFF_PART + at * 16, xv.x, xv.y, xv.z, xv.w);
            mbar_wait(sb + B_GU, 0);
            mbar_wait(sb + B_EMPTY + 24, 0);
            bar_sync(4, 128);
            float c[5][4];
#pragma unroll
            for (int i = 0; i < 5; i++) c[i][0] = c[i][1] = c[i][2] = c[i][3] = 0.f;
            const uint32_t mi = lane >> 3, kr = c7 + (mi >> 1) * 8;
            {
                const uint32_t wa = sb + OFF_GU + (aw >> 1) * 1024 + kr * 64 + ((((aw & 1) * 2 + (mi & 1)) ^ ((kr >> 1) & 3)) << 4);
#pragma unroll
                for (uint32_t i = 0; i < 10; i++) {
                    uint32_t xb[4], a0[4], a1[4];
                    ldsm_x4(xb, sb + OFF_PART + i * 128 + mi * 32 + (lane & 1) * 16);
                    ldsm_x4_t(a0, wa + i * 4096);
                    ldsm_x4_t(a1, wa + i * 4096 + 2048);
                    mma16816(c[(2 * i) & 3], a0[0], a0[1], a0[2], a0[3], xb[0], xb[1]);
                    mma16816(c[(2 * i + 1) & 3], a1[0], a1[1], a1[2], a1[3], xb[2], xb[3]);
                }
#pragma unroll
                for (int e = 0; e < 4; e++) { c[0][e] = (c[0][e] + c[1][e]) + (c[2][e] + c[3][e]); }
                const uint32_t rd = mapa(sb, rank ^ (t & 1));
                if (t < 2)
                    asm volatile("st.async.shared::cluster.mbarrier::complete_tx::bytes.v4.f32 [%0], {%1,%2,%3,%4}, [%5];"
                                 :: "r"(rd + (t ? OFF_PART + 1280 : M_UPD + 192) + aw * 128 + g * 16), "f"(c[0][0]), "f"(c[0][1]), "f"(c[0][2]), "f"(c[0][3]), "r"(rd + B_H) : "memory");
            }
            TR(r54);
            const float rs = rcp(bflo(sv));
            const uint32_t da = sb + OFF_DN + kr * 128 + (((2 * aw + (mi & 1)) ^ c7) << 4);
            uint8_t* yp = P.scr + (G_Y + (fp % 6) * 10240 + rank * 2560 + t * 512 + aw * 128 + g * 16);
#pragma unroll
            for (int i = 0; i < 5; i++) c[i][0] = c[i][1] = c[i][2] = c[i][3] = 0.f;
            mbar_wait(sb + B_H, 0);
#pragma unroll
            for (uint32_t ks = 0; ks < 2; ks++) {
                const uint32_t og = sb + ks * 128 + lane * 4 + P.up_first, ou = og ^ 256;
                const float gs = bf16r((F(lds32(og + M_UPD + 192)) + F(lds32(og + OFF_PART + 1280))) * rs);
                const float h = bf16r(gs * sigm(gs)) * bf16r((F(lds32(ou + M_UPD + 192)) + F(lds32(ou + OFF_PART + 1280))) * rs);
                const uint32_t hp = pack_bf16(h, __shfl_down_sync(0xffffffffu, h, 4));
                const uint32_t h0 = __shfl_sync(0xffffffffu, hp, t * 8 + (g & 1)), h1 = __shfl_sync(0xffffffffu, hp, t * 8 + (g & 1) + 2);
#pragma unroll
                for (uint32_t j = 0; j < 5; j++) {
                    uint32_t a[4];
                    ldsm_x4_t(a, da + j * 4096 + ks * 2048);
                    mma16816(c[j], a[0], a[1], a[2], a[3], h0, h1);
                }
            }
#pragma unroll
            for (int e = 0; e < 4; e++) {
                const float lo = (t & 1) ? c[1][e] : c[0][e], hi = (t & 1) ? c[3][e] : c[2][e];
                c[0][e] = (t & 2) ? hi : lo;
            }
            asm volatile("" : "+f"(c[0][0]), "+f"(c[4][0]) :: "memory");
            BLOCK_SPLIT(tag);
            bar_sync(8, 384);
            { red4(yp, c[0][0], c[0][2]); red4(yp + 5120, c[0][1], c[0][3]); }
            if (t == 0) { red4(yp + 2048, c[4][0], c[4][2]); red4(yp + 2048 + 5120, c[4][1], c[4][3]); }
            TR(r55);
        }
        else bar_arrive(8, 384);
        mbar_wait(sb + B_X, 0); mbar_wait(sb + B_GU, 0);
        TRW(r51, 51); TRW(r30, 30); TRW(r52, 52); TRW(r53, 53); TRW(r54, 54); TRW(r55, 55); TRW(r20, 20); TRW(r22, 22);
        if (owns) {
            const uint32_t u = min(at >> 1, 39u), col = (u >> 3) * 32 + (u & 7) * 2;
            const bool mine = (tok >> 7) == rb;
            k1 ^= ((~(int)k1) >> 31) | 0x80000000u;
            const float sg = bf16r(sigm(bfhi(k1))), rs = rcp(bflo(sv));
            uint32_t x0, x1, y0, y1, n0, n1;
            asm volatile("ld.global.nc.u16 %0, [%2];\nld.global.nc.u16 %1, [%2 + 16];" : "=r"(x0), "=r"(x1) : "l"(P.x + (tok * 1280 + hg * 160 + col)));
            const float a0 = (bflo(x0) - bfhi(sv)) * rs, a1 = (bflo(x1) - bfhi(sv)) * rs;
            bar_sync(4, 128);
#pragma unroll 1
            do {
                __nanosleep(YSL);
                uint32_t v[6][4];
#pragma unroll
                for (int r = 0; r < 6; r++) ldg128(P.scr + (G_Y + (at & 1) * 5120 + hg * 640 + u * 16) + r * 10240, v[r][0], v[r][1], v[r][2], v[r][3]);
                y0 = U(((F(v[0][0]) + F(v[1][0])) + (F(v[2][0]) + F(v[3][0]))) + (F(v[4][0]) + F(v[5][0])));
                y1 = U(((F(v[0][1]) + F(v[1][1])) + (F(v[2][1]) + F(v[3][1]))) + (F(v[4][1]) + F(v[5][1])));
                n0 = U(((F(v[0][2]) + F(v[1][2])) + (F(v[2][2]) + F(v[3][2]))) + (F(v[4][2]) + F(v[5][2])));
                n1 = U(((F(v[0][3]) + F(v[1][3])) + (F(v[2][3]) + F(v[3][3]))) + (F(v[4][3]) + F(v[5][3])));
            } while (any(mine && (F(n0) != NFFN / 2 || F(n1) != NFFN / 2)) && ++spins < SPIN);
            const float v0 = a0 + bf16r(bf16r(F(y0)) * sg), v1 = a1 + bf16r(bf16r(F(y1)) * sg);
            const uint32_t gp = pack_bf16(v0 * sigm(v0), v1 * sigm(v1));
            asm volatile("st.shared.u16 [%0], %1;\nst.shared.u16 [%0 + 16], %2;" :: "r"(sb + M_UPD + (at & 1) * 160 + col), "r"(gp), "r"(gp >> 16) : "memory");
            __syncwarp();
            if (lane < 2) mbar_arrive(sb + B_UPD);
            TS(56);
        }
    }
}

typedef CUresult (*EncodeFn)(CUtensorMap*, CUtensorMapDataType, cuuint32_t, void*, const cuuint64_t*, const cuuint64_t*,
                             const cuuint32_t*, const cuuint32_t*, CUtensorMapInterleave, CUtensorMapSwizzle,
                             CUtensorMapL2promotion, CUtensorMapFloatOOBfill);

bool encode(EncodeFn fn, CUtensorMap* tm, const void* ptr, cuuint64_t d0, cuuint64_t d1, cuuint64_t d2, cuuint64_t s1, cuuint64_t s2,
            cuuint32_t b0, cuuint32_t b1, cuuint32_t b2, CUtensorMapSwizzle sw) {
    const cuuint64_t dims[3] = {d0, d1, d2}, strides[2] = {s1, s2};
    const cuuint32_t box[3] = {b0, b1, b2}, es[3] = {1, 1, 1};
    return fn(tm, CU_TENSOR_MAP_DATA_TYPE_BFLOAT16, 3, const_cast<void*>(ptr), dims, strides, box, es,
              CU_TENSOR_MAP_INTERLEAVE_NONE, sw, CU_TENSOR_MAP_L2_PROMOTION_L2_128B,
              CU_TENSOR_MAP_FLOAT_OOB_FILL_NONE) == CUDA_SUCCESS;
}

}

extern "C" void kernel_launch(void* const* d_in, const int* in_sizes, int n_in, void* d_out, int out_size) {
    static Params P;
    static bool by_sm = false;
    static const void* cached[9] = {};
    bool same = cached[8] == d_out;
    for (int i = 0; i < 8; i++) same = same && cached[i] == d_in[i];
    if (!same) {
        const void *x = d_in[0], *wqkv = d_in[1], *wo = d_in[2], *wg = d_in[5], *wu = d_in[6], *wd = d_in[7];
        void* fnp = nullptr;
        cudaDriverEntryPointQueryResult qr;
        cudaGetDriverEntryPoint("cuTensorMapEncodeTiled", &fnp, cudaEnableDefault, &qr);
        EncodeFn fn = (EncodeFn)fnp;
        const CUtensorMapSwizzle S0 = CU_TENSOR_MAP_SWIZZLE_NONE, S32 = CU_TENSOR_MAP_SWIZZLE_32B, S64 = CU_TENSOR_MAP_SWIZZLE_64B,
                                 S128 = CU_TENSOR_MAP_SWIZZLE_128B;
        const bool ok = fn != nullptr &&
            encode(fn, &P.tm[T_X], x, 640, 1024, 2, 2560, 1280, 64, 64, 2, S128) &&
            encode(fn, &P.tm[T_OUT], d_out, 640, 1024, 2, 2560, 1280, 80, 16, 1, S0) &&
            encode(fn, &P.tm[T_W], wqkv, 640, 640, 3, 3840, 1280, 64, 32, 3, S128) &&
            encode(fn, &P.tm[T_WR], wqkv, 640, 640, 3, 3840, 1280, 16, 32, 3, S32) &&
            encode(fn, &P.tm[T_GU], wg < wu ? wg : wu, 1728, 640, 2, 3456, wg < wu ? (const char*)wu - (const char*)wg : (const char*)wg - (const char*)wu,
                   32, 16, 2, S64) &&
            encode(fn, &P.tm[T_D], wd, 64, 1728, 10, 1280, 128, 64, 32, 5, S128) &&
            encode(fn, &P.tm[T_WO], wo, 640, 640, 1, 1280, 1280 * 640, 32, 80, 1, S64) &&
            encode(fn, &P.tm[T_WOR], wo, 640, 640, 1, 1280, 1280 * 640, 16, 40, 1, S64);
        if (!ok) return;
        P.up_first = wg < wu ? 0 : 256;
        P.wo = (const uint8_t*)wo; P.wd = (const uint8_t*)wd;
        P.x = (const uint8_t*)x; P.w = (const uint8_t*)wqkv; P.w_r = (const uint8_t*)d_in[4];
        if (cudaGetSymbolAddress((void**)&P.scr, g_scr) != cudaSuccess) return;
        cudaFuncSetAttribute(fused_kernel<true>, cudaFuncAttributeMaxDynamicSharedMemorySize, SMEM_BYTES);
        cudaFuncSetAttribute(fused_kernel<false>, cudaFuncAttributeMaxDynamicSharedMemorySize, SMEM_BYTES);
        int ncl = 0, sms = 0, dev = 0;
        {
            cudaLaunchConfig_t cfg = {};
            cfg.gridDim = dim3(128); cfg.blockDim = dim3(NTHREADS); cfg.dynamicSmemBytes = SMEM_BYTES;
            cudaLaunchAttribute at[1];
            at[0].id = cudaLaunchAttributeClusterDimension;
            at[0].val.clusterDim.x = 2; at[0].val.clusterDim.y = 1; at[0].val.clusterDim.z = 1;
            cfg.attrs = at; cfg.numAttrs = 1;
            if (cudaOccupancyMaxActiveClusters(&ncl, fused_kernel<true>, &cfg) != cudaSuccess || ncl < 64) return;
            cudaGetDevice(&dev);
            cudaDeviceGetAttribute(&sms, cudaDevAttrMultiProcessorCount, dev);
        }
        by_sm = sms == 132 && ncl == 66;
        for (int i = 0; i < 8; i++) cached[i] = d_in[i];
        cached[8] = d_out;
    }
    if (by_sm) fused_kernel<true><<<132, NTHREADS, SMEM_BYTES>>>(P);
    else fused_kernel<false><<<128, NTHREADS, SMEM_BYTES>>>(P);
}
```

```cpp
#include <cuda_runtime.h>
#include <cuda_bf16.h>
#include <cuda.h>
#include <stdint.h>

namespace {

typedef __nv_bfloat16 bf16;

constexpr int SEQ = 2048, DM = 640;
constexpr int NTHREADS = 512;
constexpr int NFFN = 108;
#define LEAD 2
#define PACE0 250
#define PACE1 950
#define PX0 1500
#define PX1 500
#define GU0 6000
#define GU1 220
#define GT0 2300
#define GT1 430
#define WOP 150
#define AUXS 500
#define EX1T 8200
#define EX2D 2200
#define SERAT 2
#define CHKJ 2
#define LDJ 4
#define YSL 200
#define HGMAP 0x62740351u
#define TPUB 3
#define AHEAD 4
#define LDAT 1
#define ODDX 1

constexpr int ST = 47104;
constexpr int ST_BM = 16384, ST_BR = 40960;
constexpr int OFF_X = 0;
constexpr int OFF_DN = 20480;
constexpr int OFF_PART = 40960;
constexpr int OFF_G = 43008;
constexpr int OFF_WO = 63488;
constexpr int WO_SLOT = 15360;
constexpr int OFF_GU = 4 * ST;
constexpr int M_ST = OFF_GU + 40960;
constexpr int M_CS = M_ST + 1024;
constexpr int M_UPD = M_CS + 1024;
constexpr int M_TOP = M_UPD + 640;
constexpr int M_SEL = M_TOP + 64;
constexpr int B_Z = M_SEL + 16, B_G = B_Z + 8, B_AX = B_Z + 32, B_PREP = B_AX + 40, B_UPD = B_PREP + 8, B_GU = B_AX + 64, B_X = B_GU + 8, B_H = B_X + 8,
              B_SEL = B_H + 8, B_FULL = B_GU + 32, B_EMPTY = B_FULL + 32, B_HO = B_EMPTY + 32, B_WO = B_HO + 32;
constexpr int SMEM_BYTES = B_WO + 32;
static_assert(SMEM_BYTES <= 232448 && OFF_WO + 2 * WO_SLOT <= 2 * ST && OFF_WO + 5 * WO_SLOT <= 3 * ST && OFF_WO + 8 * WO_SLOT <= 4 * ST, "smem");

enum { T_X, T_W, T_WR, T_GU, T_D, T_WO, T_WOR, T_OUT, T_N };
struct Params {
    CUtensorMap tm[T_N];
    const uint8_t* x;
    const uint8_t* w_r;
    const uint8_t* w;
    const uint8_t* wo;
    const uint8_t* wd;
    uint8_t* scr;
    uint32_t up_first;
};

constexpr uint32_t XB = 27392;
constexpr uint32_t G_TOP = 25600;
constexpr uint32_t G_CS = G_TOP + 1024;
constexpr uint32_t G_ST = G_CS + 128;
constexpr uint32_t G_FLAG = G_ST + 512;
constexpr uint32_t G_Y = 128 * XB;
constexpr uint32_t G_EPOCH = G_Y + 128 * 512;
static_assert(G_FLAG + 128 == XB, "scratch");
__device__ __align__(1024) uint8_t g_scr[G_EPOCH + 1024];

#define TSINIT
#define TR(v)
#define TRD(v)
#define TRW(v, i)
#define TS(i)
#define TSG(i)
constexpr unsigned SPIN = 1u << 20;

__device__ __forceinline__ void mbar_init(uint32_t bar, int cnt) {
    asm volatile("mbarrier.init.shared::cta.b64 [%0], %1;" :: "r"(bar), "r"(cnt) : "memory");
}
__device__ __forceinline__ void mbar_expect_tx(uint32_t bar, int bytes) {
    asm volatile("mbarrier.arrive.expect_tx.shared::cta.b64 _, [%0], %1;" :: "r"(bar), "r"(bytes) : "memory");
}
__device__ __forceinline__ void mbar_arrive(uint32_t bar) {
    asm volatile("mbarrier.arrive.shared::cta.b64 _, [%0];" :: "r"(bar) : "memory");
}
__device__ __forceinline__ uint32_t mapa(uint32_t a, uint32_t cta) {
    uint32_t r;
    asm("mapa.shared::cluster.u32 %0, %1, %2;" : "=r"(r) : "r"(a), "r"(cta));
    return r;
}
__device__ __forceinline__ void mbar_arrive_cl(uint32_t cbar) {
    asm volatile("mbarrier.arrive.shared::cluster.b64 _, [%0];" :: "r"(cbar) : "memory");
}
__device__ __forceinline__ void mbar_wait(uint32_t bar, int parity) {
    asm volatile("{\n.reg .pred p;\nLAB_WAIT:\nmbarrier.try_wait.parity.shared::cta.b64 p, [%0], %1;\n@!p bra LAB_WAIT;\n}"
                 :: "r"(bar), "r"(parity) : "memory");
}
__device__ __forceinline__ bool mbar_try(uint32_t bar, int parity) {
    uint32_t r;
    asm volatile("{\n.reg .pred p;\nmbarrier.test_wait.parity.shared::cta.b64 p, [%1], %2;\nselp.u32 %0, 1, 0, p;\n}"
                 : "=r"(r) : "r"(bar), "r"(parity) : "memory");
    return r != 0;
}
__device__ __forceinline__ void tma(uint32_t dst, const CUtensorMap* tm, uint32_t bar, int c0, int c1, int c2 = 0) {
    asm volatile("cp.async.bulk.tensor.3d.shared::cluster.global.mbarrier::complete_tx::bytes [%0], [%1, {%3, %4, %5}], [%2];"
                 :: "r"(dst), "l"(tm), "r"(bar), "r"(c0), "r"(c1), "r"(c2) : "memory");
}
__device__ __forceinline__ void tma_mc(uint32_t dst, const CUtensorMap* tm, uint32_t bar, int c0, int c1) {
    asm volatile("cp.async.bulk.tensor.3d.shared::cluster.global.mbarrier::complete_tx::bytes.multicast::cluster [%0], [%1, {%3, %4, %5}], [%2], %6;"
                 :: "r"(dst), "l"(tm), "r"(bar), "r"(c0), "r"(c1), "r"(0), "h"((uint16_t)3) : "memory");
}
__device__ __forceinline__ void tma_st(const CUtensorMap* tm, uint32_t src, int c0, int c1, int c2) {
    asm volatile("cp.async.bulk.tensor.3d.global.shared::cta.bulk_group [%0, {%2, %3, %4}], [%1];\ncp.async.bulk.commit_group;"
                 :: "l"(tm), "r"(src), "r"(c0), "r"(c1), "r"(c2) : "memory");
}
__device__ __forceinline__ void l2_prefetch(const void* p, int bytes) {
    asm volatile("cp.async.bulk.prefetch.L2.global [%0], %1;" :: "l"(p), "r"(bytes) : "memory");
}
__device__ __forceinline__ void cluster_arrive() { asm volatile("barrier.cluster.arrive.relaxed.aligned;" ::: "memory"); }
__device__ __forceinline__ void cluster_wait() { asm volatile("barrier.cluster.wait.aligned;" ::: "memory"); }
__device__ __forceinline__ void bar_sync(int id, int n) { asm volatile("bar.sync %0, %1;" :: "r"(id), "r"(n) : "memory"); }
__device__ __forceinline__ void bar_arrive(int id, int n) { asm volatile("bar.arrive %0, %1;" :: "r"(id), "r"(n) : "memory"); }
__device__ __forceinline__ bool bar_or(int id, int n, bool v) {
    uint32_t r;
    asm volatile("{\n.reg .pred p, q;\nsetp.ne.u32 p, %3, 0;\nbar.red.or.pred q, %1, %2, p;\nselp.u32 %0, 1, 0, q;\n}"
                 : "=r"(r) : "r"(id), "r"(n), "r"((uint32_t)v) : "memory");
    return r != 0;
}
__device__ __forceinline__ void fence_proxy_async_smem() { asm volatile("fence.proxy.async.shared::cta;" ::: "memory"); }
__device__ __forceinline__ void stg128(void* p, uint32_t a, uint32_t b, uint32_t c, uint32_t d) {
    asm volatile("{\n.reg .b64 l, h;\n.reg .b128 q;\nmov.b64 l, {%1, %2};\nmov.b64 h, {%3, %4};\nmov.b128 q, {l, h};\n"
                 "st.relaxed.gpu.global.b128 [%0], q;\n}" :: "l"(p), "r"(a), "r"(b), "r"(c), "r"(d) : "memory");
}
__device__ __forceinline__ void ldg128(const void* p, uint32_t& a, uint32_t& b, uint32_t& c, uint32_t& d) {
    asm volatile("{\n.reg .b64 l, h;\n.reg .b128 q;\nld.relaxed.gpu.global.b128 q, [%4];\nmov.b128 {l, h}, q;\n"
                 "mov.b64 {%0, %1}, l;\nmov.b64 {%2, %3}, h;\n}" : "=r"(a), "=r"(b), "=r"(c), "=r"(d) : "l"(p) : "memory");
}
__device__ __forceinline__ void stg64(void* p, uint32_t a, uint32_t b) {
    asm volatile("{\n.reg .b64 l;\nmov.b64 l, {%1, %2};\nst.relaxed.gpu.global.b64 [%0], l;\n}" :: "l"(p), "r"(a), "r"(b) : "memory");
}
__device__ __forceinline__ void red4(void* p, float a, float b) {
    asm volatile("red.relaxed.gpu.global.add.v4.f32 [%0], {%1, %2, %3, %3};" :: "l"(p), "f"(a), "f"(b), "f"(1.0f) : "memory");
}
__device__ __forceinline__ void stg32(void* p, uint32_t a) {
    asm volatile("st.relaxed.gpu.global.u32 [%0], %1;" :: "l"(p), "r"(a) : "memory");
}
__device__ __forceinline__ uint2 ldg64(const void* p) {
    uint2 v;
    asm volatile("{\n.reg .b64 l;\nld.relaxed.gpu.global.b64 l, [%2];\nmov.b64 {%0, %1}, l;\n}" : "=r"(v.x), "=r"(v.y) : "l"(p) : "memory");
    return v;
}
__device__ __forceinline__ unsigned ldg32(const void* p) {
    unsigned v;
    asm volatile("ld.relaxed.gpu.global.u32 %0, [%1];" : "=r"(v) : "l"(p) : "memory");
    return v;
}
__device__ __forceinline__ void ldsm_x4(uint32_t (&r)[4], uint32_t a) {
    asm volatile("ldmatrix.sync.aligned.m8n8.x4.shared.b16 {%0,%1,%2,%3}, [%4];"
                 : "=r"(r[0]), "=r"(r[1]), "=r"(r[2]), "=r"(r[3]) : "r"(a));
}
__device__ __forceinline__ void ldsm_x4_t(uint32_t (&r)[4], uint32_t a) {
    asm volatile("ldmatrix.sync.aligned.m8n8.x4.trans.shared.b16 {%0,%1,%2,%3}, [%4];"
                 : "=r"(r[0]), "=r"(r[1]), "=r"(r[2]), "=r"(r[3]) : "r"(a));
}
__device__ __forceinline__ void stsm_x4(uint32_t a, const uint32_t (&r)[4]) {
    asm volatile("stmatrix.sync.aligned.m8n8.x4.shared.b16 [%0], {%1,%2,%3,%4};"
                 :: "r"(a), "r"(r[0]), "r"(r[1]), "r"(r[2]), "r"(r[3]));
}
__device__ __forceinline__ uint32_t movm(uint32_t a) {
    uint32_t d;
    asm("movmatrix.sync.aligned.m8n8.trans.b16 %0, %1;" : "=r"(d) : "r"(a));
    return d;
}
__device__ __forceinline__ void mma16816(float (&c)[4], uint32_t a0, uint32_t a1, uint32_t a2, uint32_t a3, uint32_t b0, uint32_t b1) {
    asm("mma.sync.aligned.m16n8k16.row.col.f32.bf16.bf16.f32 {%0,%1,%2,%3}, {%4,%5,%6,%7}, {%8,%9}, {%0,%1,%2,%3};"
        : "+f"(c[0]), "+f"(c[1]), "+f"(c[2]), "+f"(c[3]) : "r"(a0), "r"(a1), "r"(a2), "r"(a3), "r"(b0), "r"(b1));
}
__device__ __forceinline__ void mma1688(float (&c)[4], uint32_t a0, uint32_t a1, uint32_t b0) {
    asm("mma.sync.aligned.m16n8k8.row.col.f32.bf16.bf16.f32 {%0,%1,%2,%3}, {%4,%5}, {%6}, {%0,%1,%2,%3};"
        : "+f"(c[0]), "+f"(c[1]), "+f"(c[2]), "+f"(c[3]) : "r"(a0), "r"(a1), "r"(b0));
}
__device__ __forceinline__ void wgmma_fence() { asm volatile("wgmma.fence.sync.aligned;" ::: "memory"); }
__device__ __forceinline__ void wgmma_commit() { asm volatile("wgmma.commit_group.sync.aligned;" ::: "memory"); }
template <int N> __device__ __forceinline__ void wgmma_wait() { asm volatile("wgmma.wait_group.sync.aligned %0;" :: "n"(N) : "memory"); }
__device__ __forceinline__ uint64_t mk(uint32_t lo, uint32_t hi) { return (uint64_t)lo | ((uint64_t)hi << 32); }
constexpr uint32_t HI128 = (1024 >> 4) | (1u << 30), HI64 = (512 >> 4) | (2u << 30), HI32 = (256 >> 4) | (3u << 30);
__device__ __forceinline__ uint32_t pack_bf16(float lo, float hi) {
    uint32_t r;
    asm("cvt.rn.bf16x2.f32 %0, %1, %2;" : "=r"(r) : "f"(hi), "f"(lo));
    return r;
}
__device__ __forceinline__ float bflo(uint32_t u) { return __uint_as_float(u << 16); }
__device__ __forceinline__ float bfhi(uint32_t u) { return __uint_as_float(u & 0xFFFF0000u); }
__device__ __forceinline__ float bf16r(float v) { return __uint_as_float(pack_bf16(0.f, v)); }
__device__ __forceinline__ float ex2(float v) { float r; asm("ex2.approx.ftz.f32 %0, %1;" : "=f"(r) : "f"(v)); return r; }
__device__ __forceinline__ float rcp(float v) { float r; asm("rcp.approx.ftz.f32 %0, %1;" : "=f"(r) : "f"(v)); return r; }
__device__ __forceinline__ float sqrt_a(float v) { float r; asm("sqrt.approx.ftz.f32 %0, %1;" : "=f"(r) : "f"(v)); return r; }
__device__ __forceinline__ float tanh_a(float v) { float r; asm("tanh.approx.f32 %0, %1;" : "=f"(r) : "f"(v)); return r; }
constexpr float LOG2E = 1.4426950408889634f;
__device__ __forceinline__ float sigm(float v) { return rcp(1.0f + ex2(-LOG2E * v)); }
__device__ __forceinline__ uint4 lds128(uint32_t a) {
    uint4 v;
    asm volatile("ld.shared.v4.u32 {%0,%1,%2,%3}, [%4];" : "=r"(v.x), "=r"(v.y), "=r"(v.z), "=r"(v.w) : "r"(a));
    return v;
}
__device__ __forceinline__ float4 lds128f(uint32_t a) {
    float4 v;
    asm volatile("ld.shared.v4.f32 {%0,%1,%2,%3}, [%4];" : "=f"(v.x), "=f"(v.y), "=f"(v.z), "=f"(v.w) : "r"(a));
    return v;
}
__device__ __forceinline__ float2 lds64f(uint32_t a) {
    float2 v;
    asm volatile("ld.shared.v2.f32 {%0,%1}, [%2];" : "=f"(v.x), "=f"(v.y) : "r"(a));
    return v;
}
__device__ __forceinline__ uint32_t lds32(uint32_t a) {
    uint32_t v;
    asm volatile("ld.shared.u32 %0, [%1];" : "=r"(v) : "r"(a));
    return v;
}
__device__ __forceinline__ void sts128(uint32_t a, uint32_t x, uint32_t y, uint32_t z, uint32_t w) {
    asm volatile("st.shared.v4.u32 [%0], {%1,%2,%3,%4};" :: "r"(a), "r"(x), "r"(y), "r"(z), "r"(w) : "memory");
}
__device__ __forceinline__ void sts64(uint32_t a, uint32_t x, uint32_t y) {
    asm volatile("st.shared.v2.u32 [%0], {%1,%2};" :: "r"(a), "r"(x), "r"(y) : "memory");
}
__device__ __forceinline__ void sts32(uint32_t a, uint32_t x) { asm volatile("st.shared.u32 [%0], %1;" :: "r"(a), "r"(x) : "memory"); }
__device__ __forceinline__ unsigned redux_max(unsigned v) {
    unsigned r;
    asm volatile("redux.sync.max.u32 %0, %1, 0xffffffff;" : "=r"(r) : "r"(v));
    return r;
}
__device__ __forceinline__ float shx(float v, int o) { return __shfl_xor_sync(0xffffffffu, v, o); }
__device__ __forceinline__ uint32_t U(float v) { return __float_as_uint(v); }
__device__ __forceinline__ float F(uint32_t v) { return __uint_as_float(v); }

__device__ __forceinline__ void wgmma_n192_lo(float (&d)[120], uint64_t da, uint64_t db, int scale_d) {
    asm volatile("{\n.reg .pred p;\nsetp.ne.b32 p, %98, 0;\n"
        "wgmma.mma_async.sync.aligned.m64n192k16.f32.bf16.bf16 "
        "{%0, %1, %2, %3, %4, %5, %6, %7, %8, %9, %10, %11, %12, %13, %14, %15, "
        "%16, %17, %18, %19, %20, %21, %22, %23, %24, %25, %26, %27, %28, %29, %30, %31, "
        "%32, %33, %34, %35, %36, %37, %38, %39, %40, %41, %42, %43, %44, %45, %46, %47, "
        "%48, %49, %50, %51, %52, %53, %54, %55, %56, %57, %58, %59, %60, %61, %62, %63, "
        "%64, %65, %66, %67, %68, %69, %70, %71, %72, %73, %74, %75, %76, %77, %78, %79, "
        "%80, %81, %82, %83, %84, %85, %86, %87, %88, %89, %90, %91, %92, %93, %94, %95}, "
        "%96, %97, p, 1, 1, 0, 1;\n}\n"
        : "+f"(d[0]), "+f"(d[1]), "+f"(d[2]), "+f"(d[3]), "+f"(d[4]), "+f"(d[5]), "+f"(d[6]), "+f"(d[7]),
          "+f"(d[8]), "+f"(d[9]), "+f"(d[10]), "+f"(d[11]), "+f"(d[12]), "+f"(d[13]), "+f"(d[14]), "+f"(d[15]),
          "+f"(d[16]), "+f"(d[17]), "+f"(d[18]), "+f"(d[19]), "+f"(d[20]), "+f"(d[21]), "+f"(d[22]), "+f"(d[23]),
          "+f"(d[24]), "+f"(d[25]), "+f"(d[26]), "+f"(d[27]), "+f"(d[28]), "+f"(d[29]), "+f"(d[30]), "+f"(d[31]),
          "+f"(d[32]), "+f"(d[33]), "+f"(d[34]), "+f"(d[35]), "+f"(d[36]), "+f"(d[37]), "+f"(d[38]), "+f"(d[39]),
          "+f"(d[40]), "+f"(d[41]), "+f"(d[42]), "+f"(d[43]), "+f"(d[44]), "+f"(d[45]), "+f"(d[46]), "+f"(d[47]),
          "+f"(d[48]), "+f"(d[49]), "+f"(d[50]), "+f"(d[51]), "+f"(d[52]), "+f"(d[53]), "+f"(d[54]), "+f"(d[55]),
          "+f"(d[56]), "+f"(d[57]), "+f"(d[58]), "+f"(d[59]), "+f"(d[60]), "+f"(d[61]), "+f"(d[62]), "+f"(d[63]),
          "+f"(d[64]), "+f"(d[65]), "+f"(d[66]), "+f"(d[67]), "+f"(d[68]), "+f"(d[69]), "+f"(d[70]), "+f"(d[71]),
          "+f"(d[72]), "+f"(d[73]), "+f"(d[74]), "+f"(d[75]), "+f"(d[76]), "+f"(d[77]), "+f"(d[78]), "+f"(d[79]),
          "+f"(d[80]), "+f"(d[81]), "+f"(d[82]), "+f"(d[83]), "+f"(d[84]), "+f"(d[85]), "+f"(d[86]), "+f"(d[87]),
          "+f"(d[88]), "+f"(d[89]), "+f"(d[90]), "+f"(d[91]), "+f"(d[92]), "+f"(d[93]), "+f"(d[94]), "+f"(d[95])
        : "l"(da), "l"(db), "r"(scale_d));
}
__device__ __forceinline__ void wgmma_n48_hi(float (&d)[120], uint64_t da, uint64_t db, int scale_d) {
    asm volatile("{\n.reg .pred p;\nsetp.ne.b32 p, %26, 0;\n"
        "wgmma.mma_async.sync.aligned.m64n48k16.f32.bf16.bf16 "
        "{%0, %1, %2, %3, %4, %5, %6, %7, %8, %9, %10, %11, %12, %13, %14, %15, "
        "%16, %17, %18, %19, %20, %21, %22, %23}, "
        "%24, %25, p, 1, 1, 0, 1;\n}\n"
        : "+f"(d[96]), "+f"(d[97]), "+f"(d[98]), "+f"(d[99]), "+f"(d[100]), "+f"(d[101]), "+f"(d[102]), "+f"(d[103]),
          "+f"(d[104]), "+f"(d[105]), "+f"(d[106]), "+f"(d[107]), "+f"(d[108]), "+f"(d[109]), "+f"(d[110]), "+f"(d[111]),
          "+f"(d[112]), "+f"(d[113]), "+f"(d[114]), "+f"(d[115]), "+f"(d[116]), "+f"(d[117]), "+f"(d[118]), "+f"(d[119])
        : "l"(da), "l"(db), "r"(scale_d));
}
__device__ __forceinline__ void wgmma_rs_n80(float (&d)[40], uint32_t a0, uint32_t a1, uint32_t a2, uint32_t a3, uint64_t db, int scale_d) {
    asm volatile("{\n.reg .pred p;\nsetp.ne.b32 p, %45, 0;\n"
        "wgmma.mma_async.sync.aligned.m64n80k16.f32.bf16.bf16 "
        "{%0, %1, %2, %3, %4, %5, %6, %7, %8, %9, %10, %11, %12, %13, %14, %15, "
        "%16, %17, %18, %19, %20, %21, %22, %23, %24, %25, %26, %27, %28, %29, %30, %31, "
        "%32, %33, %34, %35, %36, %37, %38, %39}, "
        "{%40, %41, %42, %43}, %44, p, 1, 1, 1;\n}\n"
        : "+f"(d[0]), "+f"(d[1]), "+f"(d[2]), "+f"(d[3]), "+f"(d[4]), "+f"(d[5]), "+f"(d[6]), "+f"(d[7]),
          "+f"(d[8]), "+f"(d[9]), "+f"(d[10]), "+f"(d[11]), "+f"(d[12]), "+f"(d[13]), "+f"(d[14]), "+f"(d[15]),
          "+f"(d[16]), "+f"(d[17]), "+f"(d[18]), "+f"(d[19]), "+f"(d[20]), "+f"(d[21]), "+f"(d[22]), "+f"(d[23]),
          "+f"(d[24]), "+f"(d[25]), "+f"(d[26]), "+f"(d[27]), "+f"(d[28]), "+f"(d[29]), "+f"(d[30]), "+f"(d[31]),
          "+f"(d[32]), "+f"(d[33]), "+f"(d[34]), "+f"(d[35]), "+f"(d[36]), "+f"(d[37]), "+f"(d[38]), "+f"(d[39])
        : "r"(a0), "r"(a1), "r"(a2), "r"(a3), "l"(db), "r"(scale_d));
}
__device__ __forceinline__ void wgmma_rs_n192_lo(float (&d)[120], uint32_t a0, uint32_t a1, uint32_t a2, uint32_t a3, uint64_t db, int scale_d) {
    asm volatile("{\n.reg .pred p;\nsetp.ne.b32 p, %101, 0;\n"
        "wgmma.mma_async.sync.aligned.m64n192k16.f32.bf16.bf16 "
        "{%0, %1, %2, %3, %4, %5, %6, %7, %8, %9, %10, %11, %12, %13, %14, %15, "
        "%16, %17, %18, %19, %20, %21, %22, %23, %24, %25, %26, %27, %28, %29, %30, %31, "
        "%32, %33, %34, %35, %36, %37, %38, %39, %40, %41, %42, %43, %44, %45, %46, %47, "
        "%48, %49, %50, %51, %52, %53, %54, %55, %56, %57, %58, %59, %60, %61, %62, %63, "
        "%64, %65, %66, %67, %68, %69, %70, %71, %72, %73, %74, %75, %76, %77, %78, %79, "
        "%80, %81, %82, %83, %84, %85, %86, %87, %88, %89, %90, %91, %92, %93, %94, %95}, "
        "{%96, %97, %98, %99}, %100, p, 1, 1, 1;\n}\n"
        : "+f"(d[0]), "+f"(d[1]), "+f"(d[2]), "+f"(d[3]), "+f"(d[4]), "+f"(d[5]), "+f"(d[6]), "+f"(d[7]),
          "+f"(d[8]), "+f"(d[9]), "+f"(d[10]), "+f"(d[11]), "+f"(d[12]), "+f"(d[13]), "+f"(d[14]), "+f"(d[15]),
          "+f"(d[16]), "+f"(d[17]), "+f"(d[18]), "+f"(d[19]), "+f"(d[20]), "+f"(d[21]), "+f"(d[22]), "+f"(d[23]),
          "+f"(d[24]), "+f"(d[25]), "+f"(d[26]), "+f"(d[27]), "+f"(d[28]), "+f"(d[29]), "+f"(d[30]), "+f"(d[31]),
          "+f"(d[32]), "+f"(d[33]), "+f"(d[34]), "+f"(d[35]), "+f"(d[36]), "+f"(d[37]), "+f"(d[38]), "+f"(d[39]),
          "+f"(d[40]), "+f"(d[41]), "+f"(d[42]), "+f"(d[43]), "+f"(d[44]), "+f"(d[45]), "+f"(d[46]), "+f"(d[47]),
          "+f"(d[48]), "+f"(d[49]), "+f"(d[50]), "+f"(d[51]), "+f"(d[52]), "+f"(d[53]), "+f"(d[54]), "+f"(d[55]),
          "+f"(d[56]), "+f"(d[57]), "+f"(d[58]), "+f"(d[59]), "+f"(d[60]), "+f"(d[61]), "+f"(d[62]), "+f"(d[63]),
          "+f"(d[64]), "+f"(d[65]), "+f"(d[66]), "+f"(d[67]), "+f"(d[68]), "+f"(d[69]), "+f"(d[70]), "+f"(d[71]),
          "+f"(d[72]), "+f"(d[73]), "+f"(d[74]), "+f"(d[75]), "+f"(d[76]), "+f"(d[77]), "+f"(d[78]), "+f"(d[79]),
          "+f"(d[80]), "+f"(d[81]), "+f"(d[82]), "+f"(d[83]), "+f"(d[84]), "+f"(d[85]), "+f"(d[86]), "+f"(d[87]),
          "+f"(d[88]), "+f"(d[89]), "+f"(d[90]), "+f"(d[91]), "+f"(d[92]), "+f"(d[93]), "+f"(d[94]), "+f"(d[95])
        : "r"(a0), "r"(a1), "r"(a2), "r"(a3), "l"(db), "r"(scale_d));
}
__device__ __forceinline__ void wgmma_rs_n48_hi(float (&d)[120], uint32_t a0, uint32_t a1, uint32_t a2, uint32_t a3, uint64_t db, int scale_d) {
    asm volatile("{\n.reg .pred p;\nsetp.ne.b32 p, %29, 0;\n"
        "wgmma.mma_async.sync.aligned.m64n48k16.f32.bf16.bf16 "
        "{%0, %1, %2, %3, %4, %5, %6, %7, %8, %9, %10, %11, %12, %13, %14, %15, "
        "%16, %17, %18, %19, %20, %21, %22, %23}, "
        "{%24, %25, %26, %27}, %28, p, 1, 1, 1;\n}\n"
        : "+f"(d[96]), "+f"(d[97]), "+f"(d[98]), "+f"(d[99]), "+f"(d[100]), "+f"(d[101]), "+f"(d[102]), "+f"(d[103]),
          "+f"(d[104]), "+f"(d[105]), "+f"(d[106]), "+f"(d[107]), "+f"(d[108]), "+f"(d[109]), "+f"(d[110]), "+f"(d[111]),
          "+f"(d[112]), "+f"(d[113]), "+f"(d[114]), "+f"(d[115]), "+f"(d[116]), "+f"(d[117]), "+f"(d[118]), "+f"(d[119])
        : "r"(a0), "r"(a1), "r"(a2), "r"(a3), "l"(db), "r"(scale_d));
}
__device__ __forceinline__ void wgmma_n8(float (&d)[4], uint64_t da, uint64_t db, int scale_d) {
    asm volatile("{\n.reg .pred p;\nsetp.ne.b32 p, %6, 0;\n"
                 "wgmma.mma_async.sync.aligned.m64n8k16.f32.bf16.bf16 {%0, %1, %2, %3}, %4, %5, p, 1, 1, 1, 0;\n}\n"
                 : "+f"(d[0]), "+f"(d[1]), "+f"(d[2]), "+f"(d[3]) : "l"(da), "l"(db), "r"(scale_d));
}
__device__ __forceinline__ constexpr int jt_of(int sec, int c, bool odd) {
    return odd ? (c >= 2 ? sec * 8 + c - 2 : 24 + sec * 2 + c) : (c < 8 ? sec * 8 + c : 24 + sec * 2 + (c - 8));
}
#define BOTH(...) if (hg & ODDX) { constexpr bool odd = true; __VA_ARGS__ } else { constexpr bool odd = false; __VA_ARGS__ }

__device__ __forceinline__ bool elect() {
    uint32_t r;
    asm volatile("{\n.reg .pred p;\nelect.sync _|p, 0xffffffff;\nselp.u32 %0, 1, 0, p;\n}" : "=r"(r));
    return r != 0;
}
__device__ __forceinline__ uint32_t clock32() { uint32_t r; asm volatile("mov.u32 %0, %%clock;" : "=r"(r)); return r; }
#define BLOCK_SPLIT(v) asm volatile("{\n.reg .pred p;\nLAB_SPLIT:\nsetp.eq.u32 p, %0, 0;\n@p nanosleep.u32 1;\n@p bra LAB_SPLIT;\n}" :: "r"(v) : "memory")
__device__ __forceinline__ bool any(bool v) { return __any_sync(0xffffffffu, v); }
__device__ __forceinline__ bool retry(unsigned& spins) { __nanosleep(100); return ++spins < SPIN; }
__device__ __forceinline__ uint32_t opaque_tid() { uint32_t r; asm volatile("mov.u32 %0, %%tid.x;" : "=r"(r)); return r; }

template <bool BY_SM>
__global__ void __cluster_dims__(2, 1, 1) __launch_bounds__(NTHREADS, 1)
fused_kernel(const __grid_constant__ Params P) {
    extern __shared__ __align__(1024) uint8_t smem[];
    const uint32_t sb = (uint32_t)__cvta_generic_to_shared(smem);
    const uint32_t warp = __shfl_sync(0xffffffffu, threadIdx.x >> 5, 0);
    const uint32_t rank = blockIdx.x & 1;
    constexpr uint32_t sbd = 1024 >> 4;
    const uint32_t t0 = clock32();
    if (warp >= 8 && elect()) {
        const uint32_t bb = sb + B_Z - 256 + (warp ^ 1) * 32;
        const int cnt = ((0xF00F7027u >> (4 * (warp - 8))) & 15) + 1;
        mbar_init(bb, cnt); mbar_init(bb + 8, cnt); mbar_init(bb + 16, cnt); mbar_init(bb + 24, cnt);
        if (warp == 10) { mbar_expect_tx(sb + B_H, 1024); mbar_expect_tx(sb + B_GU, 40960); }
        if (warp == 13) mbar_expect_tx(sb + B_FULL + 16, ST);
        asm volatile("fence.mbarrier_init.release.cluster;" ::: "memory");
    }
    __syncwarp();
    cluster_arrive();
    if (warp < 3 && elect()) asm volatile("prefetch.tensormap [%0];" :: "l"(&P.tm[warp]) : "memory");
    if ((sb & 0xFFFFFF) != 1024) __trap();
    uint32_t gpc = blockIdx.x >> 4, pos = (blockIdx.x >> 1) & 7;
    if (BY_SM) {
        uint32_t tpc;
        asm("mov.u32 %0, %%smid;" : "=r"(tpc));
        tpc >>= 1;
        if (tpc - 60 < 2) {
            __nanosleep(2000);
            return;
        }
        const uint32_t q = ((tpc - 32) * 37) >> 8;
        gpc = tpc < 32 ? tpc & 7 : (tpc < 60 ? tpc - 31 - 7 * q : 0);
        pos = tpc < 32 ? tpc >> 3 : (tpc < 60 ? 4 + q : tpc - 58);
    }
    const uint32_t hg = (HGMAP >> (4 * pos)) & 7, rb = gpc * 2 + rank, fp = 8 * pos + gpc - 10;
    const uint32_t b = rb * 8 + hg;
    const uint32_t k0 = (((hg >> 2) ^ (rb >> 1)) & 1) * 320;

    if (warp == 13 && elect()) tma(sb + 2 * ST, &P.tm[T_X], sb + B_FULL + 16, k0, rb * 64);
    if (warp == 12) {
        cluster_wait();
        if (elect()) {
            tma_mc(sb + 2 * ST + ST_BM + rank * 12288, &P.tm[T_W], sb + B_FULL + 16, hg * 80 + (hg & ODDX) * 16, k0 + rank * 32);
            tma_mc(sb + 2 * ST + ST_BR + rank * 3072, &P.tm[T_WR], sb + B_FULL + 16, hg * 80 + 64 - (hg & ODDX) * 64, k0 + rank * 32);
        }
        __syncwarp();
    }

    if (warp < 8) {
        asm volatile("setmaxnreg.inc.sync.aligned.u32 208;");
        const uint32_t lane = opaque_tid() & 31, g = lane >> 2, t = lane & 3;
        const uint32_t p = warp >> 2, w = warp & 3;
        const uint32_t empty_cl = mapa(sb + B_EMPTY, lane & 1);
        uint8_t* const orow = P.scr + (rb * (8 * XB) + warp * 2560 + lane * 16);
        const uint32_t ta = sb + warp * 2560 + (lane & 15) * 160 + (lane >> 4) * 16;
        uint32_t A[7][20];
        TRD(r12); TRD(r32); TRD(r34); TRD(r22); TRD(r44);
        uint32_t par;
        uint8_t* const halo = orow + (hg * XB + (8 + p - warp) * 2560);
        uint8_t* const flag = P.scr + (G_FLAG + b * XB + w * 8 + p * 4);
        cluster_wait();
        {
            float acc[120];
            bool ok, prep;
            uint32_t xr[5][4];
            float2 s0, s1;
            const uint32_t xa = sb + (warp * 16 + (lane & 15)) * 128 + (((lane >> 4) ^ (lane & 7)) << 4);
            mbar_wait(sb + B_FULL + 16, 0);
#pragma unroll
            for (uint32_t kb = 2; kb < 12; kb++) {
                const uint32_t s = kb & 3;
                const bool hold = kb == 12 - LEAD && p;
                if (hold) {
                    wgmma_wait<0>();
                    if (lane < 2) mbar_arrive_cl(empty_cl + 8 * ((11 - LEAD) & 3));
                    bar_sync(1, 256);
                }
                wgmma_fence();
                const uint32_t st = sbd + s * (ST >> 4);
#pragma unroll
                for (int ks = 0; ks < 4; ks++) {
                    const uint64_t da = mk(st + p * 512 + ks * 2 + 0x10000, HI128);
                    wgmma_n48_hi(acc, da, mk(st + (ST_BR >> 4) + (ks >> 1) * 192 + (ks & 1) * 32 + (64 << 16), HI32), ks || kb > 2);
                    wgmma_n192_lo(acc, da, mk(st + (ST_BM >> 4) + (ks >> 1) * 768 + (ks & 1) * 128 + (256 << 16), HI128), ks || kb > 2);
                    if (ks == 0) {
                        wgmma_commit();
                        wgmma_wait<1>();
                        if (!hold && kb > 2 && lane < 2) mbar_arrive_cl(empty_cl + 8 * ((kb - 1) & 3));
                    }
                    if (ks == 1) {
#pragma unroll
                        for (uint32_t j = 0; j < 5; j++)
                            if (((5 * hg + j) >> 2) == kb - 2 + (kb < 7 ? k0 >> 6 : -(k0 >> 6))) ldsm_x4(xr[j], (xa + s * ST) ^ (((hg + j) & 3) << 5));
                        if (w == 3 && kb < 7) stg128(halo + (kb - 2) * 512, 0u, 0u, 0u, 0u);
                        if (lane == 0 && kb == 2) stg32(flag, 0u);
                        if (kb < 11) ok = mbar_try(sb + B_FULL + 8 * ((kb + 1) & 3), ((kb - 1) >> 2) & 1);
                        if (kb == 10) prep = mbar_try(sb + B_PREP, 0);
                        if (kb == 11 && prep) {
                            s0 = lds64f(sb + M_ST + (warp * 16 + g) * 8); s1 = lds64f(sb + M_ST + (warp * 16 + g + 8) * 8);
                            par = lds32(sb + M_SEL + 8);
                        }
                    }
                }
                wgmma_commit();
                if (kb < 11 && !ok) mbar_wait(sb + B_FULL + 8 * ((kb + 1) & 3), ((kb - 1) >> 2) & 1);
            }
            if (!prep) {
                mbar_wait(sb + B_PREP, 0);
                s0 = lds64f(sb + M_ST + (warp * 16 + g) * 8); s1 = lds64f(sb + M_ST + (warp * 16 + g + 8) * 8);
                par = lds32(sb + M_SEL + 8);
            }
            {
                const uint32_t a0 = t ? 0u : __byte_perm(U(-s0.y), 0, 0x3232), a1 = t ? 0u : __byte_perm(U(-s1.y), 0, 0x3232);
                wgmma_fence();
                wgmma_rs_n48_hi(acc, a0, a1, 0u, 0u, mk(sbd + (M_CS >> 4) + 48, 2), 1);
                wgmma_rs_n192_lo(acc, a0, a1, 0u, 0u, mk(sbd + (M_CS >> 4), 2), 1);
                wgmma_commit();
            }
            if (!p) bar_arrive(1, 256);
            wgmma_wait<0>();
#pragma unroll
            for (int i = 0; i < 120; i++) asm volatile("" : "+f"(acc[i]) :: "memory");
            if (lane < 2) mbar_arrive_cl(empty_cl + 24);
            TR(r12);
            uint32_t Q[10], Ql[10], KX[10], VX[10], Y[20];
#define KI(c) ((c) == 2 ? 8 : (c) == 7 ? 9 : (c) - ((c) > 2) - ((c) > 7))
#define KY(c) Y[KI(c)]
#define VY(c) Y[10 + (c)]
            uint32_t Z[20];
            const bool start = w == 0 && rb == 0, remote = w == 0 && rb != 0;
            const uint32_t slot = sb + OFF_G + warp * 2560 + lane * 16;
            {
                BOTH(_Pragma("unroll") for (int c = 0; c < 10; c++) {
                    const int jk = jt_of(1, c, odd), jv = jt_of(2, c, odd);
                    VY(c) = movm(pack_bf16(acc[4 * jv + 2] * s1.x, acc[4 * jv + 3] * s1.x));
                    KY(c) = pack_bf16(acc[4 * jk + 2] * s1.x, acc[4 * jk + 3] * s1.x);
                    asm volatile("" : "+r"(KY(c)), "+r"(VY(c)));
                })
                if (w == 3) {
#pragma unroll
                    for (int j = 0; j < 5; j++) {
                        Y[4 * j] = (Y[4 * j] & ~0x10001u) | par;
                        stg128(halo + j * 512, Y[4 * j], Y[4 * j + 1], Y[4 * j + 2], Y[4 * j + 3]);
                    }
                } else {
                    mbar_wait(sb + B_EMPTY + 8, 1);
#pragma unroll
                    for (int j = 0; j < 5; j++) sts128(slot + 2560 + j * 512, Y[4 * j], Y[4 * j + 1], Y[4 * j + 2], Y[4 * j + 3]);
                }
                BOTH(_Pragma("unroll") for (int c = 0; c < 10; c++) {
                    const int jk = jt_of(1, c, odd), jv = jt_of(2, c, odd);
                    KX[c] = pack_bf16(acc[4 * jk] * s0.x, acc[4 * jk + 1] * s0.x);
                    VX[c] = movm(pack_bf16(acc[4 * jv] * s0.x, acc[4 * jv + 1] * s0.x));
                    asm volatile("" : "+r"(KX[c]), "+r"(VX[c]));
                })
                BLOCK_SPLIT(par);
                bar_sync(2 + p, 128);
                if (remote) {
#pragma unroll
                    for (int j = 0; j < 5; j++) ldg128(halo - 8 * XB + j * 512, Z[4 * j], Z[4 * j + 1], Z[4 * j + 2], Z[4 * j + 3]);
                } else {
#pragma unroll
                    for (int j = 0; j < 5; j++) {
                        const uint4 v = lds128(slot + (w ? 0 : 2560) + j * 512);
                        Z[4 * j] = v.x; Z[4 * j + 1] = v.y; Z[4 * j + 2] = v.z; Z[4 * j + 3] = v.w;
                    }
                }
                BOTH(_Pragma("unroll") for (int c = 0; c < 10; c++) {
                    const int jq = jt_of(0, c, odd);
                    Ql[c] = pack_bf16(acc[4 * jq], acc[4 * jq + 1]);
                    Q[c] = pack_bf16(acc[4 * jq + 2], acc[4 * jq + 3]);
                    asm volatile("" : "+r"(Ql[c]), "+r"(Q[c]));
                })
            }
            auto unit = [&](const uint32_t (&q)[10], const uint32_t (&z)[20], const int c0, const uint32_t mx, const float sq, const float nz, const int h) {
                const uint32_t qa = t < 2 ? q[c0 + 2] : 0u, qb = t < 2 ? 0u : q[c0 + 2];
                float xa[4] = {0.f, 0.f, 0.f, 0.f}, za[4] = {0.f, 0.f, 0.f, 0.f}, xb[4], zb[4];
                mma1688(xa, qa, qb, KX[c0 + 2]);
                mma1688(za, qa, qb, z[KI(c0 + 2)]);
#pragma unroll
                for (int e = 0; e < 4; e++) { xb[e] = xa[e]; zb[e] = za[e]; }
                mma16816(xa, q[c0], q[c0 + 3], q[c0 + 1], q[c0 + 4], KX[c0], KX[c0 + 1]);
                mma16816(za, q[c0], q[c0 + 3], q[c0 + 1], q[c0 + 4], z[KI(c0)], z[KI(c0 + 1)]);
                mma16816(xb, q[c0], q[c0 + 3], q[c0 + 1], q[c0 + 4], KX[c0 + 3], KX[c0 + 4]);
                mma16816(zb, q[c0], q[c0 + 3], q[c0 + 1], q[c0 + 4], z[KI(c0 + 3)], z[KI(c0 + 4)]);
                const bool h0 = mx & 1u, h1 = (int)mx < 0;
                const float l00 = h0 ? xa[0] : za[0] + nz, l01 = h1 ? xa[1] : za[1] + nz;
                const float l10 = h0 ? xb[2] : zb[2] + nz, l11 = h1 ? xb[3] : zb[3] + nz;
                float m0 = fmaxf(l00, l01), m1 = fmaxf(l10, l11);
                m0 = fmaxf(m0, shx(m0, 1)); m1 = fmaxf(m1, shx(m1, 1));
                m0 = fmaxf(m0, shx(m0, 2)) * -sq; m1 = fmaxf(m1, shx(m1, 2)) * -sq;
                const uint32_t pa = pack_bf16(ex2(fmaf(l00, sq, m0)), ex2(fmaf(l01, sq, m0)));
                const uint32_t pb = pack_bf16(ex2(fmaf(l10, sq, m1)), ex2(fmaf(l11, sq, m1)));
                float dn[4] = {0.f, 0.f, 0.f, 0.f};
                mma1688(dn, pa, pb, 0x3F803F80u);
                const float i0 = rcp(dn[0]), i1 = rcp(dn[2]), i2 = t < 2 ? i0 : i1;
#pragma unroll
                for (int c = 0; c < 5; c++) {
                    float oc[4] = {0.f, 0.f, 0.f, 0.f};
                    mma16816(oc, pa & mx, pb & mx, pa & ~mx, pb & ~mx, VX[c0 + c], z[10 + c0 + c]);
                    const bool first = c < 2 || (c == 2 && t < 2);
                    const float iv = c < 2 ? i0 : (c > 2 ? i1 : i2);
                    A[0][2 * (c0 + c) + h] = pack_bf16((first ? oc[0] : oc[2]) * iv, (first ? oc[1] : oc[3]) * iv);
                }
            };
            const uint32_t mo = (2 * t > g ? 0xFFFFu : 0u) | (2 * t + 1 > g ? 0xFFFF0000u : 0u);
            constexpr float SC = 0.22360679774997896f * LOG2E;
            {
                unsigned spins = 0;
#pragma unroll 1
                while (remote && any((Z[0] & Z[4] & Z[8] & Z[12] & Z[16] & par) == 0u) && ++spins < SPIN) {
#pragma unroll
                    for (int j = 0; j < 5; j++) ldg128(halo - 8 * XB + j * 512, Z[4 * j], Z[4 * j + 1], Z[4 * j + 2], Z[4 * j + 3]);
                }
                TR(r32);
                const float nz = start ? -INFINITY : 0.f;
                unit(Q, Y, 0, mo, s1.x * SC, 0.f, 1);
                unit(Q, Y, 5, mo, s1.x * SC, 0.f, 1);
                unit(Ql, Z, 0, ~mo, s0.x * SC, nz, 0);
                unit(Ql, Z, 5, ~mo, s0.x * SC, nz, 0);
            }
#pragma unroll
            for (int j = 0; j < 5; j++) {
                A[0][4 * j] = (A[0][4 * j] & ~0x10001u) | par;
                stg128(orow + hg * XB + j * 512, A[0][4 * j], A[0][4 * j + 1], A[0][4 * j + 2], A[0][4 * j + 3]);
            }
            if (lane == 0) stg32(flag, par);
            TR(r34);
            if (p) bar_arrive(8, 384);
            BLOCK_SPLIT(par);
            {
                const float r0 = 0.5f * s0.x, r1 = 0.5f * s1.x, n0 = -r0 * s0.y, n1 = -r1 * s1.y;
#pragma unroll
                for (int j = 0; j < 5; j++) {
                    uint32_t gf[4];
#pragma unroll
                    for (int q = 0; q < 4; q++) {
                        const float v0 = fmaf(bflo(xr[j][q]), q & 1 ? r1 : r0, q & 1 ? n1 : n0), v1 = fmaf(bfhi(xr[j][q]), q & 1 ? r1 : r0, q & 1 ? n1 : n0);
                        gf[q] = pack_bf16(fmaf(v0, tanh_a(v0), v0), fmaf(v1, tanh_a(v1), v1));
                    }
                    stsm_x4(ta + OFF_G + j * 32, gf);
                    stsm_x4(ta + OFF_X + j * 32, xr[j]);
                }
            }
        }
        {
            float acc2[40];
            unsigned spins = 0;
            bool again, first = true;
            const uint8_t* src[7];
#pragma unroll
            for (uint32_t i = 0; i < 7; i++) { src[i] = orow + (i >= hg ? XB : 0u); asm volatile("" : "+l"(src[i])); }
            uint32_t a0 = ta + (hg & 1) * 32, a4 = ta + (~hg & 1) * 128;
            asm volatile("" : "+r"(a0), "+r"(a4));
            mbar_wait(sb + B_SEL, 0);
            const float2 sel = lds64f(sb + M_SEL);
            uint32_t routed = (U(sel.x) >> 4) == warp || (U(sel.y) >> 4) == warp;
            asm volatile("" : "+r"(routed));
            uint32_t xf[5][4], gf[5][4];
            BLOCK_SPLIT(par);
            if (p) bar_sync(9, 288); else bar_sync(5, 160);
#pragma unroll 1
            do {
#pragma unroll
                for (uint32_t i = 1; i <= AHEAD; i++)
#pragma unroll
                    for (int j = 0; j < 5; j++)
                        ldg128(src[i - 1] + (i - 1) * XB + j * 512, A[i][4 * j], A[i][4 * j + 1], A[i][4 * j + 2], A[i][4 * j + 3]);
                if (!p && first) bar_sync(8, 384);
#pragma unroll
                for (int i = 0; i < 7; i++) {
                    if (i == 5 && !p && first) bar_sync(6, 160);
                    if (AHEAD < 6 || (i != 4 && i != 6)) wgmma_fence();
#pragma unroll
                    for (int j = 0; j < 5; j++) {
                        wgmma_rs_n80(acc2, A[i][4 * j], A[i][4 * j + 1], A[i][4 * j + 2], A[i][4 * j + 3],
                                     mk(sbd + ((OFF_WO + i * WO_SLOT) >> 4) + j * 64 + (320 << 16), HI64), i || j);
                        if (j == LDAT && i >= 1 && i + AHEAD <= 7) {
                            if (AHEAD < 6) bar_arrive(10, 32);
                            const int n = (i + AHEAD) % 7;
#pragma unroll
                            for (int q = 0; q < 5; q++)
                                ldg128(src[(n + 6) % 7] + ((n + 6) % 7) * XB + q * 512, A[n][4 * q], A[n][4 * q + 1], A[n][4 * q + 2], A[n][4 * q + 3]);
                            if (AHEAD < 6) bar_arrive(10, 32);
                        }
                        if (i == 6 && j == CHKJ) {
                            uint32_t mn = par;
#pragma unroll
                            for (int q = 1; q < 8; q++) mn &= A[q % 7][0] & A[q % 7][4] & A[q % 7][8] & A[q % 7][12] & A[q % 7][16];
                            again = bar_or(2 + p, 128, mn == 0u && ++spins < SPIN);
                        }
                    }
                    if (i < 2 || i > 4) wgmma_commit();
                    if (i == SERAT && !p && first) bar_arrive(9, 288);
                    if (i == 0) TR(r22);
                    if (i == 1) wgmma_wait<1>();
                }
                first = false;
                if (again) {
                    wgmma_wait<0>();
#pragma unroll
                    for (int j = 0; j < 5; j++)
                        ldg128(orow + hg * XB + j * 512, A[0][4 * j], A[0][4 * j + 1], A[0][4 * j + 2], A[0][4 * j + 3]);
                }
            } while (again);
            wgmma_wait<1>();
            wgmma_fence();
#pragma unroll
            for (int j = 0; j < 5; j++) {
                wgmma_rs_n80(acc2, A[0][4 * j], A[0][4 * j + 1], A[0][4 * j + 2], A[0][4 * j + 3],
                             mk(sbd + ((OFF_WO + 7 * WO_SLOT) >> 4) + j * 64 + (320 << 16), HI64), 1);
#pragma unroll
                for (int c = 0; c < 5; c++) {
                    if (LDJ < 5 ? j == LDJ : j == c) {
                        if (LDJ == 5 || (LDJ && c == 0)) bar_arrive(10, 32);
                        ldsm_x4(xf[c], (c < 4 ? a0 + c * 32 : a4) + OFF_X);
                        ldsm_x4(gf[c], (c < 4 ? a0 + c * 32 : a4) + OFF_G);
                    }
                }
            }
            wgmma_commit();
            if (routed) {
                const float2 sel = lds64f(sb + M_SEL);
                const uint32_t row = warp * 16 + (lane & 15);
                const uint32_t go = row == U(sel.x) ? M_UPD - row * 160 : (row == U(sel.y) ? M_UPD + 160 - row * 160 : OFF_G);
                mbar_wait(sb + B_UPD, 0);
#pragma unroll
                for (int c = 0; c < 5; c++) ldsm_x4(gf[c], (c < 4 ? a0 + c * 32 : a4) + go);
            }
            wgmma_wait<0>();
#pragma unroll
            for (int i = 0; i < 40; i++) asm volatile("" : "+f"(acc2[i]) :: "memory");
            TR(r44);
#pragma unroll
            for (int c = 0; c < 5; c++) {
#pragma unroll
                for (int q = 0; q < 4; q++)
                    asm("fma.rn.bf16x2 %0, %1, %2, %0;" : "+r"(xf[c][q]) : "r"(pack_bf16(acc2[8 * c + 2 * q], acc2[8 * c + 2 * q + 1])), "r"(gf[c][q]));
                stsm_x4((c < 4 ? a0 + c * 32 : a4) + OFF_X, xf[c]);
            }
            fence_proxy_async_smem();
            __syncwarp();
            if (lane == 0) {
                tma_st(&P.tm[T_OUT], sb + OFF_X + warp * 2560, hg * 80, rb * 64 + 16 * w, p);
                asm volatile("cp.async.bulk.wait_group.read 0;" ::: "memory");
            }
        }
        TS(46);
        TRW(r12, 12); TRW(r32, 32); TRW(r34, 34); TRW(r22, 22); TRW(r44, 44);
    } else if (warp >= 12) {
        asm volatile("setmaxnreg.dec.sync.aligned.u32 24;");
        if (warp == 12) {
            uint32_t slot = t0 + PACE0;
            if (elect()) {
                TS(48);
#pragma unroll 1
                for (uint32_t kb = 1; kb < 10; kb++) {
                    const uint32_t s = (kb + 2) & 3;
                    const uint32_t st = sb + s * ST, fb = sb + B_FULL + 8 * s;
                    const uint32_t kc = kb * 64 + (kb < 5 ? k0 : -k0);
                    if (kb >= 4) {
                        mbar_wait(fb + 32, kb >> 3);
                        if (kb < 9) mbar_wait(sb + B_AX - 32 + 8 * kb, 0);
                    }
                    {
                        slot += PACE1;
#pragma unroll 1
                        while ((int)(clock32() - slot) < 0) { }
                        mbar_expect_tx(fb, ST);
                        tma(st, &P.tm[T_X], fb, kc, rb * 64);
                    }
                    tma_mc(st + ST_BM + rank * 12288, &P.tm[T_W], fb, hg * 80 + (hg & ODDX) * 16, kc + rank * 32);
                    tma_mc(st + ST_BR + rank * 3072, &P.tm[T_WR], fb, hg * 80 + 64 - (hg & ODDX) * 64, kc + rank * 32);
                }
                TS(49);
                mbar_wait(sb + B_EMPTY, 1);
                mbar_expect_tx(sb + B_X, 20480);
                tma(sb + OFF_DN, &P.tm[T_D], sb + B_X, 0, 32 * fp, 5 * rank);
                uint32_t wb = sb + B_WO - 8;
#pragma unroll 1
                for (uint32_t i = 0; i < 8; i++) {
                    if ((0x25 >> i) & 1) {
                        wb += 8;
                        mbar_wait(wb - (B_WO - B_EMPTY - 8), i == 0);
                        mbar_expect_tx(wb, i == 0 ? 2 * 12800 : 3 * 12800);
                    }
                    if (WOP) {
#pragma unroll 1
                        while ((int)(clock32() - slot) < 0) { }
                        slot = clock32() + WOP;
                    }
                    const uint32_t d = sb + OFF_WO + i * WO_SLOT;
                    const uint32_t kr = 80 * (i ? i - (i <= hg) : hg);
                    tma_mc(d + rank * 5120, &P.tm[T_WO], wb, hg * 80 + (hg & 1) * 16 + rank * 32, kr);
                    tma_mc(d + 10240 + rank * 2560, &P.tm[T_WOR], wb, hg * 80 + (~hg & 1) * 64, kr + rank * 40);
                }
                TS(50);
            }
        } else if (warp == 13) {
            if (elect()) {
#pragma unroll 1
                for (uint32_t i = 0; i < 3; i++) {
#pragma unroll 1
                    while (clock32() - t0 < PX0 + i * PX1) __nanosleep(20);
                    l2_prefetch(P.w + ((i + 2) * 245760 + b * 1920), 1920);
                    l2_prefetch(P.w + ((i + 7) * 245760 + b * 1920), 1920);
                }
#pragma unroll 1
                for (uint32_t i = 0; i < 14; i++) {
#pragma unroll 1
                    while (clock32() - t0 < GU0 + i * GU1) __nanosleep(20);
                    if (i < 10) l2_prefetch(P.wd + (i * 128 + b) * 1728, 1728);
                    else l2_prefetch(P.wo + ((i - 10) * 128 + b) * 1600, 1600);
                }
                TS(59);
            }
        } else if (warp == 15) {
            const uint32_t lane = opaque_tid() & 31;
            const uint8_t* fl = P.scr + (G_FLAG + (rb * 8 + (lane & 7)) * XB + (lane >> 3) * 8);
            cluster_wait();
            mbar_wait(sb + B_PREP, 0);
            const uint32_t par = lds32(sb + M_SEL + 8);
            mbar_wait(sb + B_WO, 0); mbar_wait(sb + B_WO + 8, 0);
            unsigned spins = 0;
            TS(23);
            uint2 f;
#pragma unroll 1
            do f = ldg64(fl); while (any(f.x != par) && ++spins < SPIN);
            bar_arrive(5, 160);
            TS(24);
            mbar_wait(sb + B_WO + 16, 0);
            bar_arrive(6, 160);
#pragma unroll 1
            while (any(f.y != par) && ++spins < SPIN) f.y = ldg32(fl + 4);
            bar_arrive(9, 288);
            TS(25);
        } else {
            uint32_t slot = t0 + GT0;
            cluster_wait();
            if (elect()) {
#pragma unroll 1
                for (uint32_t i = 0; i < 20; i++) {
                    slot += GT1;
#pragma unroll 1
                    while ((int)(clock32() - slot) < 0) __nanosleep(20);
                    tma(sb + OFF_GU + i * 2048, &P.tm[T_GU], sb + B_GU, 32 * fp, rank * 320 + i * 16);
                }
            }
        }
    } else {
        asm volatile("setmaxnreg.dec.sync.aligned.u32 72;");
        const uint32_t at = opaque_tid() - 256, lane = at & 31, g = lane >> 2, t = lane & 3, c7 = lane & 7, aw = warp - 8;
        uint8_t* const yz = P.scr + (G_Y + b * 512 + at * 4);
        stg32(yz, 0u);
        __nanosleep(AUXS);
        const uint32_t epoch = ldg32(P.scr + G_EPOCH) + 1 + ldg32(yz), tag = (epoch & 15u) | 16u;
        const uint32_t empty_cl = mapa(sb + B_EMPTY, lane & 1);
        unsigned spins = 0;
        TRD(r51); TRD(r30); TRD(r52); TRD(r53); TRD(r54); TRD(r55); TRD(r20); TRD(r22);
        {
            const uint2 wv = __ldg(reinterpret_cast<const uint2*>(P.w_r + k0 * 2 + min(at, 79u) * 8));
            if (at < 80) sts64(sb + M_UPD + at * 8, wv.x, wv.y);
        }
        uint8_t* const stw = P.scr + (b * XB + G_ST + (lane & 4) * 64 + (at >> 3) * 16);
        uint8_t* const csw = P.scr + (b * XB + G_CS + at);
        uint8_t* const tpw = P.scr + (G_TOP + (hg >> 2) * XB + rb * 64 + aw * 16);
        const bool tpub = lane == 0 && (hg & 3) == TPUB;
        cluster_wait();
        bar_sync(4, 128);
        mbar_wait(sb + B_FULL + 16, 0);
        if (t == 0) { stg128(stw, 0u, 0u, 0u, 0u); stg32(csw, 0u); }
        if (tpub) stg128(tpw, 0u, 0u, 0u, 0u);

        uint32_t k1, sv;
        {
            const uint32_t xoff = (32 * (hg & 3) + (at >> 3)) * 128 + ((c7 ^ ((at >> 3) & 7)) << 4);
            const uint32_t jt = (rb >> 2) * 8 + rank * 4 + aw;
            const uint32_t coff = jt < 24 ? ST_BM + (jt >> 3) * 4096 + lane * 128 + (((jt ^ lane) & 7) << 4)
                                          : ST_BR + ((jt >> 1) & 3) * 1024 + lane * 32 + (((jt ^ g) & 1) << 4);
            float q[8], c8[8];
#pragma unroll
            for (int e = 0; e < 8; e++) q[e] = c8[e] = 0.f;
#pragma unroll 1
            for (uint32_t kb = 2; kb < 7; kb++) {
                const uint32_t st = sb + (kb & 3) * ST;
                const uint4 wv = lds128(sb + M_UPD - 256 + kb * 128 + c7 * 16);
                mbar_wait(sb + B_FULL + 8 * (kb & 3), kb == 6);
                const uint4 v = lds128(st + xoff), vn = lds128(st + xoff + 2048);
                const uint4 cv = lds128(st + coff), cn = lds128(st + coff + (jt < 24 ? 12288 : 3072));
                if (lane < 2) mbar_arrive_cl(empty_cl + (B_AX - B_EMPTY - 16) + 8 * kb + (cn.x & 0));
                const uint32_t u[4] = {v.x, v.y, v.z, v.w}, un[4] = {vn.x, vn.y, vn.z, vn.w}, ww[4] = {wv.x, wv.y, wv.z, wv.w};
                const uint32_t cc[4] = {cv.x, cv.y, cv.z, cv.w}, cd[4] = {cn.x, cn.y, cn.z, cn.w};
#pragma unroll
                for (int e = 0; e < 4; e++) {
                    const float a0 = bflo(u[e]), a1 = bfhi(u[e]), b0 = bflo(un[e]), b1 = bfhi(un[e]), w0 = bflo(ww[e]), w1 = bfhi(ww[e]);
                    q[0] += a0 + a1; q[4] += b0 + b1; q[3] += w0 + w1;
                    q[1] = fmaf(a0, a0, fmaf(a1, a1, q[1])); q[5] = fmaf(b0, b0, fmaf(b1, b1, q[5]));
                    q[2] = fmaf(a0, w0, fmaf(a1, w1, q[2])); q[6] = fmaf(b0, w0, fmaf(b1, w1, q[6]));
                    c8[2 * e] += bflo(cc[e]) + bflo(cd[e]); c8[2 * e + 1] += bfhi(cc[e]) + bfhi(cd[e]);
                }
            }
            TR(r51);
            q[7] = q[3];
#pragma unroll
            for (int e = 0; e < 4; e++) {
                q[e] = ((lane & 4) ? q[e + 4] : q[e]) + shx((lane & 4) ? q[e] : q[e + 4], 4);
                q[e] += shx(q[e], 1); q[e] += shx(q[e], 2);
            }
            const float mh = q[0] * (1.0f / 320);
            if (t == 0) stg128(stw, U(mh), U(fmaf(-mh, q[0], q[1])), U(q[2]), (U(q[3]) & ~31u) | tag);
#define TSTEP(H) { const bool up = (lane & (4 * H)) != 0; _Pragma("unroll") for (int e = 0; e < H; e++) { \
            const float send = up ? c8[e] : c8[e + H]; const float keep = up ? c8[e + H] : c8[e]; \
            c8[e] = keep + shx(send, 4 * H); } }
            TSTEP(4) TSTEP(2) TSTEP(1)
#undef TSTEP
            c8[0] += shx(c8[0], 1); c8[0] += shx(c8[0], 2);
            if (t == 0) stg32(csw, (U(c8[0]) & ~31u) | tag);
            TR(r30);
            const uint8_t* csp = P.scr + (G_CS + (aw * 32 + (lane >> 4) * 8 + hg) * XB + (lane & 15) * 8);
            const uint8_t* stp = P.scr + (G_ST + (rb * 8 + aw) * XB + lane * 16);
            uint32_t ra[4], rc[4];
            uint2 ca, cc;
#pragma unroll 1
            while (clock32() - t0 < EX1T) __nanosleep(20);
#pragma unroll 1
            do {
                ldg128(stp, ra[0], ra[1], ra[2], ra[3]);
                ldg128(stp + 4 * XB, rc[0], rc[1], rc[2], rc[3]);
                ca = ldg64(csp); cc = ldg64(csp + 16 * XB);
            } while (any((ra[3] ^ tag | rc[3] ^ tag) & 31u) && ++spins < SPIN);
            TR(r20);
            const float dm = 0.5f * (F(ra[0]) - F(rc[0])), m = bf16r(F(rc[0]) + dm);
            const float sd = bf16r(sqrt_a(bf16r(bf16r(fmaxf(fmaf(dm, dm, (F(ra[1]) + F(rc[1])) * (1.0f / DM)), 0.f)) + 1e-5f)));
            const float rs = rcp(sd);
            uint32_t w1, w2;
            if ((hg & 3) == TPUB) {
                k1 = pack_bf16(0.f, fmaf(-m, F(ra[3]) + F(rc[3]), F(ra[2]) + F(rc[2])) * rs);
                k1 ^= ((int)k1 >> 31) | 0x80000000u;
                k1 = (k1 & 0xFFFF0000u) | ((2047 - (rb * 128 + 2 * (at & 63) + (at >> 6))) << 5) | tag;
                w1 = redux_max(k1); w2 = redux_max(k1 == w1 ? 0u : k1);
                sv = U(m) | (U(sd) >> 16);
                const uint32_t v1 = redux_max(k1 == w1 ? sv : 0u), v2 = redux_max(k1 == w2 ? sv : 0u);
                if (lane == 0) stg128(tpw, w1, v1, w2, v2);
            }
            sts64(sb + M_ST + at * 8, U(rs), U(m));
            sts32(sb + M_SEL + 8, (tag & 1) ? 1u : 0x10000u);
#pragma unroll 1
            while (any((ca.x ^ tag | ca.y ^ tag | cc.x ^ tag | cc.y ^ tag) & 31u) && ++spins < SPIN) { ca = ldg64(csp); cc = ldg64(csp + 16 * XB); }
            {
                const float c0 = at < 120 ? F(ca.x) + F(cc.x) : 0.f, c1 = at < 120 ? F(ca.y) + F(cc.y) : 0.f;
                const uint32_t hi = pack_bf16(c0, c1);
                sts32(sb + M_CS + (at >> 2) * 32 + t * 4, hi);
                sts32(sb + M_CS + (at >> 2) * 32 + t * 4 + 16, pack_bf16(c0 - bflo(hi), c1 - bfhi(hi)));
                fence_proxy_async_smem();
                __syncwarp();
                if (lane < 2) mbar_arrive(sb + B_PREP);
            }
            TR(r52);
            if (aw == 0) {
                uint32_t ka[4], kb[4];
#pragma unroll 1
                while (clock32() - t0 < EX1T + EX2D) __nanosleep(20);
#pragma unroll 1
                do {
                    const uint8_t* tp = P.scr + (G_TOP + lane * 16);
                    uint32_t kc[4], kd[4];
                    ldg128(tp, ka[0], ka[1], ka[2], ka[3]);
                    ldg128(tp + 512, kb[0], kb[1], kb[2], kb[3]);
                    ldg128(tp + XB, kc[0], kc[1], kc[2], kc[3]);
                    ldg128(tp + XB + 512, kd[0], kd[1], kd[2], kd[3]);
                    const bool ba = (ka[0] ^ tag) & 31u, bb = (kb[0] ^ tag) & 31u;
#pragma unroll
                    for (int e = 0; e < 4; e++) { ka[e] = ba ? kc[e] : ka[e]; kb[e] = bb ? kd[e] : kb[e]; }
                } while (any((ka[0] ^ tag | kb[0] ^ tag) & 31u) && ++spins < SPIN);
                TR(r22);
                if (kb[0] > ka[0]) {
#pragma unroll
                    for (int e = 0; e < 4; e++) { const uint32_t x = ka[e]; ka[e] = kb[e]; kb[e] = x; }
                }
                if (kb[0] > ka[2]) { ka[2] = kb[0]; ka[3] = kb[1]; }
                w1 = redux_max(ka[0]);
                const uint32_t t1 = redux_max(ka[0] == w1 ? ka[1] : 0u);
                if (ka[0] == w1) { ka[0] = ka[2]; ka[1] = ka[3]; }
                w2 = redux_max(ka[0]);
                const uint32_t t3 = redux_max(ka[0] == w2 ? ka[1] : 0u);
                sts128(sb + M_TOP, w1, t1, w2, t3);
            }
            bar_sync(4, 128);
            const float2 tv = lds64f(sb + M_TOP + (lane & 1) * 8);
            k1 = U(tv.x);
            sv = U(tv.y);
        }
        TR(r53);
        const uint32_t tok = ~(k1 >> 5) & 2047;
        const unsigned owns = __ballot_sync(0xffffffffu, (tok >> 7) == rb) & 3u;
        if (at < 2) sts32(sb + M_SEL + at * 4, (tok >> 7) == rb ? (tok & 1) * 64 + ((tok & 127) >> 1) : ~0u);
        if ((at | b) == 0) *reinterpret_cast<uint32_t*>(P.scr + G_EPOCH) = epoch;
        __syncwarp();
        if (at == 0) mbar_arrive(sb + B_SEL);
        if (fp < NFFN / 2) {
            uint4 xv = __ldg(reinterpret_cast<const uint4*>(P.x + (tok * 1280 + rank * 640 + min(at >> 1, 39u) * 16)));
            const uint32_t m2 = __byte_perm(sv, 0, 0x3232);
            asm("sub.rn.bf16x2 %0, %0, %4;\nsub.rn.bf16x2 %1, %1, %4;\nsub.rn.bf16x2 %2, %2, %4;\nsub.rn.bf16x2 %3, %3, %4;"
                : "+r"(xv.x), "+r"(xv.y), "+r"(xv.z), "+r"(xv.w) : "r"(m2));
            mbar_wait(sb + B_X, 0);
            if (at < 80) sts128(sb + OFF_PART + at * 16, xv.x, xv.y, xv.z, xv.w);
            mbar_wait(sb + B_GU, 0);
            mbar_wait(sb + B_EMPTY + 24, 0);
            bar_sync(4, 128);
            float c[5][4];
#pragma unroll
            for (int i = 0; i < 5; i++) c[i][0] = c[i][1] = c[i][2] = c[i][3] = 0.f;
            const uint32_t mi = lane >> 3, kr = c7 + (mi >> 1) * 8;
            {
                const uint32_t wa = sb + OFF_GU + (aw >> 1) * 1024 + kr * 64 + ((((aw & 1) * 2 + (mi & 1)) ^ ((kr >> 1) & 3)) << 4);
#pragma unroll
                for (uint32_t i = 0; i < 10; i++) {
                    uint32_t xb[4], a0[4], a1[4];
                    ldsm_x4(xb, sb + OFF_PART + i * 128 + mi * 32 + (lane & 1) * 16);
                    ldsm_x4_t(a0, wa + i * 4096);
                    ldsm_x4_t(a1, wa + i * 4096 + 2048);
                    mma16816(c[(2 * i) & 3], a0[0], a0[1], a0[2], a0[3], xb[0], xb[1]);
                    mma16816(c[(2 * i + 1) & 3], a1[0], a1[1], a1[2], a1[3], xb[2], xb[3]);
                }
#pragma unroll
                for (int e = 0; e < 4; e++) { c[0][e] = (c[0][e] + c[1][e]) + (c[2][e] + c[3][e]); }
                const uint32_t rd = mapa(sb, rank ^ (t & 1));
                if (t < 2)
                    asm volatile("st.async.shared::cluster.mbarrier::complete_tx::bytes.v4.f32 [%0], {%1,%2,%3,%4}, [%5];"
                                 :: "r"(rd + (t ? OFF_PART + 1280 : M_UPD + 192) + aw * 128 + g * 16), "f"(c[0][0]), "f"(c[0][1]), "f"(c[0][2]), "f"(c[0][3]), "r"(rd + B_H) : "memory");
            }
            TR(r54);
            const float rs = rcp(bflo(sv));
            const uint32_t da = sb + OFF_DN + kr * 128 + (((2 * aw + (mi & 1)) ^ c7) << 4);
            uint8_t* yp = P.scr + (G_Y + (fp % 6) * 10240 + rank * 2560 + t * 512 + aw * 128 + g * 16);
#pragma unroll
            for (int i = 0; i < 5; i++) c[i][0] = c[i][1] = c[i][2] = c[i][3] = 0.f;
            mbar_wait(sb + B_H, 0);
#pragma unroll
            for (uint32_t ks = 0; ks < 2; ks++) {
                const uint32_t og = sb + ks * 128 + lane * 4 + P.up_first, ou = og ^ 256;
                const float gs = bf16r((F(lds32(og + M_UPD + 192)) + F(lds32(og + OFF_PART + 1280))) * rs);
                const float h = bf16r(gs * sigm(gs)) * bf16r((F(lds32(ou + M_UPD + 192)) + F(lds32(ou + OFF_PART + 1280))) * rs);
                const uint32_t hp = pack_bf16(h, __shfl_down_sync(0xffffffffu, h, 4));
                const uint32_t h0 = __shfl_sync(0xffffffffu, hp, t * 8 + (g & 1)), h1 = __shfl_sync(0xffffffffu, hp, t * 8 + (g & 1) + 2);
#pragma unroll
                for (uint32_t j = 0; j < 5; j++) {
                    uint32_t a[4];
                    ldsm_x4_t(a, da + j * 4096 + ks * 2048);
                    mma16816(c[j], a[0], a[1], a[2], a[3], h0, h1);
                }
            }
#pragma unroll
            for (int e = 0; e < 4; e++) {
                const float lo = (t & 1) ? c[1][e] : c[0][e], hi = (t & 1) ? c[3][e] : c[2][e];
                c[0][e] = (t & 2) ? hi : lo;
            }
            asm volatile("" : "+f"(c[0][0]), "+f"(c[4][0]) :: "memory");
            BLOCK_SPLIT(tag);
            bar_sync(8, 384);
            { red4(yp, c[0][0], c[0][2]); red4(yp + 5120, c[0][1], c[0][3]); }
            if (t == 0) { red4(yp + 2048, c[4][0], c[4][2]); red4(yp + 2048 + 5120, c[4][1], c[4][3]); }
            TR(r55);
        }
        else bar_arrive(8, 384);
        mbar_wait(sb + B_X, 0); mbar_wait(sb + B_GU, 0);
        TRW(r51, 51); TRW(r30, 30); TRW(r52, 52); TRW(r53, 53); TRW(r54, 54); TRW(r55, 55); TRW(r20, 20); TRW(r22, 22);
        if (owns) {
            const uint32_t u = min(at >> 1, 39u), col = (u >> 3) * 32 + (u & 7) * 2;
            const bool mine = (tok >> 7) == rb;
            k1 ^= ((~(int)k1) >> 31) | 0x80000000u;
            const float sg = bf16r(sigm(bfhi(k1))), rs = rcp(bflo(sv));
            uint32_t x0, x1, y0, y1, n0, n1;
            asm volatile("ld.global.nc.u16 %0, [%2];\nld.global.nc.u16 %1, [%2 + 16];" : "=r"(x0), "=r"(x1) : "l"(P.x + (tok * 1280 + hg * 160 + col)));
            const float a0 = (bflo(x0) - bfhi(sv)) * rs, a1 = (bflo(x1) - bfhi(sv)) * rs;
            bar_sync(4, 128);
#pragma unroll 1
            do {
                __nanosleep(YSL);
                uint32_t v[6][4];
#pragma unroll
                for (int r = 0; r < 6; r++) ldg128(P.scr + (G_Y + (at & 1) * 5120 + hg * 640 + u * 16) + r * 10240, v[r][0], v[r][1], v[r][2], v[r][3]);
                y0 = U(((F(v[0][0]) + F(v[1][0])) + (F(v[2][0]) + F(v[3][0]))) + (F(v[4][0]) + F(v[5][0])));
                y1 = U(((F(v[0][1]) + F(v[1][1])) + (F(v[2][1]) + F(v[3][1]))) + (F(v[4][1]) + F(v[5][1])));
                n0 = U(((F(v[0][2]) + F(v[1][2])) + (F(v[2][2]) + F(v[3][2]))) + (F(v[4][2]) + F(v[5][2])));
                n1 = U(((F(v[0][3]) + F(v[1][3])) + (F(v[2][3]) + F(v[3][3]))) + (F(v[4][3]) + F(v[5][3])));
            } while (any(mine && (F(n0) != NFFN / 2 || F(n1) != NFFN / 2)) && ++spins < SPIN);
            const float v0 = a0 + bf16r(bf16r(F(y0)) * sg), v1 = a1 + bf16r(bf16r(F(y1)) * sg);
            const uint32_t gp = pack_bf16(v0 * sigm(v0), v1 * sigm(v1));
            asm volatile("st.shared.u16 [%0], %1;\nst.shared.u16 [%0 + 16], %2;" :: "r"(sb + M_UPD + (at & 1) * 160 + col), "r"(gp), "r"(gp >> 16) : "memory");
            __syncwarp();
            if (lane < 2) mbar_arrive(sb + B_UPD);
            TS(56);
        }
    }
}

typedef CUresult (*EncodeFn)(CUtensorMap*, CUtensorMapDataType, cuuint32_t, void*, const cuuint64_t*, const cuuint64_t*,
                             const cuuint32_t*, const cuuint32_t*, CUtensorMapInterleave, CUtensorMapSwizzle,
                             CUtensorMapL2promotion, CUtensorMapFloatOOBfill);

bool encode(EncodeFn fn, CUtensorMap* tm, const void* ptr, cuuint64_t d0, cuuint64_t d1, cuuint64_t d2, cuuint64_t s1, cuuint64_t s2,
            cuuint32_t b0, cuuint32_t b1, cuuint32_t b2, CUtensorMapSwizzle sw) {
    const cuuint64_t dims[3] = {d0, d1, d2}, strides[2] = {s1, s2};
    const cuuint32_t box[3] = {b0, b1, b2}, es[3] = {1, 1, 1};
    return fn(tm, CU_TENSOR_MAP_DATA_TYPE_BFLOAT16, 3, const_cast<void*>(ptr), dims, strides, box, es,
              CU_TENSOR_MAP_INTERLEAVE_NONE, sw, CU_TENSOR_MAP_L2_PROMOTION_L2_128B,
              CU_TENSOR_MAP_FLOAT_OOB_FILL_NONE) == CUDA_SUCCESS;
}

}

extern "C" void kernel_launch(void* const* d_in, const int* in_sizes, int n_in, void* d_out, int out_size) {
    static Params P;
    static bool by_sm = false;
    static const void* cached[9] = {};
    bool same = cached[8] == d_out;
    for (int i = 0; i < 8; i++) same = same && cached[i] == d_in[i];
    if (!same) {
        const void *x = d_in[0], *wqkv = d_in[1], *wo = d_in[2], *wg = d_in[5], *wu = d_in[6], *wd = d_in[7];
        void* fnp = nullptr;
        cudaDriverEntryPointQueryResult qr;
        cudaGetDriverEntryPoint("cuTensorMapEncodeTiled", &fnp, cudaEnableDefault, &qr);
        EncodeFn fn = (EncodeFn)fnp;
        const CUtensorMapSwizzle S0 = CU_TENSOR_MAP_SWIZZLE_NONE, S32 = CU_TENSOR_MAP_SWIZZLE_32B, S64 = CU_TENSOR_MAP_SWIZZLE_64B,
                                 S128 = CU_TENSOR_MAP_SWIZZLE_128B;
        const bool ok = fn != nullptr &&
            encode(fn, &P.tm[T_X], x, 640, 1024, 2, 2560, 1280, 64, 64, 2, S128) &&
            encode(fn, &P.tm[T_OUT], d_out, 640, 1024, 2, 2560, 1280, 80, 16, 1, S0) &&
            encode(fn, &P.tm[T_W], wqkv, 640, 640, 3, 3840, 1280, 64, 32, 3, S128) &&
            encode(fn, &P.tm[T_WR], wqkv, 640, 640, 3, 3840, 1280, 16, 32, 3, S32) &&
            encode(fn, &P.tm[T_GU], wg < wu ? wg : wu, 1728, 640, 2, 3456, wg < wu ? (const char*)wu - (const char*)wg : (const char*)wg - (const char*)wu,
                   32, 16, 2, S64) &&
            encode(fn, &P.tm[T_D], wd, 64, 1728, 10, 1280, 128, 64, 32, 5, S128) &&
            encode(fn, &P.tm[T_WO], wo, 640, 640, 1, 1280, 1280 * 640, 32, 80, 1, S64) &&
            encode(fn, &P.tm[T_WOR], wo, 640, 640, 1, 1280, 1280 * 640, 16, 40, 1, S64);
        if (!ok) return;
        P.up_first = wg < wu ? 0 : 256;
        P.wo = (const uint8_t*)wo; P.wd = (const uint8_t*)wd;
        P.x = (const uint8_t*)x; P.w = (const uint8_t*)wqkv; P.w_r = (const uint8_t*)d_in[4];
        if (cudaGetSymbolAddress((void**)&P.scr, g_scr) != cudaSuccess) return;
        cudaFuncSetAttribute(fused_kernel<true>, cudaFuncAttributeMaxDynamicSharedMemorySize, SMEM_BYTES);
        cudaFuncSetAttribute(fused_kernel<false>, cudaFuncAttributeMaxDynamicSharedMemorySize, SMEM_BYTES);
        int ncl = 0, sms = 0, dev = 0;
        {
            cudaLaunchConfig_t cfg = {};
            cfg.gridDim = dim3(128); cfg.blockDim = dim3(NTHREADS); cfg.dynamicSmemBytes = SMEM_BYTES;
            cudaLaunchAttribute at[1];
            at[0].id = cudaLaunchAttributeClusterDimension;
            at[0].val.clusterDim.x = 2; at[0].val.clusterDim.y = 1; at[0].val.clusterDim.z = 1;
            cfg.attrs = at; cfg.numAttrs = 1;
            if (cudaOccupancyMaxActiveClusters(&ncl, fused_kernel<true>, &cfg) != cudaSuccess || ncl < 64) return;
            cudaGetDevice(&dev);
            cudaDeviceGetAttribute(&sms, cudaDevAttrMultiProcessorCount, dev);
        }
        by_sm = sms == 132 && ncl == 66;
        for (int i = 0; i < 8; i++) cached[i] = d_in[i];
        cached[8] = d_out;
    }
    if (by_sm) fused_kernel<true><<<132, NTHREADS, SMEM_BYTES>>>(P);
    else fused_kernel<false><<<128, NTHREADS, SMEM_BYTES>>>(P);
}
```

```cpp
#include <cuda_runtime.h>
#include <cuda_bf16.h>
#include <cuda.h>
#include <stdint.h>

namespace {

typedef __nv_bfloat16 bf16;

constexpr int SEQ = 2048, DM = 640;
constexpr int NTHREADS = 512;
constexpr int NFFN = 108;
#define LEAD 2
#define PACE0 100
#define PACE1 950
#define PX0 1500
#define PX1 500
#define GU0 6000
#define GU1 220
#define GT0 2300
#define GT1 430
#define WOP 150
#define AUXS 500
#define EX1T 7800
#define EX2D 2200
#define SERAT 2
#define CHKJ 2
#define LDJ 4
#define YSL 200
#define HGMAP 0x62740351u
#define TPUB 3
#define AHEAD 4
#define LDAT 4
#define STG 0
#define GHOLD 0
#define FFNAT 0
#define WSL 300
#define PXJ 2
#define ODDX 1

constexpr int ST = 47104;
constexpr int ST_BM = 16384, ST_BR = 40960;
constexpr int OFF_X = 0;
constexpr int OFF_DN = 20480;
constexpr int OFF_PART = 40960;
constexpr int OFF_WO = 43008;
constexpr int WO_SLOT = 15360;
constexpr int OFF_GU = 4 * ST;
constexpr int M_ST = OFF_GU + 40960;
constexpr int M_CS = M_ST + 1024;
constexpr int M_UPD = M_CS + 1024;
constexpr int M_TOP = M_UPD + 640;
constexpr int M_SEL = M_TOP + 64;
constexpr int B_Z = M_SEL + 16, B_G = B_Z + 8, B_AX = B_Z + 32, B_PREP = B_AX + 40, B_UPD = B_PREP + 8, B_GU = B_AX + 64, B_X = B_GU + 8, B_H = B_X + 8,
              B_SEL = B_H + 8, B_FULL = B_GU + 32, B_EMPTY = B_FULL + 32, B_HO = B_EMPTY + 32, B_WO = B_HO + 32;
constexpr int SMEM_BYTES = B_WO + 32;
static_assert(SMEM_BYTES <= 232448 && OFF_WO + 3 * WO_SLOT <= 2 * ST && OFF_WO + 6 * WO_SLOT <= 3 * ST && OFF_WO + 8 * WO_SLOT <= 4 * ST, "smem");

enum { T_X, T_W, T_WR, T_GU, T_D, T_WO, T_WOR, T_OUT, T_N };
struct Params {
    CUtensorMap tm[T_N];
    const uint8_t* x;
    const uint8_t* w_r;
    const uint8_t* w;
    const uint8_t* wo;
    const uint8_t* wd;
    uint8_t* scr;
    uint32_t up_first;
};

constexpr uint32_t XB = 27392;
constexpr uint32_t G_TOP = 25600;
constexpr uint32_t G_CS = G_TOP + 1024;
constexpr uint32_t G_ST = G_CS + 128;
constexpr uint32_t G_FLAG = G_ST + 512;
constexpr uint32_t G_Y = 128 * XB;
constexpr uint32_t G_EPOCH = G_Y + 128 * 512;
static_assert(G_FLAG + 128 == XB, "scratch");
__device__ __align__(1024) uint8_t g_scr[G_EPOCH + 1024];

#define TSINIT
#define TR(v)
#define TRD(v)
#define TRW(v, i)
#define TS(i)
#define TSG(i)
constexpr unsigned SPIN = 1u << 20;

__device__ __forceinline__ void mbar_init(uint32_t bar, int cnt) {
    asm volatile("mbarrier.init.shared::cta.b64 [%0], %1;" :: "r"(bar), "r"(cnt) : "memory");
}
__device__ __forceinline__ void mbar_expect_tx(uint32_t bar, int bytes) {
    asm volatile("mbarrier.arrive.expect_tx.shared::cta.b64 _, [%0], %1;" :: "r"(bar), "r"(bytes) : "memory");
}
__device__ __forceinline__ void mbar_arrive(uint32_t bar) {
    asm volatile("mbarrier.arrive.shared::cta.b64 _, [%0];" :: "r"(bar) : "memory");
}
__device__ __forceinline__ uint32_t mapa(uint32_t a, uint32_t cta) {
    uint32_t r;
    asm("mapa.shared::cluster.u32 %0, %1, %2;" : "=r"(r) : "r"(a), "r"(cta));
    return r;
}
__device__ __forceinline__ void mbar_arrive_cl(uint32_t cbar) {
    asm volatile("mbarrier.arrive.shared::cluster.b64 _, [%0];" :: "r"(cbar) : "memory");
}
__device__ __forceinline__ void mbar_wait(uint32_t bar, int parity) {
    asm volatile("{\n.reg .pred p;\nLAB_WAIT:\nmbarrier.try_wait.parity.shared::cta.b64 p, [%0], %1;\n@!p bra LAB_WAIT;\n}"
                 :: "r"(bar), "r"(parity) : "memory");
}
__device__ __forceinline__ bool mbar_try(uint32_t bar, int parity) {
    uint32_t r;
    asm volatile("{\n.reg .pred p;\nmbarrier.test_wait.parity.shared::cta.b64 p, [%1], %2;\nselp.u32 %0, 1, 0, p;\n}"
                 : "=r"(r) : "r"(bar), "r"(parity) : "memory");
    return r != 0;
}
__device__ __forceinline__ void tma(uint32_t dst, const CUtensorMap* tm, uint32_t bar, int c0, int c1, int c2 = 0) {
    asm volatile("cp.async.bulk.tensor.3d.shared::cluster.global.mbarrier::complete_tx::bytes [%0], [%1, {%3, %4, %5}], [%2];"
                 :: "r"(dst), "l"(tm), "r"(bar), "r"(c0), "r"(c1), "r"(c2) : "memory");
}
__device__ __forceinline__ void tma_mc(uint32_t dst, const CUtensorMap* tm, uint32_t bar, int c0, int c1) {
    asm volatile("cp.async.bulk.tensor.3d.shared::cluster.global.mbarrier::complete_tx::bytes.multicast::cluster [%0], [%1, {%3, %4, %5}], [%2], %6;"
                 :: "r"(dst), "l"(tm), "r"(bar), "r"(c0), "r"(c1), "r"(0), "h"((uint16_t)3) : "memory");
}
__device__ __forceinline__ void tma_st(const CUtensorMap* tm, uint32_t src, int c0, int c1, int c2) {
    asm volatile("cp.async.bulk.tensor.3d.global.shared::cta.bulk_group [%0, {%2, %3, %4}], [%1];\ncp.async.bulk.commit_group;"
                 :: "l"(tm), "r"(src), "r"(c0), "r"(c1), "r"(c2) : "memory");
}
__device__ __forceinline__ void l2_prefetch(const void* p, int bytes) {
    asm volatile("cp.async.bulk.prefetch.L2.global [%0], %1;" :: "l"(p), "r"(bytes) : "memory");
}
__device__ __forceinline__ void cluster_arrive() { asm volatile("barrier.cluster.arrive.relaxed.aligned;" ::: "memory"); }
__device__ __forceinline__ void cluster_wait() { asm volatile("barrier.cluster.wait.aligned;" ::: "memory"); }
__device__ __forceinline__ void bar_sync(int id, int n) { asm volatile("bar.sync %0, %1;" :: "r"(id), "r"(n) : "memory"); }
__device__ __forceinline__ void bar_arrive(int id, int n) { asm volatile("bar.arrive %0, %1;" :: "r"(id), "r"(n) : "memory"); }
__device__ __forceinline__ bool bar_or(int id, int n, bool v) {
    uint32_t r;
    asm volatile("{\n.reg .pred p, q;\nsetp.ne.u32 p, %3, 0;\nbar.red.or.pred q, %1, %2, p;\nselp.u32 %0, 1, 0, q;\n}"
                 : "=r"(r) : "r"(id), "r"(n), "r"((uint32_t)v) : "memory");
    return r != 0;
}
__device__ __forceinline__ void fence_proxy_async_smem() { asm volatile("fence.proxy.async.shared::cta;" ::: "memory"); }
__device__ __forceinline__ void stg128(void* p, uint32_t a, uint32_t b, uint32_t c, uint32_t d) {
    asm volatile("{\n.reg .b64 l, h;\n.reg .b128 q;\nmov.b64 l, {%1, %2};\nmov.b64 h, {%3, %4};\nmov.b128 q, {l, h};\n"
                 "st.relaxed.gpu.global.b128 [%0], q;\n}" :: "l"(p), "r"(a), "r"(b), "r"(c), "r"(d) : "memory");
}
__device__ __forceinline__ void ldg128(const void* p, uint32_t& a, uint32_t& b, uint32_t& c, uint32_t& d) {
    asm volatile("{\n.reg .b64 l, h;\n.reg .b128 q;\nld.relaxed.gpu.global.b128 q, [%4];\nmov.b128 {l, h}, q;\n"
                 "mov.b64 {%0, %1}, l;\nmov.b64 {%2, %3}, h;\n}" : "=r"(a), "=r"(b), "=r"(c), "=r"(d) : "l"(p) : "memory");
}
__device__ __forceinline__ void stg64(void* p, uint32_t a, uint32_t b) {
    asm volatile("{\n.reg .b64 l;\nmov.b64 l, {%1, %2};\nst.relaxed.gpu.global.b64 [%0], l;\n}" :: "l"(p), "r"(a), "r"(b) : "memory");
}
__device__ __forceinline__ void red4(void* p, float a, float b) {
    asm volatile("red.relaxed.gpu.global.add.v4.f32 [%0], {%1, %2, %3, %3};" :: "l"(p), "f"(a), "f"(b), "f"(1.0f) : "memory");
}
__device__ __forceinline__ void stg32(void* p, uint32_t a) {
    asm volatile("st.relaxed.gpu.global.u32 [%0], %1;" :: "l"(p), "r"(a) : "memory");
}
__device__ __forceinline__ uint2 ldg64(const void* p) {
    uint2 v;
    asm volatile("{\n.reg .b64 l;\nld.relaxed.gpu.global.b64 l, [%2];\nmov.b64 {%0, %1}, l;\n}" : "=r"(v.x), "=r"(v.y) : "l"(p) : "memory");
    return v;
}
__device__ __forceinline__ unsigned ldg32(const void* p) {
    unsigned v;
    asm volatile("ld.relaxed.gpu.global.u32 %0, [%1];" : "=r"(v) : "l"(p) : "memory");
    return v;
}
__device__ __forceinline__ void ldsm_x4(uint32_t (&r)[4], uint32_t a) {
    asm volatile("ldmatrix.sync.aligned.m8n8.x4.shared.b16 {%0,%1,%2,%3}, [%4];"
                 : "=r"(r[0]), "=r"(r[1]), "=r"(r[2]), "=r"(r[3]) : "r"(a));
}
__device__ __forceinline__ void ldsm_x4_t(uint32_t (&r)[4], uint32_t a) {
    asm volatile("ldmatrix.sync.aligned.m8n8.x4.trans.shared.b16 {%0,%1,%2,%3}, [%4];"
                 : "=r"(r[0]), "=r"(r[1]), "=r"(r[2]), "=r"(r[3]) : "r"(a));
}
__device__ __forceinline__ void stsm_x4(uint32_t a, const uint32_t (&r)[4]) {
    asm volatile("stmatrix.sync.aligned.m8n8.x4.shared.b16 [%0], {%1,%2,%3,%4};"
                 :: "r"(a), "r"(r[0]), "r"(r[1]), "r"(r[2]), "r"(r[3]));
}
__device__ __forceinline__ uint32_t movm(uint32_t a) {
    uint32_t d;
    asm("movmatrix.sync.aligned.m8n8.trans.b16 %0, %1;" : "=r"(d) : "r"(a));
    return d;
}
__device__ __forceinline__ void mma16816(float (&c)[4], uint32_t a0, uint32_t a1, uint32_t a2, uint32_t a3, uint32_t b0, uint32_t b1) {
    asm("mma.sync.aligned.m16n8k16.row.col.f32.bf16.bf16.f32 {%0,%1,%2,%3}, {%4,%5,%6,%7}, {%8,%9}, {%0,%1,%2,%3};"
        : "+f"(c[0]), "+f"(c[1]), "+f"(c[2]), "+f"(c[3]) : "r"(a0), "r"(a1), "r"(a2), "r"(a3), "r"(b0), "r"(b1));
}
__device__ __forceinline__ void mma1688(float (&c)[4], uint32_t a0, uint32_t a1, uint32_t b0) {
    asm("mma.sync.aligned.m16n8k8.row.col.f32.bf16.bf16.f32 {%0,%1,%2,%3}, {%4,%5}, {%6}, {%0,%1,%2,%3};"
        : "+f"(c[0]), "+f"(c[1]), "+f"(c[2]), "+f"(c[3]) : "r"(a0), "r"(a1), "r"(b0));
}
__device__ __forceinline__ void wgmma_fence() { asm volatile("wgmma.fence.sync.aligned;" ::: "memory"); }
__device__ __forceinline__ void wgmma_commit() { asm volatile("wgmma.commit_group.sync.aligned;" ::: "memory"); }
template <int N> __device__ __forceinline__ void wgmma_wait() { asm volatile("wgmma.wait_group.sync.aligned %0;" :: "n"(N) : "memory"); }
__device__ __forceinline__ uint64_t mk(uint32_t lo, uint32_t hi) { return (uint64_t)lo | ((uint64_t)hi << 32); }
constexpr uint32_t HI128 = (1024 >> 4) | (1u << 30), HI64 = (512 >> 4) | (2u << 30), HI32 = (256 >> 4) | (3u << 30);
__device__ __forceinline__ uint32_t pack_bf16(float lo, float hi) {
    uint32_t r;
    asm("cvt.rn.bf16x2.f32 %0, %1, %2;" : "=r"(r) : "f"(hi), "f"(lo));
    return r;
}
__device__ __forceinline__ float bflo(uint32_t u) { return __uint_as_float(u << 16); }
__device__ __forceinline__ float bfhi(uint32_t u) { return __uint_as_float(u & 0xFFFF0000u); }
__device__ __forceinline__ float bf16r(float v) { return __uint_as_float(pack_bf16(0.f, v)); }
__device__ __forceinline__ float ex2(float v) { float r; asm("ex2.approx.ftz.f32 %0, %1;" : "=f"(r) : "f"(v)); return r; }
__device__ __forceinline__ float rcp(float v) { float r; asm("rcp.approx.ftz.f32 %0, %1;" : "=f"(r) : "f"(v)); return r; }
__device__ __forceinline__ float sqrt_a(float v) { float r; asm("sqrt.approx.ftz.f32 %0, %1;" : "=f"(r) : "f"(v)); return r; }
__device__ __forceinline__ float tanh_a(float v) { float r; asm("tanh.approx.f32 %0, %1;" : "=f"(r) : "f"(v)); return r; }
constexpr float LOG2E = 1.4426950408889634f;
__device__ __forceinline__ float sigm(float v) { return rcp(1.0f + ex2(-LOG2E * v)); }
__device__ __forceinline__ uint4 lds128(uint32_t a) {
    uint4 v;
    asm volatile("ld.shared.v4.u32 {%0,%1,%2,%3}, [%4];" : "=r"(v.x), "=r"(v.y), "=r"(v.z), "=r"(v.w) : "r"(a));
    return v;
}
__device__ __forceinline__ float4 lds128f(uint32_t a) {
    float4 v;
    asm volatile("ld.shared.v4.f32 {%0,%1,%2,%3}, [%4];" : "=f"(v.x), "=f"(v.y), "=f"(v.z), "=f"(v.w) : "r"(a));
    return v;
}
__device__ __forceinline__ float2 lds64f(uint32_t a) {
    float2 v;
    asm volatile("ld.shared.v2.f32 {%0,%1}, [%2];" : "=f"(v.x), "=f"(v.y) : "r"(a));
    return v;
}
__device__ __forceinline__ uint32_t lds32(uint32_t a) {
    uint32_t v;
    asm volatile("ld.shared.u32 %0, [%1];" : "=r"(v) : "r"(a));
    return v;
}
__device__ __forceinline__ void sts128(uint32_t a, uint32_t x, uint32_t y, uint32_t z, uint32_t w) {
    asm volatile("st.shared.v4.u32 [%0], {%1,%2,%3,%4};" :: "r"(a), "r"(x), "r"(y), "r"(z), "r"(w) : "memory");
}
__device__ __forceinline__ void sts64(uint32_t a, uint32_t x, uint32_t y) {
    asm volatile("st.shared.v2.u32 [%0], {%1,%2};" :: "r"(a), "r"(x), "r"(y) : "memory");
}
__device__ __forceinline__ void sts32(uint32_t a, uint32_t x) { asm volatile("st.shared.u32 [%0], %1;" :: "r"(a), "r"(x) : "memory"); }
__device__ __forceinline__ unsigned redux_max(unsigned v) {
    unsigned r;
    asm volatile("redux.sync.max.u32 %0, %1, 0xffffffff;" : "=r"(r) : "r"(v));
    return r;
}
__device__ __forceinline__ float shx(float v, int o) { return __shfl_xor_sync(0xffffffffu, v, o); }
__device__ __forceinline__ uint32_t U(float v) { return __float_as_uint(v); }
__device__ __forceinline__ float F(uint32_t v) { return __uint_as_float(v); }

__device__ __forceinline__ void wgmma_n192_lo(float (&d)[120], uint64_t da, uint64_t db, int scale_d) {
    asm volatile("{\n.reg .pred p;\nsetp.ne.b32 p, %98, 0;\n"
        "wgmma.mma_async.sync.aligned.m64n192k16.f32.bf16.bf16 "
        "{%0, %1, %2, %3, %4, %5, %6, %7, %8, %9, %10, %11, %12, %13, %14, %15, "
        "%16, %17, %18, %19, %20, %21, %22, %23, %24, %25, %26, %27, %28, %29, %30, %31, "
        "%32, %33, %34, %35, %36, %37, %38, %39, %40, %41, %42, %43, %44, %45, %46, %47, "
        "%48, %49, %50, %51, %52, %53, %54, %55, %56, %57, %58, %59, %60, %61, %62, %63, "
        "%64, %65, %66, %67, %68, %69, %70, %71, %72, %73, %74, %75, %76, %77, %78, %79, "
        "%80, %81, %82, %83, %84, %85, %86, %87, %88, %89, %90, %91, %92, %93, %94, %95}, "
        "%96, %97, p, 1, 1, 0, 1;\n}\n"
        : "+f"(d[0]), "+f"(d[1]), "+f"(d[2]), "+f"(d[3]), "+f"(d[4]), "+f"(d[5]), "+f"(d[6]), "+f"(d[7]),
          "+f"(d[8]), "+f"(d[9]), "+f"(d[10]), "+f"(d[11]), "+f"(d[12]), "+f"(d[13]), "+f"(d[14]), "+f"(d[15]),
          "+f"(d[16]), "+f"(d[17]), "+f"(d[18]), "+f"(d[19]), "+f"(d[20]), "+f"(d[21]), "+f"(d[22]), "+f"(d[23]),
          "+f"(d[24]), "+f"(d[25]), "+f"(d[26]), "+f"(d[27]), "+f"(d[28]), "+f"(d[29]), "+f"(d[30]), "+f"(d[31]),
          "+f"(d[32]), "+f"(d[33]), "+f"(d[34]), "+f"(d[35]), "+f"(d[36]), "+f"(d[37]), "+f"(d[38]), "+f"(d[39]),
          "+f"(d[40]), "+f"(d[41]), "+f"(d[42]), "+f"(d[43]), "+f"(d[44]), "+f"(d[45]), "+f"(d[46]), "+f"(d[47]),
          "+f"(d[48]), "+f"(d[49]), "+f"(d[50]), "+f"(d[51]), "+f"(d[52]), "+f"(d[53]), "+f"(d[54]), "+f"(d[55]),
          "+f"(d[56]), "+f"(d[57]), "+f"(d[58]), "+f"(d[59]), "+f"(d[60]), "+f"(d[61]), "+f"(d[62]), "+f"(d[63]),
          "+f"(d[64]), "+f"(d[65]), "+f"(d[66]), "+f"(d[67]), "+f"(d[68]), "+f"(d[69]), "+f"(d[70]), "+f"(d[71]),
          "+f"(d[72]), "+f"(d[73]), "+f"(d[74]), "+f"(d[75]), "+f"(d[76]), "+f"(d[77]), "+f"(d[78]), "+f"(d[79]),
          "+f"(d[80]), "+f"(d[81]), "+f"(d[82]), "+f"(d[83]), "+f"(d[84]), "+f"(d[85]), "+f"(d[86]), "+f"(d[87]),
          "+f"(d[88]), "+f"(d[89]), "+f"(d[90]), "+f"(d[91]), "+f"(d[92]), "+f"(d[93]), "+f"(d[94]), "+f"(d[95])
        : "l"(da), "l"(db), "r"(scale_d));
}
__device__ __forceinline__ void wgmma_n48_hi(float (&d)[120], uint64_t da, uint64_t db, int scale_d) {
    asm volatile("{\n.reg .pred p;\nsetp.ne.b32 p, %26, 0;\n"
        "wgmma.mma_async.sync.aligned.m64n48k16.f32.bf16.bf16 "
        "{%0, %1, %2, %3, %4, %5, %6, %7, %8, %9, %10, %11, %12, %13, %14, %15, "
        "%16, %17, %18, %19, %20, %21, %22, %23}, "
        "%24, %25, p, 1, 1, 0, 1;\n}\n"
        : "+f"(d[96]), "+f"(d[97]), "+f"(d[98]), "+f"(d[99]), "+f"(d[100]), "+f"(d[101]), "+f"(d[102]), "+f"(d[103]),
          "+f"(d[104]), "+f"(d[105]), "+f"(d[106]), "+f"(d[107]), "+f"(d[108]), "+f"(d[109]), "+f"(d[110]), "+f"(d[111]),
          "+f"(d[112]), "+f"(d[113]), "+f"(d[114]), "+f"(d[115]), "+f"(d[116]), "+f"(d[117]), "+f"(d[118]), "+f"(d[119])
        : "l"(da), "l"(db), "r"(scale_d));
}
__device__ __forceinline__ void wgmma_rs_n80(float (&d)[40], uint32_t a0, uint32_t a1, uint32_t a2, uint32_t a3, uint64_t db, int scale_d) {
    asm volatile("{\n.reg .pred p;\nsetp.ne.b32 p, %45, 0;\n"
        "wgmma.mma_async.sync.aligned.m64n80k16.f32.bf16.bf16 "
        "{%0, %1, %2, %3, %4, %5, %6, %7, %8, %9, %10, %11, %12, %13, %14, %15, "
        "%16, %17, %18, %19, %20, %21, %22, %23, %24, %25, %26, %27, %28, %29, %30, %31, "
        "%32, %33, %34, %35, %36, %37, %38, %39}, "
        "{%40, %41, %42, %43}, %44, p, 1, 1, 1;\n}\n"
        : "+f"(d[0]), "+f"(d[1]), "+f"(d[2]), "+f"(d[3]), "+f"(d[4]), "+f"(d[5]), "+f"(d[6]), "+f"(d[7]),
          "+f"(d[8]), "+f"(d[9]), "+f"(d[10]), "+f"(d[11]), "+f"(d[12]), "+f"(d[13]), "+f"(d[14]), "+f"(d[15]),
          "+f"(d[16]), "+f"(d[17]), "+f"(d[18]), "+f"(d[19]), "+f"(d[20]), "+f"(d[21]), "+f"(d[22]), "+f"(d[23]),
          "+f"(d[24]), "+f"(d[25]), "+f"(d[26]), "+f"(d[27]), "+f"(d[28]), "+f"(d[29]), "+f"(d[30]), "+f"(d[31]),
          "+f"(d[32]), "+f"(d[33]), "+f"(d[34]), "+f"(d[35]), "+f"(d[36]), "+f"(d[37]), "+f"(d[38]), "+f"(d[39])
        : "r"(a0), "r"(a1), "r"(a2), "r"(a3), "l"(db), "r"(scale_d));
}
__device__ __forceinline__ void wgmma_rs_n192_lo(float (&d)[120], uint32_t a0, uint32_t a1, uint32_t a2, uint32_t a3, uint64_t db, int scale_d) {
    asm volatile("{\n.reg .pred p;\nsetp.ne.b32 p, %101, 0;\n"
        "wgmma.mma_async.sync.aligned.m64n192k16.f32.bf16.bf16 "
        "{%0, %1, %2, %3, %4, %5, %6, %7, %8, %9, %10, %11, %12, %13, %14, %15, "
        "%16, %17, %18, %19, %20, %21, %22, %23, %24, %25, %26, %27, %28, %29, %30, %31, "
        "%32, %33, %34, %35, %36, %37, %38, %39, %40, %41, %42, %43, %44, %45, %46, %47, "
        "%48, %49, %50, %51, %52, %53, %54, %55, %56, %57, %58, %59, %60, %61, %62, %63, "
        "%64, %65, %66, %67, %68, %69, %70, %71, %72, %73, %74, %75, %76, %77, %78, %79, "
        "%80, %81, %82, %83, %84, %85, %86, %87, %88, %89, %90, %91, %92, %93, %94, %95}, "
        "{%96, %97, %98, %99}, %100, p, 1, 1, 1;\n}\n"
        : "+f"(d[0]), "+f"(d[1]), "+f"(d[2]), "+f"(d[3]), "+f"(d[4]), "+f"(d[5]), "+f"(d[6]), "+f"(d[7]),
          "+f"(d[8]), "+f"(d[9]), "+f"(d[10]), "+f"(d[11]), "+f"(d[12]), "+f"(d[13]), "+f"(d[14]), "+f"(d[15]),
          "+f"(d[16]), "+f"(d[17]), "+f"(d[18]), "+f"(d[19]), "+f"(d[20]), "+f"(d[21]), "+f"(d[22]), "+f"(d[23]),
          "+f"(d[24]), "+f"(d[25]), "+f"(d[26]), "+f"(d[27]), "+f"(d[28]), "+f"(d[29]), "+f"(d[30]), "+f"(d[31]),
          "+f"(d[32]), "+f"(d[33]), "+f"(d[34]), "+f"(d[35]), "+f"(d[36]), "+f"(d[37]), "+f"(d[38]), "+f"(d[39]),
          "+f"(d[40]), "+f"(d[41]), "+f"(d[42]), "+f"(d[43]), "+f"(d[44]), "+f"(d[45]), "+f"(d[46]), "+f"(d[47]),
          "+f"(d[48]), "+f"(d[49]), "+f"(d[50]), "+f"(d[51]), "+f"(d[52]), "+f"(d[53]), "+f"(d[54]), "+f"(d[55]),
          "+f"(d[56]), "+f"(d[57]), "+f"(d[58]), "+f"(d[59]), "+f"(d[60]), "+f"(d[61]), "+f"(d[62]), "+f"(d[63]),
          "+f"(d[64]), "+f"(d[65]), "+f"(d[66]), "+f"(d[67]), "+f"(d[68]), "+f"(d[69]), "+f"(d[70]), "+f"(d[71]),
          "+f"(d[72]), "+f"(d[73]), "+f"(d[74]), "+f"(d[75]), "+f"(d[76]), "+f"(d[77]), "+f"(d[78]), "+f"(d[79]),
          "+f"(d[80]), "+f"(d[81]), "+f"(d[82]), "+f"(d[83]), "+f"(d[84]), "+f"(d[85]), "+f"(d[86]), "+f"(d[87]),
          "+f"(d[88]), "+f"(d[89]), "+f"(d[90]), "+f"(d[91]), "+f"(d[92]), "+f"(d[93]), "+f"(d[94]), "+f"(d[95])
        : "r"(a0), "r"(a1), "r"(a2), "r"(a3), "l"(db), "r"(scale_d));
}
__device__ __forceinline__ void wgmma_rs_n48_hi(float (&d)[120], uint32_t a0, uint32_t a1, uint32_t a2, uint32_t a3, uint64_t db, int scale_d) {
    asm volatile("{\n.reg .pred p;\nsetp.ne.b32 p, %29, 0;\n"
        "wgmma.mma_async.sync.aligned.m64n48k16.f32.bf16.bf16 "
        "{%0, %1, %2, %3, %4, %5, %6, %7, %8, %9, %10, %11, %12, %13, %14, %15, "
        "%16, %17, %18, %19, %20, %21, %22, %23}, "
        "{%24, %25, %26, %27}, %28, p, 1, 1, 1;\n}\n"
        : "+f"(d[96]), "+f"(d[97]), "+f"(d[98]), "+f"(d[99]), "+f"(d[100]), "+f"(d[101]), "+f"(d[102]), "+f"(d[103]),
          "+f"(d[104]), "+f"(d[105]), "+f"(d[106]), "+f"(d[107]), "+f"(d[108]), "+f"(d[109]), "+f"(d[110]), "+f"(d[111]),
          "+f"(d[112]), "+f"(d[113]), "+f"(d[114]), "+f"(d[115]), "+f"(d[116]), "+f"(d[117]), "+f"(d[118]), "+f"(d[119])
        : "r"(a0), "r"(a1), "r"(a2), "r"(a3), "l"(db), "r"(scale_d));
}
__device__ __forceinline__ void wgmma_n8(float (&d)[4], uint64_t da, uint64_t db, int scale_d) {
    asm volatile("{\n.reg .pred p;\nsetp.ne.b32 p, %6, 0;\n"
                 "wgmma.mma_async.sync.aligned.m64n8k16.f32.bf16.bf16 {%0, %1, %2, %3}, %4, %5, p, 1, 1, 1, 0;\n}\n"
                 : "+f"(d[0]), "+f"(d[1]), "+f"(d[2]), "+f"(d[3]) : "l"(da), "l"(db), "r"(scale_d));
}
__device__ __forceinline__ constexpr int jt_of(int sec, int c, bool odd) {
    return odd ? (c >= 2 ? sec * 8 + c - 2 : 24 + sec * 2 + c) : (c < 8 ? sec * 8 + c : 24 + sec * 2 + (c - 8));
}
#define BOTH(...) if (hg & ODDX) { constexpr bool odd = true; __VA_ARGS__ } else { constexpr bool odd = false; __VA_ARGS__ }

__device__ __forceinline__ bool elect() {
    uint32_t r;
    asm volatile("{\n.reg .pred p;\nelect.sync _|p, 0xffffffff;\nselp.u32 %0, 1, 0, p;\n}" : "=r"(r));
    return r != 0;
}
__device__ __forceinline__ uint32_t clock32() { uint32_t r; asm volatile("mov.u32 %0, %%clock;" : "=r"(r)); return r; }
#define BLOCK_SPLIT(v) asm volatile("{\n.reg .pred p;\nLAB_SPLIT:\nsetp.eq.u32 p, %0, 0;\n@p nanosleep.u32 1;\n@p bra LAB_SPLIT;\n}" :: "r"(v) : "memory")
__device__ __forceinline__ bool any(bool v) { return __any_sync(0xffffffffu, v); }
__device__ __forceinline__ bool retry(unsigned& spins) { __nanosleep(100); return ++spins < SPIN; }
__device__ __forceinline__ uint32_t opaque_tid() { uint32_t r; asm volatile("mov.u32 %0, %%tid.x;" : "=r"(r)); return r; }

template <bool BY_SM>
__global__ void __cluster_dims__(2, 1, 1) __launch_bounds__(NTHREADS, 1)
fused_kernel(const __grid_constant__ Params P) {
    extern __shared__ __align__(1024) uint8_t smem[];
    const uint32_t sb = (uint32_t)__cvta_generic_to_shared(smem);
    const uint32_t warp = __shfl_sync(0xffffffffu, threadIdx.x >> 5, 0);
    const uint32_t rank = blockIdx.x & 1;
    constexpr uint32_t sbd = 1024 >> 4;
    const uint32_t t0 = clock32();
    if (warp >= 8 && elect()) {
        const uint32_t bb = sb + B_Z - 256 + (warp ^ 1) * 32;
        const int cnt = ((0xF00F7027u >> (4 * (warp - 8))) & 15) + 1;
        mbar_init(bb, cnt); mbar_init(bb + 8, cnt); mbar_init(bb + 16, cnt); mbar_init(bb + 24, cnt);
        if (warp == 10) { mbar_expect_tx(sb + B_H, 1024); mbar_expect_tx(sb + B_GU, 40960); }
        if (warp == 13) mbar_expect_tx(sb + B_FULL + 16, ST);
        asm volatile("fence.mbarrier_init.release.cluster;" ::: "memory");
    }
    __syncwarp();
    cluster_arrive();
    if (warp < 3 && elect()) asm volatile("prefetch.tensormap [%0];" :: "l"(&P.tm[warp]) : "memory");
    if (warp - 3 < 2 && blockIdx.x < 128 && elect()) l2_prefetch(P.w + ((warp - 3) * 5 * 245760 + blockIdx.x * 1920), 1920);
    if ((sb & 0xFFFFFF) != 1024) __trap();
    uint32_t gpc = blockIdx.x >> 4, pos = (blockIdx.x >> 1) & 7;
    if (BY_SM) {
        uint32_t tpc;
        asm("mov.u32 %0, %%smid;" : "=r"(tpc));
        tpc >>= 1;
        if (tpc - 60 < 2) {
            __nanosleep(2000);
            return;
        }
        const uint32_t q = ((tpc - 32) * 37) >> 8;
        gpc = tpc < 32 ? tpc & 7 : (tpc < 60 ? tpc - 31 - 7 * q : 0);
        pos = tpc < 32 ? tpc >> 3 : (tpc < 60 ? 4 + q : tpc - 58);
    }
    const uint32_t hg = (HGMAP >> (4 * pos)) & 7, rb = gpc * 2 + rank, fp = 8 * pos + gpc - 10;
    const uint32_t b = rb * 8 + hg;
    const uint32_t k0 = (((hg >> 2) ^ (rb >> 1)) & 1) * 320;

    if (warp == 13 && elect()) tma(sb + 2 * ST, &P.tm[T_X], sb + B_FULL + 16, k0, rb * 64);
    if (warp == 12) {
        cluster_wait();
        if (elect()) {
            tma_mc(sb + 2 * ST + ST_BM + rank * 12288, &P.tm[T_W], sb + B_FULL + 16, hg * 80 + (hg & ODDX) * 16, k0 + rank * 32);
            tma_mc(sb + 2 * ST + ST_BR + rank * 3072, &P.tm[T_WR], sb + B_FULL + 16, hg * 80 + 64 - (hg & ODDX) * 64, k0 + rank * 32);
        }
        __syncwarp();
    }

    if (warp < 8) {
        asm volatile("setmaxnreg.inc.sync.aligned.u32 208;");
        const uint32_t lane = opaque_tid() & 31, g = lane >> 2, t = lane & 3;
        const uint32_t p = warp >> 2, w = warp & 3;
        const uint32_t empty_cl = mapa(sb + B_EMPTY, lane & 1);
        uint8_t* const orow = P.scr + (rb * (8 * XB) + warp * 2560 + lane * 16);
        const uint32_t ta = sb + warp * 2560 + (lane & 15) * 160 + (lane >> 4) * 16;
        uint32_t A[5][20];
        uint32_t xr[5][4], gf[5][4];
        TRD(r12); TRD(r32); TRD(r34); TRD(r22); TRD(r44);
        uint32_t par;
        uint8_t* const halo = orow + (hg * XB + (8 + p - warp) * 2560);
        uint8_t* const flag = P.scr + (G_FLAG + b * XB + w * 8 + p * 4);
        cluster_wait();
        {
            float acc[120];
            bool ok, prep;
            float2 s0, s1;
            uint32_t xa[5], cap[2] = {0u, 0u};
#pragma unroll
            for (uint32_t j = 0; j < 5; j++) {
                const uint32_t cg = 5 * hg + (j < 4 ? j + (hg & 1) : (~hg & 1) * 4);
                xa[j] = (sb + (warp * 16 + (lane & 15)) * 128 + (((lane >> 4) ^ (lane & 7)) << 4)) ^ ((cg & 3) << 5);
                const uint32_t i = cg >> 2, late = (i >= 5) ^ (k0 != 0), bit = 1u << (5 * (i >= 5 ? i - 5 : i) + j);
                cap[0] |= late ? 0u : bit; cap[1] |= late ? bit : 0u;
            }
            uint32_t sta = sb + M_ST + (warp * 16 + g) * 8;
            asm volatile("" : "+r"(sta), "+r"(cap[0]), "+r"(cap[1]), "+r"(xa[0]), "+r"(xa[1]), "+r"(xa[2]), "+r"(xa[3]), "+r"(xa[4]));
            mbar_wait(sb + B_FULL + 16, 0);
#pragma unroll
            for (uint32_t kb = 2; kb < 12; kb++) {
                const uint32_t s = kb & 3;
                const bool hold = kb == 12 - LEAD && p;
                if (hold) {
                    wgmma_wait<0>();
                    if (lane < 2) mbar_arrive_cl(empty_cl + 8 * ((11 - LEAD) & 3));
                    bar_sync(1, 256);
                }
                wgmma_fence();
                const uint32_t st = sbd + s * (ST >> 4);
#pragma unroll
                for (int ks = 0; ks < 4; ks++) {
                    const uint64_t da = mk(st + p * 512 + ks * 2 + 0x10000, HI128);
                    wgmma_n48_hi(acc, da, mk(st + (ST_BR >> 4) + (ks >> 1) * 192 + (ks & 1) * 32 + (64 << 16), HI32), ks || kb > 2);
                    wgmma_n192_lo(acc, da, mk(st + (ST_BM >> 4) + (ks >> 1) * 768 + (ks & 1) * 128 + (256 << 16), HI128), ks || kb > 2);
                    if (ks == 0) {
                        wgmma_commit();
                        wgmma_wait<1>();
                        if (!hold && kb > 2 && lane < 2) mbar_arrive_cl(empty_cl + 8 * ((kb - 1) & 3));
                    }
                    if (ks == 1) {
#pragma unroll
                        for (uint32_t j = 0; j < 5; j++)
                            if ((cap[kb >= 7] >> (5 * ((kb - 2) % 5) + j)) & 1) ldsm_x4(xr[j], xa[j] + s * ST);
                        if (w == 3 && kb < 7) stg128(halo + (kb - 2) * 512, 0u, 0u, 0u, 0u);
                        if (lane == 0 && kb == 2) stg32(flag, 0u);
                        if (kb < 11) ok = mbar_try(sb + B_FULL + 8 * ((kb + 1) & 3), ((kb - 1) >> 2) & 1);
                        if (kb == 10) prep = mbar_try(sb + B_PREP, 0);
                        if (kb == 11 && prep) {
                            s0 = lds64f(sta); s1 = lds64f(sta + 64);
                            par = lds32(sb + M_SEL + 8);
                        }
                    }
                }
                wgmma_commit();
                if (kb < 11 && !ok) mbar_wait(sb + B_FULL + 8 * ((kb + 1) & 3), ((kb - 1) >> 2) & 1);
            }
            if (!prep) {
                mbar_wait(sb + B_PREP, 0);
                s0 = lds64f(sta); s1 = lds64f(sta + 64);
                par = lds32(sb + M_SEL + 8);
            }
            {
                const uint32_t a0 = t ? 0u : __byte_perm(U(-s0.y), 0, 0x3232), a1 = t ? 0u : __byte_perm(U(-s1.y), 0, 0x3232);
                wgmma_fence();
                wgmma_rs_n48_hi(acc, a0, a1, 0u, 0u, mk(sbd + (M_CS >> 4) + 48, 2), 1);
                wgmma_rs_n192_lo(acc, a0, a1, 0u, 0u, mk(sbd + (M_CS >> 4), 2), 1);
                wgmma_commit();
            }
            if (!p) bar_arrive(1, 256);
            wgmma_wait<0>();
#pragma unroll
            for (int i = 0; i < 120; i++) asm volatile("" : "+f"(acc[i]) :: "memory");
            if (lane < 2) mbar_arrive_cl(empty_cl + 24);
            TR(r12);
            uint32_t Q[10], Ql[10], KX[10], VX[10], Y[20];
#define KI(c) ((c) == 2 ? 8 : (c) == 7 ? 9 : (c) - ((c) > 2) - ((c) > 7))
#define KY(c) Y[KI(c)]
#define VY(c) Y[10 + (c)]
            uint32_t Z[20];
            const bool start = w == 0 && rb == 0, remote = w == 0 && rb != 0;
            const uint32_t slot = sb + OFF_X + warp * 2560 + lane * 16;
            {
                BOTH(_Pragma("unroll") for (int c = 0; c < 10; c++) {
                    const int jk = jt_of(1, c, odd), jv = jt_of(2, c, odd);
                    VY(c) = movm(pack_bf16(acc[4 * jv + 2] * s1.x, acc[4 * jv + 3] * s1.x));
                    KY(c) = pack_bf16(acc[4 * jk + 2] * s1.x, acc[4 * jk + 3] * s1.x);
                    asm volatile("" : "+r"(KY(c)), "+r"(VY(c)));
                })
                if (w == 3) {
#pragma unroll
                    for (int j = 0; j < 5; j++) {
                        Y[4 * j] = (Y[4 * j] & ~0x10001u) | par;
                        stg128(halo + j * 512, Y[4 * j], Y[4 * j + 1], Y[4 * j + 2], Y[4 * j + 3]);
                    }
                } else {
                    mbar_wait(sb + B_EMPTY, 1);
#pragma unroll
                    for (int j = 0; j < 5; j++) sts128(slot + 2560 + j * 512, Y[4 * j], Y[4 * j + 1], Y[4 * j + 2], Y[4 * j + 3]);
                }
                BOTH(_Pragma("unroll") for (int c = 0; c < 10; c++) {
                    const int jk = jt_of(1, c, odd), jv = jt_of(2, c, odd);
                    KX[c] = pack_bf16(acc[4 * jk] * s0.x, acc[4 * jk + 1] * s0.x);
                    VX[c] = movm(pack_bf16(acc[4 * jv] * s0.x, acc[4 * jv + 1] * s0.x));
                    asm volatile("" : "+r"(KX[c]), "+r"(VX[c]));
                })
                BLOCK_SPLIT(par);
                bar_sync(2 + p, 128);
                if (remote) {
#pragma unroll
                    for (int j = 0; j < 5; j++) ldg128(halo - 8 * XB + j * 512, Z[4 * j], Z[4 * j + 1], Z[4 * j + 2], Z[4 * j + 3]);
                } else {
#pragma unroll
                    for (int j = 0; j < 5; j++) {
                        const uint4 v = lds128(slot + (w ? 0 : 2560) + j * 512);
                        Z[4 * j] = v.x; Z[4 * j + 1] = v.y; Z[4 * j + 2] = v.z; Z[4 * j + 3] = v.w;
                    }
                }
                BOTH(_Pragma("unroll") for (int c = 0; c < 10; c++) {
                    const int jq = jt_of(0, c, odd);
                    Ql[c] = pack_bf16(acc[4 * jq], acc[4 * jq + 1]);
                    Q[c] = pack_bf16(acc[4 * jq + 2], acc[4 * jq + 3]);
                    asm volatile("" : "+r"(Ql[c]), "+r"(Q[c]));
                })
            }
            auto scores = [&](float (&l)[4], const uint32_t (&q)[10], const uint32_t (&z)[20], const int c0, const uint32_t mx, const float nz) {
                const uint32_t qa = t < 2 ? q[c0 + 2] : 0u, qb = t < 2 ? 0u : q[c0 + 2];
                float xa[4] = {0.f, 0.f, 0.f, 0.f}, za[4] = {nz, nz, nz, nz}, xb[4], zb[4];
                mma1688(xa, qa, qb, KX[c0 + 2]);
                mma1688(za, qa, qb, z[KI(c0 + 2)]);
#pragma unroll
                for (int e = 0; e < 4; e++) { xb[e] = xa[e]; zb[e] = za[e]; }
                mma16816(xa, q[c0], q[c0 + 3], q[c0 + 1], q[c0 + 4], KX[c0], KX[c0 + 1]);
                mma16816(za, q[c0], q[c0 + 3], q[c0 + 1], q[c0 + 4], z[KI(c0)], z[KI(c0 + 1)]);
                mma16816(xb, q[c0], q[c0 + 3], q[c0 + 1], q[c0 + 4], KX[c0 + 3], KX[c0 + 4]);
                mma16816(zb, q[c0], q[c0 + 3], q[c0 + 1], q[c0 + 4], z[KI(c0 + 3)], z[KI(c0 + 4)]);
                const bool h0 = mx & 1u, h1 = (int)mx < 0;
                l[0] = h0 ? xa[0] : za[0]; l[1] = h1 ? xa[1] : za[1];
                l[2] = h0 ? xb[2] : zb[2]; l[3] = h1 ? xb[3] : zb[3];
                asm volatile("" : "+f"(l[0]), "+f"(l[1]), "+f"(l[2]), "+f"(l[3]));
            };
            auto soft = [&](uint32_t (&pr)[2], const float (&l)[4], const float sq) {
                float m0 = fmaxf(l[0], l[1]), m1 = fmaxf(l[2], l[3]);
                m0 = fmaxf(m0, shx(m0, 1)); m1 = fmaxf(m1, shx(m1, 1));
                m0 = fmaxf(m0, shx(m0, 2)) * -sq; m1 = fmaxf(m1, shx(m1, 2)) * -sq;
                pr[0] = pack_bf16(ex2(fmaf(l[0], sq, m0)), ex2(fmaf(l[1], sq, m0)));
                pr[1] = pack_bf16(ex2(fmaf(l[2], sq, m1)), ex2(fmaf(l[3], sq, m1)));
                asm volatile("" : "+r"(pr[0]), "+r"(pr[1]));
            };
            auto values = [&](const uint32_t (&pr)[2], const uint32_t (&z)[20], const int c0, const uint32_t mx, const int h) {
                float dn[4] = {0.f, 0.f, 0.f, 0.f};
                mma1688(dn, pr[0], pr[1], 0x3F803F80u);
                const float i0 = rcp(dn[0]), i1 = rcp(dn[2]), i2 = t < 2 ? i0 : i1;
#pragma unroll
                for (int c = 0; c < 5; c++) {
                    float oc[4] = {0.f, 0.f, 0.f, 0.f};
                    mma16816(oc, pr[0] & mx, pr[1] & mx, pr[0] & ~mx, pr[1] & ~mx, VX[c0 + c], z[10 + c0 + c]);
                    const bool first = c < 2 || (c == 2 && t < 2);
                    const float iv = c < 2 ? i0 : (c > 2 ? i1 : i2);
                    A[0][2 * (c0 + c) + h] = pack_bf16((first ? oc[0] : oc[2]) * iv, (first ? oc[1] : oc[3]) * iv);
                    asm volatile("" : "+r"(A[0][2 * (c0 + c) + h]));
                }
            };
            const uint32_t mo = (2 * t > g ? 0xFFFFu : 0u) | (2 * t + 1 > g ? 0xFFFF0000u : 0u);
            constexpr float SC = 0.22360679774997896f * LOG2E;
            {
                float l[4][4];
                uint32_t pr[4][2];
                unsigned spins = 0;
#pragma unroll 1
                while (remote && any((Z[0] & Z[4] & Z[8] & Z[12] & Z[16] & par) == 0u) && ++spins < SPIN) {
#pragma unroll
                    for (int j = 0; j < 5; j++) ldg128(halo - 8 * XB + j * 512, Z[4 * j], Z[4 * j + 1], Z[4 * j + 2], Z[4 * j + 3]);
                }
                TR(r32);
                const float nz = start ? -INFINITY : 0.f;
                scores(l[0], Q, Y, 0, mo, 0.f);
                scores(l[1], Q, Y, 5, mo, 0.f);
                scores(l[2], Ql, Z, 0, ~mo, nz);
                scores(l[3], Ql, Z, 5, ~mo, nz);
                soft(pr[0], l[0], s1.x * SC);
                soft(pr[1], l[1], s1.x * SC);
                soft(pr[2], l[2], s0.x * SC);
                soft(pr[3], l[3], s0.x * SC);
                values(pr[0], Y, 0, mo, 1);
                values(pr[1], Y, 5, mo, 1);
                values(pr[2], Z, 0, ~mo, 0);
                values(pr[3], Z, 5, ~mo, 0);
            }
#pragma unroll
            for (int j = 0; j < 5; j++) {
                A[0][4 * j] = (A[0][4 * j] & ~0x10001u) | par;
                stg128(orow + hg * XB + j * 512, A[0][4 * j], A[0][4 * j + 1], A[0][4 * j + 2], A[0][4 * j + 3]);
            }
            if (lane == 0) stg32(flag, par);
            TR(r34);
            if (p) bar_arrive(8, 384);
            BLOCK_SPLIT(par);
            {
                const float r0 = 0.5f * s0.x, r1 = 0.5f * s1.x, n0 = -r0 * s0.y, n1 = -r1 * s1.y;
#pragma unroll
                for (int j = 0; j < 5; j++) {
#pragma unroll
                    for (int q = 0; q < 4; q++) {
                        const float v0 = fmaf(bflo(xr[j][q]), q & 1 ? r1 : r0, q & 1 ? n1 : n0), v1 = fmaf(bfhi(xr[j][q]), q & 1 ? r1 : r0, q & 1 ? n1 : n0);
                        gf[j][q] = pack_bf16(fmaf(v0, tanh_a(v0), v0), fmaf(v1, tanh_a(v1), v1));
                        asm volatile("" : "+r"(gf[j][q]));
                    }
                }
            }
        }
        {
            float acc2[40];
            unsigned spins = 0;
            bool again, first = true;
            const uint8_t* src[7];
#pragma unroll
            for (uint32_t i = 0; i < 7; i++) { src[i] = orow + (i >= hg ? XB : 0u); asm volatile("" : "+l"(src[i])); }
            mbar_wait(sb + B_SEL, 0);
            const float2 sel = lds64f(sb + M_SEL);
            uint32_t routed = (U(sel.x) >> 4) == warp || (U(sel.y) >> 4) == warp;
            asm volatile("" : "+r"(routed));
            BLOCK_SPLIT(par);
            if (p) bar_sync(9, 288); else bar_sync(5, 160);
#pragma unroll 1
            do {
#pragma unroll
                for (uint32_t i = 1; i < 5; i++)
#pragma unroll
                    for (int j = 0; j < 5; j++)
                        ldg128(src[i - 1] + (i - 1) * XB + j * 512, A[i][4 * j], A[i][4 * j + 1], A[i][4 * j + 2], A[i][4 * j + 3]);
                if (!p && first) bar_sync(8, 384);
                uint32_t mn = par;
#pragma unroll
                for (int i = 0; i < 8; i++) {
                    const uint32_t (&a)[20] = A[i % 5];
                    if (i == 3 && !p && first) bar_sync(6, 160);
                    wgmma_fence();
#pragma unroll
                    for (int j = 0; j < 5; j++) {
                        wgmma_rs_n80(acc2, a[4 * j], a[4 * j + 1], a[4 * j + 2], a[4 * j + 3],
                                     mk(sbd + ((OFF_WO + i * WO_SLOT) >> 4) + j * 64 + (320 << 16), HI64), i || j);
                        if (i == 7 && j == CHKJ) {
#pragma unroll
                            for (int q = 0; q < 5; q++) mn &= A[q][0] & A[q][4] & A[q][8] & A[q][12] & A[q][16];
                            again = bar_or(2 + p, 128, mn == 0u && ++spins < SPIN);
                        }
                    }
                    if (i < 4 || i == 7) wgmma_commit();
                    if (i == SERAT && !p && first) bar_arrive(9, 288);
                    if (i == 0) TR(r22);
                    if (i >= 1 && i < 4) {
                        uint32_t (&n)[20] = A[i - 1];
                        if (i > 1) mn &= n[0] & n[4] & n[8] & n[12] & n[16];
                        const uint8_t* q = src[i + 3] + (i > 1 ? mn & 256u : 0u);
                        wgmma_wait<1>();
                        bar_arrive(10, 32);
#pragma unroll
                        for (int j = 0; j < 5; j++) ldg128(q + (i + 3) * XB + j * 512, n[4 * j], n[4 * j + 1], n[4 * j + 2], n[4 * j + 3]);
                        bar_arrive(10, 32);
                    }
                }
                first = false;
                if (again) {
                    wgmma_wait<0>();
#pragma unroll
                    for (int j = 0; j < 5; j++)
                        ldg128(orow + hg * XB + j * 512, A[0][4 * j], A[0][4 * j + 1], A[0][4 * j + 2], A[0][4 * j + 3]);
                }
            } while (again);
            const uint32_t o0 = (hg & 1) * 32, o4 = (~hg & 1) * 128;
            if (routed) {
                const float2 sel = lds64f(sb + M_SEL);
                mbar_wait(sb + B_UPD, 0);
#pragma unroll
                for (uint32_t h = 0; h < 2; h++) {
                    const uint32_t row = warp * 16 + g + 8 * h, ga = sb + M_UPD + (row == U(sel.x) ? 0 : 160) + t * 4;
                    if (row == U(sel.x) || row == U(sel.y)) {
#pragma unroll
                        for (int c = 0; c < 5; c++) { gf[c][h] = lds32(ga + (c < 4 ? o0 + c * 32 : o4)); gf[c][h + 2] = lds32(ga + (c < 4 ? o0 + c * 32 : o4) + 16); }
                    }
                }
                __syncwarp();
            }
            wgmma_wait<0>();
#pragma unroll
            for (int i = 0; i < 40; i++) asm volatile("" : "+f"(acc2[i]) :: "memory");
            TR(r44);
#pragma unroll
            for (int c = 0; c < 5; c++) {
#pragma unroll
                for (int q = 0; q < 4; q++)
                    asm("fma.rn.bf16x2 %0, %1, %2, %0;" : "+r"(xr[c][q]) : "r"(pack_bf16(acc2[8 * c + 2 * q], acc2[8 * c + 2 * q + 1])), "r"(gf[c][q]));
                stsm_x4(ta + (c < 4 ? o0 + c * 32 : o4) + OFF_X, xr[c]);
            }
            fence_proxy_async_smem();
            __syncwarp();
            if (lane == 0) {
                tma_st(&P.tm[T_OUT], sb + OFF_X + warp * 2560, hg * 80, rb * 64 + 16 * w, p);
                asm volatile("cp.async.bulk.wait_group.read 0;" ::: "memory");
            }
        }
        TS(46);
        TRW(r12, 12); TRW(r32, 32); TRW(r34, 34); TRW(r22, 22); TRW(r44, 44);
    } else if (warp >= 12) {
        asm volatile("setmaxnreg.dec.sync.aligned.u32 24;");
        if (warp == 12) {
            uint32_t slot = t0 + PACE0;
            if (elect()) {
#pragma unroll 1
                for (uint32_t kb = 1; kb < 10; kb++) {
                    const uint32_t s = (kb + 2) & 3;
                    const uint32_t st = sb + s * ST, fb = sb + B_FULL + 8 * s;
                    const uint32_t kc = kb * 64 + (kb < 5 ? k0 : -k0);
                    if (kb >= 4) {
                        mbar_wait(fb + 32, kb >> 3);
                        if (kb < 9) mbar_wait(sb + B_AX - 32 + 8 * kb, 0);
                    }
                    {
                        slot += PACE1;
#pragma unroll 1
                        while ((int)(clock32() - slot) < 0) { }
                        mbar_expect_tx(fb, ST);
                        tma(st, &P.tm[T_X], fb, kc, rb * 64);
                    }
                    tma_mc(st + ST_BM + rank * 12288, &P.tm[T_W], fb, hg * 80 + (hg & ODDX) * 16, kc + rank * 32);
                    tma_mc(st + ST_BR + rank * 3072, &P.tm[T_WR], fb, hg * 80 + 64 - (hg & ODDX) * 64, kc + rank * 32);
                }
                mbar_wait(sb + B_EMPTY, 1);
                mbar_expect_tx(sb + B_X, 20480);
                tma(sb + OFF_DN, &P.tm[T_D], sb + B_X, 0, 32 * fp, 5 * rank);
                uint32_t wb = sb + B_WO - 8;
#pragma unroll 1
                for (uint32_t i = 0; i < 8; i++) {
                    if ((0x49 >> i) & 1) {
                        wb += 8;
                        mbar_wait(wb - (B_WO - B_EMPTY - 8), i == 0);
                        mbar_expect_tx(wb, i < 6 ? 3 * 12800 : 2 * 12800);
                    }
                    if (WOP) {
#pragma unroll 1
                        while ((int)(clock32() - slot) < 0) { }
                        slot = clock32() + WOP;
                    }
                    const uint32_t d = sb + OFF_WO + i * WO_SLOT;
                    const uint32_t kr = 80 * (i ? i - (i <= hg) : hg);
                    tma_mc(d + rank * 5120, &P.tm[T_WO], wb, hg * 80 + (hg & 1) * 16 + rank * 32, kr);
                    tma_mc(d + 10240 + rank * 2560, &P.tm[T_WOR], wb, hg * 80 + (~hg & 1) * 64, kr + rank * 40);
                }
            }
        } else if (warp == 13) {
            if (elect()) {
#pragma unroll 1
                for (uint32_t i = 0; i < 5 - PXJ; i++) {
#pragma unroll 1
                    while (clock32() - t0 < PX0 + i * PX1) __nanosleep(20);
                    l2_prefetch(P.w + ((i + PXJ) * 245760 + b * 1920), 1920);
                    l2_prefetch(P.w + ((i + PXJ + 5) * 245760 + b * 1920), 1920);
                }
#pragma unroll 1
                for (uint32_t i = 0; i < 14; i++) {
#pragma unroll 1
                    while (clock32() - t0 < GU0 + i * GU1) __nanosleep(20);
                    if (i < 10) l2_prefetch(P.wd + (i * 128 + b) * 1728, 1728);
                    else l2_prefetch(P.wo + ((i - 10) * 128 + b) * 1600, 1600);
                }
            }
        } else if (warp == 15) {
            const uint32_t lane = opaque_tid() & 31;
            const uint8_t* fl = P.scr + (G_FLAG + (rb * 8 + (lane & 7)) * XB + (lane >> 3) * 8);
            cluster_wait();
            mbar_wait(sb + B_PREP, 0);
            const uint32_t par = lds32(sb + M_SEL + 8);
            mbar_wait(sb + B_WO, 0);
            mbar_wait(sb + B_EMPTY + 24, 0);
            __nanosleep(WSL);
            unsigned spins = 0;
            uint2 f;
#pragma unroll 1
            do f = ldg64(fl); while (any(f.x != par) && ++spins < SPIN);
            bar_arrive(5, 160);
            TS(24);
            mbar_wait(sb + B_WO + 8, 0); mbar_wait(sb + B_WO + 16, 0);
            bar_arrive(6, 160);
#pragma unroll 1
            while (any(f.y != par) && ++spins < SPIN) f.y = ldg32(fl + 4);
            bar_arrive(9, 288);
            TS(25);
        } else {
            uint32_t slot = t0 + GT0;
            cluster_wait();
            if (elect()) {
#pragma unroll 1
                for (uint32_t i = 0; i < 20; i++) {
                    slot += GT1;
#pragma unroll 1
                    while ((int)(clock32() - slot) < 0) __nanosleep(20);
                    tma(sb + OFF_GU + i * 2048, &P.tm[T_GU], sb + B_GU, 32 * fp, rank * 320 + i * 16);
                }
            }
        }
    } else {
        asm volatile("setmaxnreg.dec.sync.aligned.u32 72;");
        const uint32_t at = opaque_tid() - 256, lane = at & 31, g = lane >> 2, t = lane & 3, c7 = lane & 7, aw = warp - 8;
        uint8_t* const yz = P.scr + (G_Y + b * 512 + at * 4);
        stg32(yz, 0u);
        __nanosleep(AUXS);
        const uint32_t epoch = ldg32(P.scr + G_EPOCH) + 1 + ldg32(yz), tag = (epoch & 15u) | 16u;
        const uint32_t empty_cl = mapa(sb + B_EMPTY, lane & 1);
        unsigned spins = 0;
        TRD(r51); TRD(r30); TRD(r52); TRD(r53); TRD(r54); TRD(r55); TRD(r20); TRD(r22);
        {
            const uint2 wv = __ldg(reinterpret_cast<const uint2*>(P.w_r + k0 * 2 + min(at, 79u) * 8));
            if (at < 80) sts64(sb + M_UPD + at * 8, wv.x, wv.y);
        }
        uint8_t* const stw = P.scr + (b * XB + G_ST + (lane & 4) * 64 + (at >> 3) * 16);
        uint8_t* const csw = P.scr + (b * XB + G_CS + at);
        uint8_t* const tpw = P.scr + (G_TOP + (hg >> 2) * XB + rb * 64 + aw * 16);
        const bool tpub = lane == 0 && (hg & 3) == TPUB;
        cluster_wait();
        bar_sync(4, 128);
        mbar_wait(sb + B_FULL + 16, 0);
        if (t == 0) { stg128(stw, 0u, 0u, 0u, 0u); stg32(csw, 0u); }
        if (tpub) stg128(tpw, 0u, 0u, 0u, 0u);

        uint32_t k1, sv;
        {
            const uint32_t xoff = (32 * (hg & 3) + (at >> 3)) * 128 + ((c7 ^ ((at >> 3) & 7)) << 4);
            const uint32_t jt = (rb >> 2) * 8 + rank * 4 + aw;
            const uint32_t coff = jt < 24 ? ST_BM + (jt >> 3) * 4096 + lane * 128 + (((jt ^ lane) & 7) << 4)
                                          : ST_BR + ((jt >> 1) & 3) * 1024 + lane * 32 + (((jt ^ g) & 1) << 4);
            float q[8], c8[8];
#pragma unroll
            for (int e = 0; e < 8; e++) q[e] = c8[e] = 0.f;
#pragma unroll 1
            for (uint32_t kb = 2; kb < 7; kb++) {
                const uint32_t st = sb + (kb & 3) * ST;
                const uint4 wv = lds128(sb + M_UPD - 256 + kb * 128 + c7 * 16);
                mbar_wait(sb + B_FULL + 8 * (kb & 3), kb == 6);
                const uint4 v = lds128(st + xoff), vn = lds128(st + xoff + 2048);
                const uint4 cv = lds128(st + coff), cn = lds128(st + coff + (jt < 24 ? 12288 : 3072));
                if (lane < 2) mbar_arrive_cl(empty_cl + (B_AX - B_EMPTY - 16) + 8 * kb + (cn.x & 0));
                const uint32_t u[4] = {v.x, v.y, v.z, v.w}, un[4] = {vn.x, vn.y, vn.z, vn.w}, ww[4] = {wv.x, wv.y, wv.z, wv.w};
                const uint32_t cc[4] = {cv.x, cv.y, cv.z, cv.w}, cd[4] = {cn.x, cn.y, cn.z, cn.w};
#pragma unroll
                for (int e = 0; e < 4; e++) {
                    const float a0 = bflo(u[e]), a1 = bfhi(u[e]), b0 = bflo(un[e]), b1 = bfhi(un[e]), w0 = bflo(ww[e]), w1 = bfhi(ww[e]);
                    q[0] += a0 + a1; q[4] += b0 + b1; q[3] += w0 + w1;
                    q[1] = fmaf(a0, a0, fmaf(a1, a1, q[1])); q[5] = fmaf(b0, b0, fmaf(b1, b1, q[5]));
                    q[2] = fmaf(a0, w0, fmaf(a1, w1, q[2])); q[6] = fmaf(b0, w0, fmaf(b1, w1, q[6]));
                    c8[2 * e] += bflo(cc[e]) + bflo(cd[e]); c8[2 * e + 1] += bfhi(cc[e]) + bfhi(cd[e]);
                }
            }
            TR(r51);
            q[7] = q[3];
#pragma unroll
            for (int e = 0; e < 4; e++) {
                q[e] = ((lane & 4) ? q[e + 4] : q[e]) + shx((lane & 4) ? q[e] : q[e + 4], 4);
                q[e] += shx(q[e], 1); q[e] += shx(q[e], 2);
            }
            const float mh = q[0] * (1.0f / 320);
            if (t == 0) stg128(stw, U(mh), U(fmaf(-mh, q[0], q[1])), U(q[2]), (U(q[3]) & ~31u) | tag);
#define TSTEP(H) { const bool up = (lane & (4 * H)) != 0; _Pragma("unroll") for (int e = 0; e < H; e++) { \
            const float send = up ? c8[e] : c8[e + H]; const float keep = up ? c8[e + H] : c8[e]; \
            c8[e] = keep + shx(send, 4 * H); } }
            TSTEP(4) TSTEP(2) TSTEP(1)
#undef TSTEP
            c8[0] += shx(c8[0], 1); c8[0] += shx(c8[0], 2);
            if (t == 0) stg32(csw, (U(c8[0]) & ~31u) | tag);
            TR(r30);
            const uint8_t* csp = P.scr + (G_CS + (aw * 32 + (lane >> 4) * 8 + hg) * XB + (lane & 15) * 8);
            const uint8_t* stp = P.scr + (G_ST + (rb * 8 + aw) * XB + lane * 16);
            uint32_t ra[4], rc[4];
            uint2 ca, cc;
#pragma unroll 1
            while (clock32() - t0 < EX1T) __nanosleep(20);
#pragma unroll 1
            do {
                ldg128(stp, ra[0], ra[1], ra[2], ra[3]);
                ldg128(stp + 4 * XB, rc[0], rc[1], rc[2], rc[3]);
                ca = ldg64(csp); cc = ldg64(csp + 16 * XB);
            } while (any((ra[3] ^ tag | rc[3] ^ tag) & 31u) && ++spins < SPIN);
            TR(r20);
            const float dm = 0.5f * (F(ra[0]) - F(rc[0])), m = bf16r(F(rc[0]) + dm);
            const float sd = bf16r(sqrt_a(bf16r(bf16r(fmaxf(fmaf(dm, dm, (F(ra[1]) + F(rc[1])) * (1.0f / DM)), 0.f)) + 1e-5f)));
            const float rs = rcp(sd);
            uint32_t w1, w2;
            if ((hg & 3) == TPUB) {
                k1 = pack_bf16(0.f, fmaf(-m, F(ra[3]) + F(rc[3]), F(ra[2]) + F(rc[2])) * rs);
                k1 ^= ((int)k1 >> 31) | 0x80000000u;
                k1 = (k1 & 0xFFFF0000u) | ((2047 - (rb * 128 + 2 * (at & 63) + (at >> 6))) << 5) | tag;
                w1 = redux_max(k1); w2 = redux_max(k1 == w1 ? 0u : k1);
                sv = U(m) | (U(sd) >> 16);
                const uint32_t v1 = redux_max(k1 == w1 ? sv : 0u), v2 = redux_max(k1 == w2 ? sv : 0u);
                if (lane == 0) stg128(tpw, w1, v1, w2, v2);
            }
            sts64(sb + M_ST + at * 8, U(rs), U(m));
            sts32(sb + M_SEL + 8, (tag & 1) ? 1u : 0x10000u);
#pragma unroll 1
            while (any((ca.x ^ tag | ca.y ^ tag | cc.x ^ tag | cc.y ^ tag) & 31u) && ++spins < SPIN) { ca = ldg64(csp); cc = ldg64(csp + 16 * XB); }
            {
                const float c0 = at < 120 ? F(ca.x) + F(cc.x) : 0.f, c1 = at < 120 ? F(ca.y) + F(cc.y) : 0.f;
                const uint32_t hi = pack_bf16(c0, c1);
                sts32(sb + M_CS + (at >> 2) * 32 + t * 4, hi);
                sts32(sb + M_CS + (at >> 2) * 32 + t * 4 + 16, pack_bf16(c0 - bflo(hi), c1 - bfhi(hi)));
                fence_proxy_async_smem();
                __syncwarp();
                if (lane < 2) mbar_arrive(sb + B_PREP);
            }
            TR(r52);
            if (aw == 0) {
                uint32_t ka[4], kb[4];
#pragma unroll 1
                while (clock32() - t0 < EX1T + EX2D) __nanosleep(20);
#pragma unroll 1
                do {
                    const uint8_t* tp = P.scr + (G_TOP + lane * 16);
                    uint32_t kc[4], kd[4];
                    ldg128(tp, ka[0], ka[1], ka[2], ka[3]);
                    ldg128(tp + 512, kb[0], kb[1], kb[2], kb[3]);
                    ldg128(tp + XB, kc[0], kc[1], kc[2], kc[3]);
                    ldg128(tp + XB + 512, kd[0], kd[1], kd[2], kd[3]);
                    const bool ba = (ka[0] ^ tag) & 31u, bb = (kb[0] ^ tag) & 31u;
#pragma unroll
                    for (int e = 0; e < 4; e++) { ka[e] = ba ? kc[e] : ka[e]; kb[e] = bb ? kd[e] : kb[e]; }
                } while (any((ka[0] ^ tag | kb[0] ^ tag) & 31u) && ++spins < SPIN);
                TR(r22);
                if (kb[0] > ka[0]) {
#pragma unroll
                    for (int e = 0; e < 4; e++) { const uint32_t x = ka[e]; ka[e] = kb[e]; kb[e] = x; }
                }
                if (kb[0] > ka[2]) { ka[2] = kb[0]; ka[3] = kb[1]; }
                w1 = redux_max(ka[0]);
                const uint32_t t1 = redux_max(ka[0] == w1 ? ka[1] : 0u);
                if (ka[0] == w1) { ka[0] = ka[2]; ka[1] = ka[3]; }
                w2 = redux_max(ka[0]);
                const uint32_t t3 = redux_max(ka[0] == w2 ? ka[1] : 0u);
                sts128(sb + M_TOP, w1, t1, w2, t3);
            }
            bar_sync(4, 128);
            const float2 tv = lds64f(sb + M_TOP + (lane & 1) * 8);
            k1 = U(tv.x);
            sv = U(tv.y);
        }
        TR(r53);
        const uint32_t tok = ~(k1 >> 5) & 2047;
        const unsigned owns = __ballot_sync(0xffffffffu, (tok >> 7) == rb) & 3u;
        if (at < 2) sts32(sb + M_SEL + at * 4, (tok >> 7) == rb ? (tok & 1) * 64 + ((tok & 127) >> 1) : ~0u);
        if ((at | b) == 0) *reinterpret_cast<uint32_t*>(P.scr + G_EPOCH) = epoch;
        __syncwarp();
        if (at == 0) mbar_arrive(sb + B_SEL);
        if (fp < NFFN / 2) {
            uint4 xv = __ldg(reinterpret_cast<const uint4*>(P.x + (tok * 1280 + rank * 640 + min(at >> 1, 39u) * 16)));
            const uint32_t m2 = __byte_perm(sv, 0, 0x3232);
            asm("sub.rn.bf16x2 %0, %0, %4;\nsub.rn.bf16x2 %1, %1, %4;\nsub.rn.bf16x2 %2, %2, %4;\nsub.rn.bf16x2 %3, %3, %4;"
                : "+r"(xv.x), "+r"(xv.y), "+r"(xv.z), "+r"(xv.w) : "r"(m2));
            mbar_wait(sb + B_X, 0);
            if (at < 80) sts128(sb + OFF_PART + at * 16, xv.x, xv.y, xv.z, xv.w);
            mbar_wait(sb + B_GU, 0);
            mbar_wait(sb + B_EMPTY + 24, 0);
            bar_sync(4, 128);
            if (FFNAT > 1) __nanosleep(FFNAT);
            float c[5][4];
#pragma unroll
            for (int i = 0; i < 5; i++) c[i][0] = c[i][1] = c[i][2] = c[i][3] = 0.f;
            const uint32_t mi = lane >> 3, kr = c7 + (mi >> 1) * 8;
            {
                const uint32_t wa = sb + OFF_GU + (aw >> 1) * 1024 + kr * 64 + ((((aw & 1) * 2 + (mi & 1)) ^ ((kr >> 1) & 3)) << 4);
#pragma unroll
                for (uint32_t i = 0; i < 10; i++) {
                    uint32_t xb[4], a0[4], a1[4];
                    ldsm_x4(xb, sb + OFF_PART + i * 128 + mi * 32 + (lane & 1) * 16);
                    ldsm_x4_t(a0, wa + i * 4096);
                    ldsm_x4_t(a1, wa + i * 4096 + 2048);
                    mma16816(c[(2 * i) & 3], a0[0], a0[1], a0[2], a0[3], xb[0], xb[1]);
                    mma16816(c[(2 * i + 1) & 3], a1[0], a1[1], a1[2], a1[3], xb[2], xb[3]);
                }
#pragma unroll
                for (int e = 0; e < 4; e++) { c[0][e] = (c[0][e] + c[1][e]) + (c[2][e] + c[3][e]); }
                const uint32_t rd = mapa(sb, rank ^ (t & 1));
                if (t < 2)
                    asm volatile("st.async.shared::cluster.mbarrier::complete_tx::bytes.v4.f32 [%0], {%1,%2,%3,%4}, [%5];"
                                 :: "r"(rd + (t ? OFF_PART + 1280 : M_UPD + 192) + aw * 128 + g * 16), "f"(c[0][0]), "f"(c[0][1]), "f"(c[0][2]), "f"(c[0][3]), "r"(rd + B_H) : "memory");
            }
            TR(r54);
            const float rs = rcp(bflo(sv));
            const uint32_t da = sb + OFF_DN + kr * 128 + (((2 * aw + (mi & 1)) ^ c7) << 4);
            uint8_t* yp = P.scr + (G_Y + (fp % 6) * 10240 + rank * 2560 + t * 512 + aw * 128 + g * 16);
#pragma unroll
            for (int i = 0; i < 5; i++) c[i][0] = c[i][1] = c[i][2] = c[i][3] = 0.f;
            mbar_wait(sb + B_H, 0);
#pragma unroll
            for (uint32_t ks = 0; ks < 2; ks++) {
                const uint32_t og = sb + ks * 128 + lane * 4 + P.up_first, ou = og ^ 256;
                const float gs = bf16r((F(lds32(og + M_UPD + 192)) + F(lds32(og + OFF_PART + 1280))) * rs);
                const float h = bf16r(gs * sigm(gs)) * bf16r((F(lds32(ou + M_UPD + 192)) + F(lds32(ou + OFF_PART + 1280))) * rs);
                const uint32_t hp = pack_bf16(h, __shfl_down_sync(0xffffffffu, h, 4));
                const uint32_t h0 = __shfl_sync(0xffffffffu, hp, t * 8 + (g & 1)), h1 = __shfl_sync(0xffffffffu, hp, t * 8 + (g & 1) + 2);
#pragma unroll
                for (uint32_t j = 0; j < 5; j++) {
                    uint32_t a[4];
                    ldsm_x4_t(a, da + j * 4096 + ks * 2048);
                    mma16816(c[j], a[0], a[1], a[2], a[3], h0, h1);
                }
            }
#pragma unroll
            for (int e = 0; e < 4; e++) {
                const float lo = (t & 1) ? c[1][e] : c[0][e], hi = (t & 1) ? c[3][e] : c[2][e];
                c[0][e] = (t & 2) ? hi : lo;
            }
            asm volatile("" : "+f"(c[0][0]), "+f"(c[4][0]) :: "memory");
            BLOCK_SPLIT(tag);
            bar_sync(8, 384);
            { red4(yp, c[0][0], c[0][2]); red4(yp + 5120, c[0][1], c[0][3]); }
            if (t == 0) { red4(yp + 2048, c[4][0], c[4][2]); red4(yp + 2048 + 5120, c[4][1], c[4][3]); }
            TR(r55);
        }
        else bar_arrive(8, 384);
        mbar_wait(sb + B_X, 0); mbar_wait(sb + B_GU, 0);
        TRW(r51, 51); TRW(r30, 30); TRW(r52, 52); TRW(r53, 53); TRW(r54, 54); TRW(r55, 55); TRW(r20, 20); TRW(r22, 22);
        if (owns) {
            const uint32_t u = min(at >> 1, 39u), col = (u >> 3) * 32 + (u & 7) * 2;
            const bool mine = (tok >> 7) == rb && at < 80;
            k1 ^= ((~(int)k1) >> 31) | 0x80000000u;
            const float sg = bf16r(sigm(bfhi(k1))), rs = rcp(bflo(sv));
            uint32_t x0, x1, y0, y1, n0, n1;
            asm volatile("ld.global.nc.u16 %0, [%2];\nld.global.nc.u16 %1, [%2 + 16];" : "=r"(x0), "=r"(x1) : "l"(P.x + (tok * 1280 + hg * 160 + col)));
            const float a0 = (bflo(x0) - bfhi(sv)) * rs, a1 = (bflo(x1) - bfhi(sv)) * rs;
            bar_sync(4, 128);
#pragma unroll 1
            do {
                __nanosleep(YSL);
                uint32_t v[6][4];
#pragma unroll
                for (int r = 0; r < 6; r++) if (mine) ldg128(P.scr + (G_Y + (at & 1) * 5120 + hg * 640 + u * 16) + r * 10240, v[r][0], v[r][1], v[r][2], v[r][3]);
                y0 = U(((F(v[0][0]) + F(v[1][0])) + (F(v[2][0]) + F(v[3][0]))) + (F(v[4][0]) + F(v[5][0])));
                y1 = U(((F(v[0][1]) + F(v[1][1])) + (F(v[2][1]) + F(v[3][1]))) + (F(v[4][1]) + F(v[5][1])));
                n0 = U(((F(v[0][2]) + F(v[1][2])) + (F(v[2][2]) + F(v[3][2]))) + (F(v[4][2]) + F(v[5][2])));
                n1 = U(((F(v[0][3]) + F(v[1][3])) + (F(v[2][3]) + F(v[3][3]))) + (F(v[4][3]) + F(v[5][3])));
            } while (any(mine && (F(n0) != NFFN / 2 || F(n1) != NFFN / 2)) && ++spins < SPIN);
            const float v0 = a0 + bf16r(bf16r(F(y0)) * sg), v1 = a1 + bf16r(bf16r(F(y1)) * sg);
            const uint32_t gp = pack_bf16(v0 * sigm(v0), v1 * sigm(v1));
            if (mine) asm volatile("st.shared.u16 [%0], %1;\nst.shared.u16 [%0 + 16], %2;" :: "r"(sb + M_UPD + (at & 1) * 160 + col), "r"(gp), "r"(gp >> 16) : "memory");
            __syncwarp();
            if (lane < 2) mbar_arrive(sb + B_UPD);
            TS(56);
        }
    }
}

typedef CUresult (*EncodeFn)(CUtensorMap*, CUtensorMapDataType, cuuint32_t, void*, const cuuint64_t*, const cuuint64_t*,
                             const cuuint32_t*, const cuuint32_t*, CUtensorMapInterleave, CUtensorMapSwizzle,
                             CUtensorMapL2promotion, CUtensorMapFloatOOBfill);

bool encode(EncodeFn fn, CUtensorMap* tm, const void* ptr, cuuint64_t d0, cuuint64_t d1, cuuint64_t d2, cuuint64_t s1, cuuint64_t s2,
            cuuint32_t b0, cuuint32_t b1, cuuint32_t b2, CUtensorMapSwizzle sw) {
    const cuuint64_t dims[3] = {d0, d1, d2}, strides[2] = {s1, s2};
    const cuuint32_t box[3] = {b0, b1, b2}, es[3] = {1, 1, 1};
    return fn(tm, CU_TENSOR_MAP_DATA_TYPE_BFLOAT16, 3, const_cast<void*>(ptr), dims, strides, box, es,
              CU_TENSOR_MAP_INTERLEAVE_NONE, sw, CU_TENSOR_MAP_L2_PROMOTION_L2_128B,
              CU_TENSOR_MAP_FLOAT_OOB_FILL_NONE) == CUDA_SUCCESS;
}

}

extern "C" void kernel_launch(void* const* d_in, const int* in_sizes, int n_in, void* d_out, int out_size) {
    static Params P;
    static bool by_sm = false;
    static const void* cached[9] = {};
    bool same = cached[8] == d_out;
    for (int i = 0; i < 8; i++) same = same && cached[i] == d_in[i];
    if (!same) {
        const void *x = d_in[0], *wqkv = d_in[1], *wo = d_in[2], *wg = d_in[5], *wu = d_in[6], *wd = d_in[7];
        void* fnp = nullptr;
        cudaDriverEntryPointQueryResult qr;
        cudaGetDriverEntryPoint("cuTensorMapEncodeTiled", &fnp, cudaEnableDefault, &qr);
        EncodeFn fn = (EncodeFn)fnp;
        const CUtensorMapSwizzle S0 = CU_TENSOR_MAP_SWIZZLE_NONE, S32 = CU_TENSOR_MAP_SWIZZLE_32B, S64 = CU_TENSOR_MAP_SWIZZLE_64B,
                                 S128 = CU_TENSOR_MAP_SWIZZLE_128B;
        const bool ok = fn != nullptr &&
            encode(fn, &P.tm[T_X], x, 640, 1024, 2, 2560, 1280, 64, 64, 2, S128) &&
            encode(fn, &P.tm[T_OUT], d_out, 640, 1024, 2, 2560, 1280, 80, 16, 1, S0) &&
            encode(fn, &P.tm[T_W], wqkv, 640, 640, 3, 3840, 1280, 64, 32, 3, S128) &&
            encode(fn, &P.tm[T_WR], wqkv, 640, 640, 3, 3840, 1280, 16, 32, 3, S32) &&
            encode(fn, &P.tm[T_GU], wg < wu ? wg : wu, 1728, 640, 2, 3456, wg < wu ? (const char*)wu - (const char*)wg : (const char*)wg - (const char*)wu,
                   32, 16, 2, S64) &&
            encode(fn, &P.tm[T_D], wd, 64, 1728, 10, 1280, 128, 64, 32, 5, S128) &&
            encode(fn, &P.tm[T_WO], wo, 640, 640, 1, 1280, 1280 * 640, 32, 80, 1, S64) &&
            encode(fn, &P.tm[T_WOR], wo, 640, 640, 1, 1280, 1280 * 640, 16, 40, 1, S64);
        if (!ok) return;
        P.up_first = wg < wu ? 0 : 256;
        P.wo = (const uint8_t*)wo; P.wd = (const uint8_t*)wd;
        P.x = (const uint8_t*)x; P.w = (const uint8_t*)wqkv; P.w_r = (const uint8_t*)d_in[4];
        if (cudaGetSymbolAddress((void**)&P.scr, g_scr) != cudaSuccess) return;
        cudaFuncSetAttribute(fused_kernel<true>, cudaFuncAttributeMaxDynamicSharedMemorySize, SMEM_BYTES);
        cudaFuncSetAttribute(fused_kernel<false>, cudaFuncAttributeMaxDynamicSharedMemorySize, SMEM_BYTES);
        int ncl = 0, sms = 0, dev = 0;
        {
            cudaLaunchConfig_t cfg = {};
            cfg.gridDim = dim3(128); cfg.blockDim = dim3(NTHREADS); cfg.dynamicSmemBytes = SMEM_BYTES;
            cudaLaunchAttribute at[1];
            at[0].id = cudaLaunchAttributeClusterDimension;
            at[0].val.clusterDim.x = 2; at[0].val.clusterDim.y = 1; at[0].val.clusterDim.z = 1;
            cfg.attrs = at; cfg.numAttrs = 1;
            if (cudaOccupancyMaxActiveClusters(&ncl, fused_kernel<true>, &cfg) != cudaSuccess || ncl < 64) return;
            cudaGetDevice(&dev);
            cudaDeviceGetAttribute(&sms, cudaDevAttrMultiProcessorCount, dev);
        }
        by_sm = sms == 132 && ncl == 66;
        for (int i = 0; i < 8; i++) cached[i] = d_in[i];
        cached[8] = d_out;
    }
    if (by_sm) fused_kernel<true><<<132, NTHREADS, SMEM_BYTES>>>(P);
    else fused_kernel<false><<<128, NTHREADS, SMEM_BYTES>>>(P);
}
```

```cpp
#include <cuda_runtime.h>
#include <cuda_bf16.h>
#include <cuda.h>
#include <stdint.h>

namespace {

constexpr int DM = 640;
constexpr int NTHREADS = 512;
constexpr int NFFN = 108;
#define LEAD 2
#define PACE0 100
#define PACE1 950
#define PX0 1500
#define PX1 500
#define GU0 6000
#define GU1 220
#define GT0 2300
#define GT1 430
#define WOP 150
#define AUXS 500
#define EX1T 7800
#define EX2D 2200
#define SERAT 2
#define YSL 200
#define WSL 300

constexpr int ST = 47104;
constexpr int ST_BM = 16384, ST_BR = 40960;
constexpr int OFF_X = 0;
constexpr int OFF_DN = 20480;
constexpr int OFF_PART = 40960;
constexpr int OFF_WO = 43008;
constexpr int WO_SLOT = 15360;
constexpr int OFF_GU = 4 * ST;
constexpr int M_ST = OFF_GU + 40960;
constexpr int M_CS = M_ST + 1024;
constexpr int M_UPD = M_CS + 1024;
constexpr int M_TOP = M_UPD + 640;
constexpr int M_SEL = M_TOP + 64;
constexpr int B_AX = M_SEL + 16, B_PREP = B_AX + 40, B_UPD = B_PREP + 8,
              B_GU = B_AX + 64, B_DN = B_GU + 8, B_H = B_DN + 8, B_SEL = B_H + 8,
              B_FULL = B_GU + 32, B_EMPTY = B_FULL + 32, B_WO = B_EMPTY + 32;
constexpr int SMEM_BYTES = B_WO + 32;
static_assert(SMEM_BYTES <= 232448 && OFF_WO + 3 * WO_SLOT <= 2 * ST && OFF_WO + 6 * WO_SLOT <= 3 * ST && OFF_WO + 8 * WO_SLOT <= 4 * ST, "smem");

enum { T_X, T_W, T_WR, T_GU, T_D, T_WO, T_WOR, T_OUT, T_N };
struct Params {
    CUtensorMap tm[T_N];
    const uint8_t* x;
    const uint8_t* w_r;
    const uint8_t* w;
    const uint8_t* wo;
    const uint8_t* wd;
    uint8_t* scr;
    uint32_t up_first;
};

constexpr uint32_t XB = 27392;
constexpr uint32_t G_TOP = 25600;
constexpr uint32_t G_CS = G_TOP + 1024;
constexpr uint32_t G_ST = G_CS + 128;
constexpr uint32_t G_FLAG = G_ST + 512;
constexpr uint32_t G_Y = 128 * XB;
constexpr uint32_t G_EPOCH = G_Y + 128 * 512;
static_assert(G_FLAG + 128 == XB, "scratch");
__device__ __align__(1024) uint8_t g_scr[G_EPOCH + 1024];

#define TR(v)
#define TRD(v)
#define TRW(v, i)
#define TS(i)
#define TSG(i)
constexpr unsigned SPIN = 1u << 20;

__device__ __forceinline__ void mbar_init(uint32_t bar, int cnt) {
    asm volatile("mbarrier.init.shared::cta.b64 [%0], %1;" :: "r"(bar), "r"(cnt) : "memory");
}
__device__ __forceinline__ void mbar_expect_tx(uint32_t bar, int bytes) {
    asm volatile("mbarrier.arrive.expect_tx.shared::cta.b64 _, [%0], %1;" :: "r"(bar), "r"(bytes) : "memory");
}
__device__ __forceinline__ void mbar_arrive(uint32_t bar) {
    asm volatile("mbarrier.arrive.shared::cta.b64 _, [%0];" :: "r"(bar) : "memory");
}
__device__ __forceinline__ uint32_t mapa(uint32_t a, uint32_t cta) {
    uint32_t r;
    asm("mapa.shared::cluster.u32 %0, %1, %2;" : "=r"(r) : "r"(a), "r"(cta));
    return r;
}
__device__ __forceinline__ void mbar_arrive_cl(uint32_t cbar) {
    asm volatile("mbarrier.arrive.shared::cluster.b64 _, [%0];" :: "r"(cbar) : "memory");
}
__device__ __forceinline__ void mbar_wait(uint32_t bar, int parity) {
    asm volatile("{\n.reg .pred p;\nLAB_WAIT:\nmbarrier.try_wait.parity.shared::cta.b64 p, [%0], %1;\n@!p bra LAB_WAIT;\n}"
                 :: "r"(bar), "r"(parity) : "memory");
}
__device__ __forceinline__ bool mbar_try(uint32_t bar, int parity) {
    uint32_t r;
    asm volatile("{\n.reg .pred p;\nmbarrier.test_wait.parity.shared::cta.b64 p, [%1], %2;\nselp.u32 %0, 1, 0, p;\n}"
                 : "=r"(r) : "r"(bar), "r"(parity) : "memory");
    return r != 0;
}
__device__ __forceinline__ void tma(uint32_t dst, const CUtensorMap* tm, uint32_t bar, int c0, int c1, int c2 = 0) {
    asm volatile("cp.async.bulk.tensor.3d.shared::cluster.global.mbarrier::complete_tx::bytes [%0], [%1, {%3, %4, %5}], [%2];"
                 :: "r"(dst), "l"(tm), "r"(bar), "r"(c0), "r"(c1), "r"(c2) : "memory");
}
__device__ __forceinline__ void tma_mc(uint32_t dst, const CUtensorMap* tm, uint32_t bar, int c0, int c1) {
    asm volatile("cp.async.bulk.tensor.3d.shared::cluster.global.mbarrier::complete_tx::bytes.multicast::cluster [%0], [%1, {%3, %4, %5}], [%2], %6;"
                 :: "r"(dst), "l"(tm), "r"(bar), "r"(c0), "r"(c1), "r"(0), "h"((uint16_t)3) : "memory");
}
__device__ __forceinline__ void tma_st(const CUtensorMap* tm, uint32_t src, int c0, int c1, int c2) {
    asm volatile("cp.async.bulk.tensor.3d.global.shared::cta.bulk_group [%0, {%2, %3, %4}], [%1];\ncp.async.bulk.commit_group;"
                 :: "l"(tm), "r"(src), "r"(c0), "r"(c1), "r"(c2) : "memory");
}
__device__ __forceinline__ void l2_prefetch(const void* p, int bytes) {
    asm volatile("cp.async.bulk.prefetch.L2.global [%0], %1;" :: "l"(p), "r"(bytes) : "memory");
}
__device__ __forceinline__ void cluster_arrive() { asm volatile("barrier.cluster.arrive.relaxed.aligned;" ::: "memory"); }
__device__ __forceinline__ void cluster_wait() { asm volatile("barrier.cluster.wait.aligned;" ::: "memory"); }
__device__ __forceinline__ void bar_sync(int id, int n) { asm volatile("bar.sync %0, %1;" :: "r"(id), "r"(n) : "memory"); }
__device__ __forceinline__ void bar_arrive(int id, int n) { asm volatile("bar.arrive %0, %1;" :: "r"(id), "r"(n) : "memory"); }
__device__ __forceinline__ bool bar_or(int id, int n, bool v) {
    uint32_t r;
    asm volatile("{\n.reg .pred p, q;\nsetp.ne.u32 p, %3, 0;\nbar.red.or.pred q, %1, %2, p;\nselp.u32 %0, 1, 0, q;\n}"
                 : "=r"(r) : "r"(id), "r"(n), "r"((uint32_t)v) : "memory");
    return r != 0;
}
__device__ __forceinline__ void fence_proxy_async_smem() { asm volatile("fence.proxy.async.shared::cta;" ::: "memory"); }
__device__ __forceinline__ void stg128(void* p, uint32_t a, uint32_t b, uint32_t c, uint32_t d) {
    asm volatile("{\n.reg .b64 l, h;\n.reg .b128 q;\nmov.b64 l, {%1, %2};\nmov.b64 h, {%3, %4};\nmov.b128 q, {l, h};\n"
                 "st.relaxed.gpu.global.b128 [%0], q;\n}" :: "l"(p), "r"(a), "r"(b), "r"(c), "r"(d) : "memory");
}
__device__ __forceinline__ void ldg128(const void* p, uint32_t& a, uint32_t& b, uint32_t& c, uint32_t& d) {
    asm volatile("{\n.reg .b64 l, h;\n.reg .b128 q;\nld.relaxed.gpu.global.b128 q, [%4];\nmov.b128 {l, h}, q;\n"
                 "mov.b64 {%0, %1}, l;\nmov.b64 {%2, %3}, h;\n}" : "=r"(a), "=r"(b), "=r"(c), "=r"(d) : "l"(p) : "memory");
}
__device__ __forceinline__ void red4(void* p, float a, float b) {
    asm volatile("red.relaxed.gpu.global.add.v4.f32 [%0], {%1, %2, %3, %3};" :: "l"(p), "f"(a), "f"(b), "f"(1.0f) : "memory");
}
__device__ __forceinline__ void stg32(void* p, uint32_t a) {
    asm volatile("st.relaxed.gpu.global.u32 [%0], %1;" :: "l"(p), "r"(a) : "memory");
}
__device__ __forceinline__ uint2 ldg64(const void* p) {
    uint2 v;
    asm volatile("{\n.reg .b64 l;\nld.relaxed.gpu.global.b64 l, [%2];\nmov.b64 {%0, %1}, l;\n}" : "=r"(v.x), "=r"(v.y) : "l"(p) : "memory");
    return v;
}
__device__ __forceinline__ unsigned ldg32(const void* p) {
    unsigned v;
    asm volatile("ld.relaxed.gpu.global.u32 %0, [%1];" : "=r"(v) : "l"(p) : "memory");
    return v;
}
__device__ __forceinline__ void ldsm_x4(uint32_t (&r)[4], uint32_t a) {
    asm volatile("ldmatrix.sync.aligned.m8n8.x4.shared.b16 {%0,%1,%2,%3}, [%4];"
                 : "=r"(r[0]), "=r"(r[1]), "=r"(r[2]), "=r"(r[3]) : "r"(a));
}
__device__ __forceinline__ void ldsm_x4_t(uint32_t (&r)[4], uint32_t a) {
    asm volatile("ldmatrix.sync.aligned.m8n8.x4.trans.shared.b16 {%0,%1,%2,%3}, [%4];"
                 : "=r"(r[0]), "=r"(r[1]), "=r"(r[2]), "=r"(r[3]) : "r"(a));
}
__device__ __forceinline__ void stsm_x4(uint32_t a, const uint32_t (&r)[4]) {
    asm volatile("stmatrix.sync.aligned.m8n8.x4.shared.b16 [%0], {%1,%2,%3,%4};"
                 :: "r"(a), "r"(r[0]), "r"(r[1]), "r"(r[2]), "r"(r[3]));
}
__device__ __forceinline__ uint32_t movm(uint32_t a) {
    uint32_t d;
    asm("movmatrix.sync.aligned.m8n8.trans.b16 %0, %1;" : "=r"(d) : "r"(a));
    return d;
}
__device__ __forceinline__ void mma16816(float (&c)[4], uint32_t a0, uint32_t a1, uint32_t a2, uint32_t a3, uint32_t b0, uint32_t b1) {
    asm("mma.sync.aligned.m16n8k16.row.col.f32.bf16.bf16.f32 {%0,%1,%2,%3}, {%4,%5,%6,%7}, {%8,%9}, {%0,%1,%2,%3};"
        : "+f"(c[0]), "+f"(c[1]), "+f"(c[2]), "+f"(c[3]) : "r"(a0), "r"(a1), "r"(a2), "r"(a3), "r"(b0), "r"(b1));
}
__device__ __forceinline__ void mma1688(float (&c)[4], uint32_t a0, uint32_t a1, uint32_t b0) {
    asm("mma.sync.aligned.m16n8k8.row.col.f32.bf16.bf16.f32 {%0,%1,%2,%3}, {%4,%5}, {%6}, {%0,%1,%2,%3};"
        : "+f"(c[0]), "+f"(c[1]), "+f"(c[2]), "+f"(c[3]) : "r"(a0), "r"(a1), "r"(b0));
}
__device__ __forceinline__ void wgmma_fence() { asm volatile("wgmma.fence.sync.aligned;" ::: "memory"); }
__device__ __forceinline__ void wgmma_commit() { asm volatile("wgmma.commit_group.sync.aligned;" ::: "memory"); }
template <int N> __device__ __forceinline__ void wgmma_wait() { asm volatile("wgmma.wait_group.sync.aligned %0;" :: "n"(N) : "memory"); }
__device__ __forceinline__ uint64_t mk(uint32_t lo, uint32_t hi) { return (uint64_t)lo | ((uint64_t)hi << 32); }
constexpr uint32_t HI128 = (1024 >> 4) | (1u << 30), HI64 = (512 >> 4) | (2u << 30), HI32 = (256 >> 4) | (3u << 30);
__device__ __forceinline__ uint32_t pack_bf16(float lo, float hi) {
    uint32_t r;
    asm("cvt.rn.bf16x2.f32 %0, %1, %2;" : "=r"(r) : "f"(hi), "f"(lo));
    return r;
}
__device__ __forceinline__ float bflo(uint32_t u) { return __uint_as_float(u << 16); }
__device__ __forceinline__ float bfhi(uint32_t u) { return __uint_as_float(u & 0xFFFF0000u); }
__device__ __forceinline__ float bf16r(float v) { return __uint_as_float(pack_bf16(0.f, v)); }
__device__ __forceinline__ float ex2(float v) { float r; asm("ex2.approx.ftz.f32 %0, %1;" : "=f"(r) : "f"(v)); return r; }
__device__ __forceinline__ float rcp(float v) { float r; asm("rcp.approx.ftz.f32 %0, %1;" : "=f"(r) : "f"(v)); return r; }
__device__ __forceinline__ float sqrt_a(float v) { float r; asm("sqrt.approx.ftz.f32 %0, %1;" : "=f"(r) : "f"(v)); return r; }
__device__ __forceinline__ float tanh_a(float v) { float r; asm("tanh.approx.f32 %0, %1;" : "=f"(r) : "f"(v)); return r; }
constexpr float LOG2E = 1.4426950408889634f;
__device__ __forceinline__ float sigm(float v) { return rcp(1.0f + ex2(-LOG2E * v)); }
__device__ __forceinline__ uint4 lds128(uint32_t a) {
    uint4 v;
    asm volatile("ld.shared.v4.u32 {%0,%1,%2,%3}, [%4];" : "=r"(v.x), "=r"(v.y), "=r"(v.z), "=r"(v.w) : "r"(a));
    return v;
}
__device__ __forceinline__ float2 lds64f(uint32_t a) {
    float2 v;
    asm volatile("ld.shared.v2.f32 {%0,%1}, [%2];" : "=f"(v.x), "=f"(v.y) : "r"(a));
    return v;
}
__device__ __forceinline__ uint32_t lds32(uint32_t a) {
    uint32_t v;
    asm volatile("ld.shared.u32 %0, [%1];" : "=r"(v) : "r"(a));
    return v;
}
__device__ __forceinline__ void sts128(uint32_t a, uint32_t x, uint32_t y, uint32_t z, uint32_t w) {
    asm volatile("st.shared.v4.u32 [%0], {%1,%2,%3,%4};" :: "r"(a), "r"(x), "r"(y), "r"(z), "r"(w) : "memory");
}
__device__ __forceinline__ void sts64(uint32_t a, uint32_t x, uint32_t y) {
    asm volatile("st.shared.v2.u32 [%0], {%1,%2};" :: "r"(a), "r"(x), "r"(y) : "memory");
}
__device__ __forceinline__ void sts32(uint32_t a, uint32_t x) { asm volatile("st.shared.u32 [%0], %1;" :: "r"(a), "r"(x) : "memory"); }
__device__ __forceinline__ unsigned redux_max(unsigned v) {
    unsigned r;
    asm volatile("redux.sync.max.u32 %0, %1, 0xffffffff;" : "=r"(r) : "r"(v));
    return r;
}
__device__ __forceinline__ float shx(float v, int o) { return __shfl_xor_sync(0xffffffffu, v, o); }
__device__ __forceinline__ uint32_t U(float v) { return __float_as_uint(v); }
__device__ __forceinline__ float F(uint32_t v) { return __uint_as_float(v); }

__device__ __forceinline__ void wgmma_n192_lo(float (&d)[120], uint64_t da, uint64_t db, int scale_d) {
    asm volatile("{\n.reg .pred p;\nsetp.ne.b32 p, %98, 0;\n"
        "wgmma.mma_async.sync.aligned.m64n192k16.f32.bf16.bf16 "
        "{%0, %1, %2, %3, %4, %5, %6, %7, %8, %9, %10, %11, %12, %13, %14, %15, "
        "%16, %17, %18, %19, %20, %21, %22, %23, %24, %25, %26, %27, %28, %29, %30, %31, "
        "%32, %33, %34, %35, %36, %37, %38, %39, %40, %41, %42, %43, %44, %45, %46, %47, "
        "%48, %49, %50, %51, %52, %53, %54, %55, %56, %57, %58, %59, %60, %61, %62, %63, "
        "%64, %65, %66, %67, %68, %69, %70, %71, %72, %73, %74, %75, %76, %77, %78, %79, "
        "%80, %81, %82, %83, %84, %85, %86, %87, %88, %89, %90, %91, %92, %93, %94, %95}, "
        "%96, %97, p, 1, 1, 0, 1;\n}\n"
        : "+f"(d[0]), "+f"(d[1]), "+f"(d[2]), "+f"(d[3]), "+f"(d[4]), "+f"(d[5]), "+f"(d[6]), "+f"(d[7]),
          "+f"(d[8]), "+f"(d[9]), "+f"(d[10]), "+f"(d[11]), "+f"(d[12]), "+f"(d[13]), "+f"(d[14]), "+f"(d[15]),
          "+f"(d[16]), "+f"(d[17]), "+f"(d[18]), "+f"(d[19]), "+f"(d[20]), "+f"(d[21]), "+f"(d[22]), "+f"(d[23]),
          "+f"(d[24]), "+f"(d[25]), "+f"(d[26]), "+f"(d[27]), "+f"(d[28]), "+f"(d[29]), "+f"(d[30]), "+f"(d[31]),
          "+f"(d[32]), "+f"(d[33]), "+f"(d[34]), "+f"(d[35]), "+f"(d[36]), "+f"(d[37]), "+f"(d[38]), "+f"(d[39]),
          "+f"(d[40]), "+f"(d[41]), "+f"(d[42]), "+f"(d[43]), "+f"(d[44]), "+f"(d[45]), "+f"(d[46]), "+f"(d[47]),
          "+f"(d[48]), "+f"(d[49]), "+f"(d[50]), "+f"(d[51]), "+f"(d[52]), "+f"(d[53]), "+f"(d[54]), "+f"(d[55]),
          "+f"(d[56]), "+f"(d[57]), "+f"(d[58]), "+f"(d[59]), "+f"(d[60]), "+f"(d[61]), "+f"(d[62]), "+f"(d[63]),
          "+f"(d[64]), "+f"(d[65]), "+f"(d[66]), "+f"(d[67]), "+f"(d[68]), "+f"(d[69]), "+f"(d[70]), "+f"(d[71]),
          "+f"(d[72]), "+f"(d[73]), "+f"(d[74]), "+f"(d[75]), "+f"(d[76]), "+f"(d[77]), "+f"(d[78]), "+f"(d[79]),
          "+f"(d[80]), "+f"(d[81]), "+f"(d[82]), "+f"(d[83]), "+f"(d[84]), "+f"(d[85]), "+f"(d[86]), "+f"(d[87]),
          "+f"(d[88]), "+f"(d[89]), "+f"(d[90]), "+f"(d[91]), "+f"(d[92]), "+f"(d[93]), "+f"(d[94]), "+f"(d[95])
        : "l"(da), "l"(db), "r"(scale_d));
}
__device__ __forceinline__ void wgmma_n48_hi(float (&d)[120], uint64_t da, uint64_t db, int scale_d) {
    asm volatile("{\n.reg .pred p;\nsetp.ne.b32 p, %26, 0;\n"
        "wgmma.mma_async.sync.aligned.m64n48k16.f32.bf16.bf16 "
        "{%0, %1, %2, %3, %4, %5, %6, %7, %8, %9, %10, %11, %12, %13, %14, %15, "
        "%16, %17, %18, %19, %20, %21, %22, %23}, "
        "%24, %25, p, 1, 1, 0, 1;\n}\n"
        : "+f"(d[96]), "+f"(d[97]), "+f"(d[98]), "+f"(d[99]), "+f"(d[100]), "+f"(d[101]), "+f"(d[102]), "+f"(d[103]),
          "+f"(d[104]), "+f"(d[105]), "+f"(d[106]), "+f"(d[107]), "+f"(d[108]), "+f"(d[109]), "+f"(d[110]), "+f"(d[111]),
          "+f"(d[112]), "+f"(d[113]), "+f"(d[114]), "+f"(d[115]), "+f"(d[116]), "+f"(d[117]), "+f"(d[118]), "+f"(d[119])
        : "l"(da), "l"(db), "r"(scale_d));
}
__device__ __forceinline__ void wgmma_rs_n80(float (&d)[40], uint32_t a0, uint32_t a1, uint32_t a2, uint32_t a3, uint64_t db, int scale_d) {
    asm volatile("{\n.reg .pred p;\nsetp.ne.b32 p, %45, 0;\n"
        "wgmma.mma_async.sync.aligned.m64n80k16.f32.bf16.bf16 "
        "{%0, %1, %2, %3, %4, %5, %6, %7, %8, %9, %10, %11, %12, %13, %14, %15, "
        "%16, %17, %18, %19, %20, %21, %22, %23, %24, %25, %26, %27, %28, %29, %30, %31, "
        "%32, %33, %34, %35, %36, %37, %38, %39}, "
        "{%40, %41, %42, %43}, %44, p, 1, 1, 1;\n}\n"
        : "+f"(d[0]), "+f"(d[1]), "+f"(d[2]), "+f"(d[3]), "+f"(d[4]), "+f"(d[5]), "+f"(d[6]), "+f"(d[7]),
          "+f"(d[8]), "+f"(d[9]), "+f"(d[10]), "+f"(d[11]), "+f"(d[12]), "+f"(d[13]), "+f"(d[14]), "+f"(d[15]),
          "+f"(d[16]), "+f"(d[17]), "+f"(d[18]), "+f"(d[19]), "+f"(d[20]), "+f"(d[21]), "+f"(d[22]), "+f"(d[23]),
          "+f"(d[24]), "+f"(d[25]), "+f"(d[26]), "+f"(d[27]), "+f"(d[28]), "+f"(d[29]), "+f"(d[30]), "+f"(d[31]),
          "+f"(d[32]), "+f"(d[33]), "+f"(d[34]), "+f"(d[35]), "+f"(d[36]), "+f"(d[37]), "+f"(d[38]), "+f"(d[39])
        : "r"(a0), "r"(a1), "r"(a2), "r"(a3), "l"(db), "r"(scale_d));
}
__device__ __forceinline__ void wgmma_rs_n192_lo(float (&d)[120], uint32_t a0, uint32_t a1, uint32_t a2, uint32_t a3, uint64_t db, int scale_d) {
    asm volatile("{\n.reg .pred p;\nsetp.ne.b32 p, %101, 0;\n"
        "wgmma.mma_async.sync.aligned.m64n192k16.f32.bf16.bf16 "
        "{%0, %1, %2, %3, %4, %5, %6, %7, %8, %9, %10, %11, %12, %13, %14, %15, "
        "%16, %17, %18, %19, %20, %21, %22, %23, %24, %25, %26, %27, %28, %29, %30, %31, "
        "%32, %33, %34, %35, %36, %37, %38, %39, %40, %41, %42, %43, %44, %45, %46, %47, "
        "%48, %49, %50, %51, %52, %53, %54, %55, %56, %57, %58, %59, %60, %61, %62, %63, "
        "%64, %65, %66, %67, %68, %69, %70, %71, %72, %73, %74, %75, %76, %77, %78, %79, "
        "%80, %81, %82, %83, %84, %85, %86, %87, %88, %89, %90, %91, %92, %93, %94, %95}, "
        "{%96, %97, %98, %99}, %100, p, 1, 1, 1;\n}\n"
        : "+f"(d[0]), "+f"(d[1]), "+f"(d[2]), "+f"(d[3]), "+f"(d[4]), "+f"(d[5]), "+f"(d[6]), "+f"(d[7]),
          "+f"(d[8]), "+f"(d[9]), "+f"(d[10]), "+f"(d[11]), "+f"(d[12]), "+f"(d[13]), "+f"(d[14]), "+f"(d[15]),
          "+f"(d[16]), "+f"(d[17]), "+f"(d[18]), "+f"(d[19]), "+f"(d[20]), "+f"(d[21]), "+f"(d[22]), "+f"(d[23]),
          "+f"(d[24]), "+f"(d[25]), "+f"(d[26]), "+f"(d[27]), "+f"(d[28]), "+f"(d[29]), "+f"(d[30]), "+f"(d[31]),
          "+f"(d[32]), "+f"(d[33]), "+f"(d[34]), "+f"(d[35]), "+f"(d[36]), "+f"(d[37]), "+f"(d[38]), "+f"(d[39]),
          "+f"(d[40]), "+f"(d[41]), "+f"(d[42]), "+f"(d[43]), "+f"(d[44]), "+f"(d[45]), "+f"(d[46]), "+f"(d[47]),
          "+f"(d[48]), "+f"(d[49]), "+f"(d[50]), "+f"(d[51]), "+f"(d[52]), "+f"(d[53]), "+f"(d[54]), "+f"(d[55]),
          "+f"(d[56]), "+f"(d[57]), "+f"(d[58]), "+f"(d[59]), "+f"(d[60]), "+f"(d[61]), "+f"(d[62]), "+f"(d[63]),
          "+f"(d[64]), "+f"(d[65]), "+f"(d[66]), "+f"(d[67]), "+f"(d[68]), "+f"(d[69]), "+f"(d[70]), "+f"(d[71]),
          "+f"(d[72]), "+f"(d[73]), "+f"(d[74]), "+f"(d[75]), "+f"(d[76]), "+f"(d[77]), "+f"(d[78]), "+f"(d[79]),
          "+f"(d[80]), "+f"(d[81]), "+f"(d[82]), "+f"(d[83]), "+f"(d[84]), "+f"(d[85]), "+f"(d[86]), "+f"(d[87]),
          "+f"(d[88]), "+f"(d[89]), "+f"(d[90]), "+f"(d[91]), "+f"(d[92]), "+f"(d[93]), "+f"(d[94]), "+f"(d[95])
        : "r"(a0), "r"(a1), "r"(a2), "r"(a3), "l"(db), "r"(scale_d));
}
__device__ __forceinline__ void wgmma_rs_n48_hi(float (&d)[120], uint32_t a0, uint32_t a1, uint32_t a2, uint32_t a3, uint64_t db, int scale_d) {
    asm volatile("{\n.reg .pred p;\nsetp.ne.b32 p, %29, 0;\n"
        "wgmma.mma_async.sync.aligned.m64n48k16.f32.bf16.bf16 "
        "{%0, %1, %2, %3, %4, %5, %6, %7, %8, %9, %10, %11, %12, %13, %14, %15, "
        "%16, %17, %18, %19, %20, %21, %22, %23}, "
        "{%24, %25, %26, %27}, %28, p, 1, 1, 1;\n}\n"
        : "+f"(d[96]), "+f"(d[97]), "+f"(d[98]), "+f"(d[99]), "+f"(d[100]), "+f"(d[101]), "+f"(d[102]), "+f"(d[103]),
          "+f"(d[104]), "+f"(d[105]), "+f"(d[106]), "+f"(d[107]), "+f"(d[108]), "+f"(d[109]), "+f"(d[110]), "+f"(d[111]),
          "+f"(d[112]), "+f"(d[113]), "+f"(d[114]), "+f"(d[115]), "+f"(d[116]), "+f"(d[117]), "+f"(d[118]), "+f"(d[119])
        : "r"(a0), "r"(a1), "r"(a2), "r"(a3), "l"(db), "r"(scale_d));
}
__device__ __forceinline__ constexpr int jt_of(int sec, int c, bool odd) {
    return odd ? (c >= 2 ? sec * 8 + c - 2 : 24 + sec * 2 + c) : (c < 8 ? sec * 8 + c : 24 + sec * 2 + (c - 8));
}
#define BOTH(...) if (hg & 1) { constexpr bool odd = true; __VA_ARGS__ } else { constexpr bool odd = false; __VA_ARGS__ }

__device__ __forceinline__ bool elect() {
    uint32_t r;
    asm volatile("{\n.reg .pred p;\nelect.sync _|p, 0xffffffff;\nselp.u32 %0, 1, 0, p;\n}" : "=r"(r));
    return r != 0;
}
__device__ __forceinline__ uint32_t clock32() { uint32_t r; asm volatile("mov.u32 %0, %%clock;" : "=r"(r)); return r; }
#define BLOCK_SPLIT(v) asm volatile("{\n.reg .pred p;\nLAB_SPLIT:\nsetp.eq.u32 p, %0, 0;\n@p nanosleep.u32 1;\n@p bra LAB_SPLIT;\n}" :: "r"(v) : "memory")
__device__ __forceinline__ bool any(bool v) { return __any_sync(0xffffffffu, v); }
__device__ __forceinline__ uint32_t opaque_tid() { uint32_t r; asm volatile("mov.u32 %0, %%tid.x;" : "=r"(r)); return r; }

template <bool BY_SM>
__global__ void __cluster_dims__(2, 1, 1) __launch_bounds__(NTHREADS, 1)
fused_kernel(const __grid_constant__ Params P) {
    extern __shared__ __align__(1024) uint8_t smem[];
    const uint32_t sb = (uint32_t)__cvta_generic_to_shared(smem);
    const uint32_t warp = __shfl_sync(0xffffffffu, threadIdx.x >> 5, 0);
    const uint32_t rank = blockIdx.x & 1;
    constexpr uint32_t sbd = 1024 >> 4;
    const uint32_t t0 = clock32();
    if (warp >= 10 && elect()) {
        const uint32_t bb = sb + B_AX - 320 + warp * 32;
        const int cnt = warp < 12 ? 8 : (warp == 14 ? 16 : 1);
        mbar_init(bb, cnt); mbar_init(bb + 8, cnt); mbar_init(bb + 16, cnt); mbar_init(bb + 24, cnt);
        if (warp == 12) { mbar_expect_tx(sb + B_H, 1024); mbar_expect_tx(sb + B_GU, 40960); }
        if (warp == 13) mbar_expect_tx(sb + B_FULL + 16, ST);
        asm volatile("fence.mbarrier_init.release.cluster;" ::: "memory");
    }
    __syncwarp();
    cluster_arrive();
    if (warp < 3 && elect()) asm volatile("prefetch.tensormap [%0];" :: "l"(&P.tm[warp]) : "memory");
    if (warp - 3 < 2 && blockIdx.x < 128 && elect()) l2_prefetch(P.w + ((warp - 3) * 5 * 245760 + blockIdx.x * 1920), 1920);
    if ((sb & 0xFFFFFF) != 1024) __trap();
    uint32_t gpc = blockIdx.x >> 4, pos = (blockIdx.x >> 1) & 7;
    if (BY_SM) {
        uint32_t tpc;
        asm("mov.u32 %0, %%smid;" : "=r"(tpc));
        tpc >>= 1;
        if (tpc - 60 < 2) {
            __nanosleep(2000);
            return;
        }
        const uint32_t q = ((tpc - 32) * 37) >> 8;
        gpc = tpc < 32 ? tpc & 7 : (tpc < 60 ? tpc - 31 - 7 * q : 0);
        pos = tpc < 32 ? tpc >> 3 : (tpc < 60 ? 4 + q : tpc - 58);
    }
    const uint32_t hg = (0x62740351u >> (4 * pos)) & 7, rb = gpc * 2 + rank, fp = 8 * pos + gpc - 10;
    const uint32_t b = rb * 8 + hg;
    const uint32_t k0 = (((hg >> 2) ^ (rb >> 1)) & 1) * 320;

    if (warp == 13 && elect()) tma(sb + 2 * ST, &P.tm[T_X], sb + B_FULL + 16, k0, rb * 64);
    if (warp == 12) {
        cluster_wait();
        if (elect()) {
            tma_mc(sb + 2 * ST + ST_BM + rank * 12288, &P.tm[T_W], sb + B_FULL + 16, hg * 80 + (hg & 1) * 16, k0 + rank * 32);
            tma_mc(sb + 2 * ST + ST_BR + rank * 3072, &P.tm[T_WR], sb + B_FULL + 16, hg * 80 + 64 - (hg & 1) * 64, k0 + rank * 32);
        }
        __syncwarp();
    }

    if (warp < 8) {
        asm volatile("setmaxnreg.inc.sync.aligned.u32 208;");
        const uint32_t lane = opaque_tid() & 31, g = lane >> 2, t = lane & 3;
        const uint32_t p = warp >> 2, w = warp & 3;
        const uint32_t empty_cl = mapa(sb + B_EMPTY, lane & 1);
        uint8_t* const orow = P.scr + (rb * (8 * XB) + warp * 2560 + lane * 16);
        const uint32_t ta = sb + warp * 2560 + (lane & 15) * 160 + (lane >> 4) * 16;
        uint32_t A[5][20];
        uint32_t xr[5][4], gf[5][4];
        TRD(r12); TRD(r32); TRD(r34); TRD(r22); TRD(r44);
        uint32_t par;
        uint8_t* const halo = orow + (hg * XB + (8 + p - warp) * 2560);
        uint8_t* const flag = P.scr + (G_FLAG + b * XB + w * 8 + p * 4);
        cluster_wait();
        {
            float acc[120];
            bool ok, prep;
            float2 s0, s1;
            uint32_t xa[5], cap[2] = {0u, 0u};
#pragma unroll
            for (uint32_t j = 0; j < 5; j++) {
                const uint32_t cg = 5 * hg + (j < 4 ? j + (hg & 1) : (~hg & 1) * 4);
                xa[j] = (sb + (warp * 16 + (lane & 15)) * 128 + (((lane >> 4) ^ (lane & 7)) << 4)) ^ ((cg & 3) << 5);
                const uint32_t i = cg >> 2, late = (i >= 5) ^ (k0 != 0), bit = 1u << (5 * (i >= 5 ? i - 5 : i) + j);
                cap[0] |= late ? 0u : bit; cap[1] |= late ? bit : 0u;
            }
            uint32_t sta = sb + M_ST + (warp * 16 + g) * 8;
            asm volatile("" : "+r"(sta), "+r"(cap[0]), "+r"(cap[1]), "+r"(xa[0]), "+r"(xa[1]), "+r"(xa[2]), "+r"(xa[3]), "+r"(xa[4]));
            mbar_wait(sb + B_FULL + 16, 0);
#pragma unroll
            for (uint32_t kb = 2; kb < 12; kb++) {
                const uint32_t s = kb & 3;
                const bool hold = kb == 12 - LEAD && p;
                if (hold) {
                    wgmma_wait<0>();
                    if (lane < 2) mbar_arrive_cl(empty_cl + 8 * ((11 - LEAD) & 3));
                    bar_sync(1, 256);
                }
                wgmma_fence();
                const uint32_t st = sbd + s * (ST >> 4);
#pragma unroll
                for (int ks = 0; ks < 4; ks++) {
                    const uint64_t da = mk(st + p * 512 + ks * 2 + 0x10000, HI128);
                    wgmma_n48_hi(acc, da, mk(st + (ST_BR >> 4) + (ks >> 1) * 192 + (ks & 1) * 32 + (64 << 16), HI32), ks || kb > 2);
                    wgmma_n192_lo(acc, da, mk(st + (ST_BM >> 4) + (ks >> 1) * 768 + (ks & 1) * 128 + (256 << 16), HI128), ks || kb > 2);
                    if (ks == 0) {
                        wgmma_commit();
                        wgmma_wait<1>();
                        if (!hold && kb > 2 && lane < 2) mbar_arrive_cl(empty_cl + 8 * ((kb - 1) & 3));
                    }
                    if (ks == 1) {
#pragma unroll
                        for (uint32_t j = 0; j < 5; j++)
                            if ((cap[kb >= 7] >> (5 * ((kb - 2) % 5) + j)) & 1) ldsm_x4(xr[j], xa[j] + s * ST);
                        if (w == 3 && kb < 7) stg128(halo + (kb - 2) * 512, 0u, 0u, 0u, 0u);
                        if (lane == 0 && kb == 2) stg32(flag, 0u);
                        if (kb < 11) ok = mbar_try(sb + B_FULL + 8 * ((kb + 1) & 3), ((kb - 1) >> 2) & 1);
                        if (kb == 10) prep = mbar_try(sb + B_PREP, 0) & mbar_try(sb + B_EMPTY, 1);
                        if (kb == 11 && prep) {
                            s0 = lds64f(sta); s1 = lds64f(sta + 64);
                            par = lds32(sb + M_SEL + 8);
                        }
                    }
                }
                wgmma_commit();
                if (kb < 11 && !ok) mbar_wait(sb + B_FULL + 8 * ((kb + 1) & 3), ((kb - 1) >> 2) & 1);
            }
            if (!prep) {
                mbar_wait(sb + B_EMPTY, 1);
                mbar_wait(sb + B_PREP, 0);
                s0 = lds64f(sta); s1 = lds64f(sta + 64);
                par = lds32(sb + M_SEL + 8);
            }
            {
                const uint32_t a0 = t ? 0u : __byte_perm(U(-s0.y), 0, 0x3232), a1 = t ? 0u : __byte_perm(U(-s1.y), 0, 0x3232);
                wgmma_fence();
                wgmma_rs_n48_hi(acc, a0, a1, 0u, 0u, mk(sbd + (M_CS >> 4) + 48, 2), 1);
                wgmma_rs_n192_lo(acc, a0, a1, 0u, 0u, mk(sbd + (M_CS >> 4), 2), 1);
                wgmma_commit();
            }
            if (!p) bar_arrive(1, 256);
            wgmma_wait<1>();
            if (lane < 2) mbar_arrive_cl(empty_cl + 24);
            wgmma_wait<0>();
#pragma unroll
            for (int i = 0; i < 120; i++) asm volatile("" : "+f"(acc[i]) :: "memory");
            TR(r12);
            uint32_t Q[10], Ql[10], KX[10], VX[10], Y[20];
#define KI(c) ((c) == 2 ? 8 : (c) == 7 ? 9 : (c) - ((c) > 2) - ((c) > 7))
#define KY(c) Y[KI(c)]
#define VY(c) Y[10 + (c)]
            uint32_t Z[20];
            const bool start = w == 0 && rb == 0, remote = w == 0 && rb != 0;
            const uint32_t slot = sb + OFF_X + warp * 2560 + lane * 16;
            {
                BOTH(_Pragma("unroll") for (int c = 0; c < 10; c++) {
                    const int jk = jt_of(1, c, odd), jv = jt_of(2, c, odd);
                    VY(c) = movm(pack_bf16(acc[4 * jv + 2] * s1.x, acc[4 * jv + 3] * s1.x));
                    KY(c) = pack_bf16(acc[4 * jk + 2] * s1.x, acc[4 * jk + 3] * s1.x);
                    asm volatile("" : "+r"(KY(c)), "+r"(VY(c)));
                })
                if (w == 3) {
#pragma unroll
                    for (int j = 0; j < 5; j++) {
                        Y[4 * j] = (Y[4 * j] & ~0x10001u) | par;
                        stg128(halo + j * 512, Y[4 * j], Y[4 * j + 1], Y[4 * j + 2], Y[4 * j + 3]);
                    }
                } else {
#pragma unroll
                    for (int j = 0; j < 5; j++) sts128(slot + 2560 + j * 512, Y[4 * j], Y[4 * j + 1], Y[4 * j + 2], Y[4 * j + 3]);
                }
                BOTH(_Pragma("unroll") for (int c = 0; c < 10; c++) {
                    const int jk = jt_of(1, c, odd), jv = jt_of(2, c, odd);
                    KX[c] = pack_bf16(acc[4 * jk] * s0.x, acc[4 * jk + 1] * s0.x);
                    VX[c] = movm(pack_bf16(acc[4 * jv] * s0.x, acc[4 * jv + 1] * s0.x));
                    asm volatile("" : "+r"(KX[c]), "+r"(VX[c]));
                })
                bar_sync(2 + p, 128);
                if (remote) {
#pragma unroll
                    for (int j = 0; j < 5; j++) ldg128(halo - 8 * XB + j * 512, Z[4 * j], Z[4 * j + 1], Z[4 * j + 2], Z[4 * j + 3]);
                } else {
#pragma unroll
                    for (int j = 0; j < 5; j++) {
                        const uint4 v = lds128(slot + (w ? 0 : 2560) + j * 512);
                        Z[4 * j] = v.x; Z[4 * j + 1] = v.y; Z[4 * j + 2] = v.z; Z[4 * j + 3] = v.w;
                    }
                }
                BOTH(_Pragma("unroll") for (int c = 0; c < 10; c++) {
                    const int jq = jt_of(0, c, odd);
                    Ql[c] = pack_bf16(acc[4 * jq], acc[4 * jq + 1]);
                    Q[c] = pack_bf16(acc[4 * jq + 2], acc[4 * jq + 3]);
                    asm volatile("" : "+r"(Ql[c]), "+r"(Q[c]));
                })
            }
            auto scores = [&](float (&l)[4], const uint32_t (&q)[10], const uint32_t (&z)[20], const int c0, const uint32_t mx, const float nz) {
                const uint32_t qa = t < 2 ? q[c0 + 2] : 0u, qb = t < 2 ? 0u : q[c0 + 2];
                float xa[4] = {0.f, 0.f, 0.f, 0.f}, za[4] = {nz, nz, nz, nz}, xb[4], zb[4];
                mma1688(xa, qa, qb, KX[c0 + 2]);
                mma1688(za, qa, qb, z[KI(c0 + 2)]);
#pragma unroll
                for (int e = 0; e < 4; e++) { xb[e] = xa[e]; zb[e] = za[e]; }
                mma16816(xa, q[c0], q[c0 + 3], q[c0 + 1], q[c0 + 4], KX[c0], KX[c0 + 1]);
                mma16816(za, q[c0], q[c0 + 3], q[c0 + 1], q[c0 + 4], z[KI(c0)], z[KI(c0 + 1)]);
                mma16816(xb, q[c0], q[c0 + 3], q[c0 + 1], q[c0 + 4], KX[c0 + 3], KX[c0 + 4]);
                mma16816(zb, q[c0], q[c0 + 3], q[c0 + 1], q[c0 + 4], z[KI(c0 + 3)], z[KI(c0 + 4)]);
                const bool h0 = mx & 1u, h1 = (int)mx < 0;
                l[0] = h0 ? xa[0] : za[0]; l[1] = h1 ? xa[1] : za[1];
                l[2] = h0 ? xb[2] : zb[2]; l[3] = h1 ? xb[3] : zb[3];
                asm volatile("" : "+f"(l[0]), "+f"(l[1]), "+f"(l[2]), "+f"(l[3]));
            };
            auto soft = [&](uint32_t (&pr)[2], const float (&l)[4], const float sq) {
                float m0 = fmaxf(l[0], l[1]), m1 = fmaxf(l[2], l[3]);
                m0 = fmaxf(m0, shx(m0, 1)); m1 = fmaxf(m1, shx(m1, 1));
                m0 = fmaxf(m0, shx(m0, 2)) * -sq; m1 = fmaxf(m1, shx(m1, 2)) * -sq;
                pr[0] = pack_bf16(ex2(fmaf(l[0], sq, m0)), ex2(fmaf(l[1], sq, m0)));
                pr[1] = pack_bf16(ex2(fmaf(l[2], sq, m1)), ex2(fmaf(l[3], sq, m1)));
                asm volatile("" : "+r"(pr[0]), "+r"(pr[1]));
            };
            auto values = [&](const uint32_t (&pr)[2], const uint32_t (&z)[20], const int c0, const uint32_t mx, const int h) {
                float dn[4] = {0.f, 0.f, 0.f, 0.f};
                mma1688(dn, pr[0], pr[1], 0x3F803F80u);
                const float i0 = rcp(dn[0]), i1 = rcp(dn[2]), i2 = t < 2 ? i0 : i1;
#pragma unroll
                for (int c = 0; c < 5; c++) {
                    float oc[4] = {0.f, 0.f, 0.f, 0.f};
                    mma16816(oc, pr[0] & mx, pr[1] & mx, pr[0] & ~mx, pr[1] & ~mx, VX[c0 + c], z[10 + c0 + c]);
                    const bool first = c < 2 || (c == 2 && t < 2);
                    const float iv = c < 2 ? i0 : (c > 2 ? i1 : i2);
                    A[0][2 * (c0 + c) + h] = pack_bf16((first ? oc[0] : oc[2]) * iv, (first ? oc[1] : oc[3]) * iv);
                    asm volatile("" : "+r"(A[0][2 * (c0 + c) + h]));
                }
            };
            auto gate = [&]() {
                const float r0 = 0.5f * s0.x, r1 = 0.5f * s1.x, n0 = -r0 * s0.y, n1 = -r1 * s1.y;
#pragma unroll
                for (int j = 0; j < 5; j++) {
#pragma unroll
                    for (int q = 0; q < 4; q++) {
                        const float v0 = fmaf(bflo(xr[j][q]), q & 1 ? r1 : r0, q & 1 ? n1 : n0), v1 = fmaf(bfhi(xr[j][q]), q & 1 ? r1 : r0, q & 1 ? n1 : n0);
                        gf[j][q] = pack_bf16(fmaf(v0, tanh_a(v0), v0), fmaf(v1, tanh_a(v1), v1));
                        asm volatile("" : "+r"(gf[j][q]));
                    }
                }
            };
            const uint32_t mo = (2 * t > g ? 0xFFFFu : 0u) | (2 * t + 1 > g ? 0xFFFF0000u : 0u);
            constexpr float SC = 0.22360679774997896f * LOG2E;
            {
                float l[4][4];
                uint32_t pr[4][2];
                unsigned spins = 0;
#pragma unroll 1
                while (remote && any((Z[0] & Z[4] & Z[8] & Z[12] & Z[16] & par) == 0u) && ++spins < SPIN) {
#pragma unroll
                    for (int j = 0; j < 5; j++) ldg128(halo - 8 * XB + j * 512, Z[4 * j], Z[4 * j + 1], Z[4 * j + 2], Z[4 * j + 3]);
                }
                TR(r32);
                const float nz = start ? -INFINITY : 0.f;
                scores(l[0], Q, Y, 0, mo, 0.f);
                scores(l[1], Q, Y, 5, mo, 0.f);
                scores(l[2], Ql, Z, 0, ~mo, nz);
                scores(l[3], Ql, Z, 5, ~mo, nz);
                soft(pr[0], l[0], s1.x * SC);
                soft(pr[1], l[1], s1.x * SC);
                soft(pr[2], l[2], s0.x * SC);
                soft(pr[3], l[3], s0.x * SC);
                values(pr[0], Y, 0, mo, 1);
                values(pr[1], Y, 5, mo, 1);
                values(pr[2], Z, 0, ~mo, 0);
                values(pr[3], Z, 5, ~mo, 0);
            }
#pragma unroll
            for (int j = 0; j < 5; j++) {
                A[0][4 * j] = (A[0][4 * j] & ~0x10001u) | par;
                stg128(orow + hg * XB + j * 512, A[0][4 * j], A[0][4 * j + 1], A[0][4 * j + 2], A[0][4 * j + 3]);
            }
            if (lane == 0) stg32(flag, par);
            TR(r34);
            if (p) bar_arrive(8, 384);
            BLOCK_SPLIT(par);
            gate();
        }
        {
            float acc2[40];
            unsigned spins = 0;
            bool again, first = true;
            const uint8_t* src[7];
#pragma unroll
            for (uint32_t i = 0; i < 7; i++) { src[i] = orow + (i >= hg ? XB : 0u); asm volatile("" : "+l"(src[i])); }
            mbar_wait(sb + B_SEL, 0);
            const float2 sel = lds64f(sb + M_SEL);
            uint32_t routed = (U(sel.x) >> 4) == warp || (U(sel.y) >> 4) == warp;
            asm volatile("" : "+r"(routed));
            BLOCK_SPLIT(par);
            if (p) bar_sync(9, 288); else bar_sync(5, 160);
#pragma unroll 1
            do {
#pragma unroll
                for (uint32_t i = 1; i < 5; i++)
#pragma unroll
                    for (int j = 0; j < 5; j++)
                        ldg128(src[i - 1] + (i - 1) * XB + j * 512, A[i][4 * j], A[i][4 * j + 1], A[i][4 * j + 2], A[i][4 * j + 3]);
                if (!p && first) bar_sync(8, 384);
                uint32_t mn = par;
#pragma unroll
                for (int i = 0; i < 8; i++) {
                    const uint32_t (&a)[20] = A[i % 5];
                    if (i == 3 && !p && first) bar_sync(6, 160);
                    wgmma_fence();
#pragma unroll
                    for (int j = 0; j < 5; j++) {
                        wgmma_rs_n80(acc2, a[4 * j], a[4 * j + 1], a[4 * j + 2], a[4 * j + 3],
                                     mk(sbd + ((OFF_WO + i * WO_SLOT) >> 4) + j * 64 + (320 << 16), HI64), i || j);
                        if (i == 7 && j == 2) {
#pragma unroll
                            for (int q = 0; q < 5; q++) mn &= A[q][0] & A[q][4] & A[q][8] & A[q][12] & A[q][16];
                            again = bar_or(2 + p, 128, mn == 0u && ++spins < SPIN);
                        }
                    }
                    if (i < 4 || i == 7) wgmma_commit();
                    if (i == SERAT && !p && first) bar_arrive(9, 288);
                    if (i == 0) TR(r22);
                    if (i >= 1 && i < 4) {
                        uint32_t (&n)[20] = A[i - 1];
                        if (i > 1) mn &= n[0] & n[4] & n[8] & n[12] & n[16];
                        const uint8_t* q = src[i + 3] + (i > 1 ? mn & 256u : 0u);
                        wgmma_wait<1>();
                        bar_arrive(10, 32);
#pragma unroll
                        for (int j = 0; j < 5; j++) ldg128(q + (i + 3) * XB + j * 512, n[4 * j], n[4 * j + 1], n[4 * j + 2], n[4 * j + 3]);
                        bar_arrive(10, 32);
                    }
                }
                first = false;
                if (again) {
                    wgmma_wait<0>();
#pragma unroll
                    for (int j = 0; j < 5; j++)
                        ldg128(orow + hg * XB + j * 512, A[0][4 * j], A[0][4 * j + 1], A[0][4 * j + 2], A[0][4 * j + 3]);
                }
            } while (again);
            const uint32_t o0 = (hg & 1) * 32, o4 = (~hg & 1) * 128;
            if (routed) {
                const float2 sel = lds64f(sb + M_SEL);
                mbar_wait(sb + B_UPD, 0);
#pragma unroll
                for (uint32_t h = 0; h < 2; h++) {
                    const uint32_t row = warp * 16 + g + 8 * h, ga = sb + M_UPD + (row == U(sel.x) ? 0 : 160) + t * 4;
                    if (row == U(sel.x) || row == U(sel.y)) {
#pragma unroll
                        for (int c = 0; c < 5; c++) { gf[c][h] = lds32(ga + (c < 4 ? o0 + c * 32 : o4)); gf[c][h + 2] = lds32(ga + (c < 4 ? o0 + c * 32 : o4) + 16); }
                    }
                }
                __syncwarp();
            }
            wgmma_wait<0>();
#pragma unroll
            for (int i = 0; i < 40; i++) asm volatile("" : "+f"(acc2[i]) :: "memory");
            TR(r44);
#pragma unroll
            for (int c = 0; c < 5; c++) {
#pragma unroll
                for (int q = 0; q < 4; q++)
                    asm("fma.rn.bf16x2 %0, %1, %2, %0;" : "+r"(xr[c][q]) : "r"(pack_bf16(acc2[8 * c + 2 * q], acc2[8 * c + 2 * q + 1])), "r"(gf[c][q]));
                stsm_x4(ta + (c < 4 ? o0 + c * 32 : o4) + OFF_X, xr[c]);
            }
            fence_proxy_async_smem();
            __syncwarp();
            if (lane == 0) {
                tma_st(&P.tm[T_OUT], sb + OFF_X + warp * 2560, hg * 80, rb * 64 + 16 * w, p);
                asm volatile("cp.async.bulk.wait_group.read 0;" ::: "memory");
            }
        }
        TS(46);
        TRW(r12, 12); TRW(r32, 32); TRW(r34, 34); TRW(r22, 22); TRW(r44, 44);
    } else if (warp >= 12) {
        asm volatile("setmaxnreg.dec.sync.aligned.u32 24;");
        if (warp == 12) {
            uint32_t slot = t0 + PACE0;
            if (elect()) {
#pragma unroll 1
                for (uint32_t kb = 1; kb < 10; kb++) {
                    const uint32_t s = (kb + 2) & 3;
                    const uint32_t st = sb + s * ST, fb = sb + B_FULL + 8 * s;
                    const uint32_t kc = kb * 64 + (kb < 5 ? k0 : -k0);
                    if (kb >= 4) {
                        mbar_wait(fb + 32, kb >> 3);
                        if (kb < 9) mbar_wait(sb + B_AX - 32 + 8 * kb, 0);
                    }
                    {
                        slot += PACE1;
#pragma unroll 1
                        while ((int)(clock32() - slot) < 0) { }
                        mbar_expect_tx(fb, ST);
                        tma(st, &P.tm[T_X], fb, kc, rb * 64);
                    }
                    tma_mc(st + ST_BM + rank * 12288, &P.tm[T_W], fb, hg * 80 + (hg & 1) * 16, kc + rank * 32);
                    tma_mc(st + ST_BR + rank * 3072, &P.tm[T_WR], fb, hg * 80 + 64 - (hg & 1) * 64, kc + rank * 32);
                }
                mbar_wait(sb + B_EMPTY, 1);
                mbar_expect_tx(sb + B_DN, 20480);
                tma(sb + OFF_DN, &P.tm[T_D], sb + B_DN, 0, 32 * fp, 5 * rank);
                uint32_t wb = sb + B_WO - 8;
#pragma unroll 1
                for (uint32_t i = 0; i < 8; i++) {
                    if ((0x49 >> i) & 1) {
                        wb += 8;
                        mbar_wait(wb - (B_WO - B_EMPTY - 8), i == 0);
                        mbar_expect_tx(wb, i < 6 ? 3 * 12800 : 2 * 12800);
                    }
                    if (WOP) {
#pragma unroll 1
                        while ((int)(clock32() - slot) < 0) { }
                        slot = clock32() + WOP;
                    }
                    const uint32_t d = sb + OFF_WO + i * WO_SLOT;
                    const uint32_t kr = 80 * (i ? i - (i <= hg) : hg);
                    tma_mc(d + rank * 5120, &P.tm[T_WO], wb, hg * 80 + (hg & 1) * 16 + rank * 32, kr);
                    tma_mc(d + 10240 + rank * 2560, &P.tm[T_WOR], wb, hg * 80 + (~hg & 1) * 64, kr + rank * 40);
                }
            }
        } else if (warp == 13) {
            if (elect()) {
#pragma unroll 1
                for (uint32_t i = 0; i < 3; i++) {
#pragma unroll 1
                    while (clock32() - t0 < PX0 + i * PX1) __nanosleep(20);
                    l2_prefetch(P.w + ((i + 2) * 245760 + b * 1920), 1920);
                    l2_prefetch(P.w + ((i + 7) * 245760 + b * 1920), 1920);
                }
#pragma unroll 1
                for (uint32_t i = 0; i < 14; i++) {
#pragma unroll 1
                    while (clock32() - t0 < GU0 + i * GU1) __nanosleep(20);
                    if (i < 10) l2_prefetch(P.wd + (i * 128 + b) * 1728, 1728);
                    else l2_prefetch(P.wo + ((i - 10) * 128 + b) * 1600, 1600);
                }
            }
        } else if (warp == 15) {
            const uint32_t lane = opaque_tid() & 31;
            const uint8_t* fl = P.scr + (G_FLAG + (rb * 8 + (lane & 7)) * XB + (lane >> 3) * 8);
            cluster_wait();
            mbar_wait(sb + B_PREP, 0);
            const uint32_t par = lds32(sb + M_SEL + 8);
            mbar_wait(sb + B_WO, 0);
            mbar_wait(sb + B_EMPTY + 24, 0);
            __nanosleep(WSL);
            unsigned spins = 0;
            uint2 f;
#pragma unroll 1
            do f = ldg64(fl); while (any(f.x != par) && ++spins < SPIN);
            bar_arrive(5, 160);
            TS(24);
            mbar_wait(sb + B_WO + 8, 0); mbar_wait(sb + B_WO + 16, 0);
            bar_arrive(6, 160);
#pragma unroll 1
            while (any(f.y != par) && ++spins < SPIN) f.y = ldg32(fl + 4);
            bar_arrive(9, 288);
            TS(25);
        } else {
            uint32_t slot = t0 + GT0;
            cluster_wait();
            if (elect()) {
#pragma unroll 1
                for (uint32_t i = 0; i < 20; i++) {
                    slot += GT1;
#pragma unroll 1
                    while ((int)(clock32() - slot) < 0) __nanosleep(20);
                    tma(sb + OFF_GU + i * 2048, &P.tm[T_GU], sb + B_GU, 32 * fp, rank * 320 + i * 16);
                }
            }
        }
    } else {
        asm volatile("setmaxnreg.dec.sync.aligned.u32 72;");
        const uint32_t at = opaque_tid() - 256, lane = at & 31, g = lane >> 2, t = lane & 3, c7 = lane & 7, aw = warp - 8;
        uint8_t* const yz = P.scr + (G_Y + b * 512 + at * 4);
        stg32(yz, 0u);
        __nanosleep(AUXS);
        const uint32_t epoch = ldg32(P.scr + G_EPOCH) + 1 + ldg32(yz), tag = (epoch & 15u) | 16u;
        const uint32_t empty_cl = mapa(sb + B_EMPTY, lane & 1);
        unsigned spins = 0;
        TRD(r51); TRD(r30); TRD(r52); TRD(r53); TRD(r54); TRD(r55); TRD(r20); TRD(r22);
        {
            const uint2 wv = __ldg(reinterpret_cast<const uint2*>(P.w_r + k0 * 2 + min(at, 79u) * 8));
            if (at < 80) sts64(sb + M_UPD + at * 8, wv.x, wv.y);
        }
        uint8_t* const stw = P.scr + (b * XB + G_ST + (lane & 4) * 64 + (at >> 3) * 16);
        uint8_t* const csw = P.scr + (b * XB + G_CS + at);
        uint8_t* const tpw = P.scr + (G_TOP + (hg >> 2) * XB + rb * 64 + aw * 16);
        const bool tpub = lane == 0 && (hg & 3) == 3;
        cluster_wait();
        bar_sync(4, 128);
        mbar_wait(sb + B_FULL + 16, 0);
        if (t == 0) { stg128(stw, 0u, 0u, 0u, 0u); stg32(csw, 0u); }
        if (tpub) stg128(tpw, 0u, 0u, 0u, 0u);

        uint32_t k1, sv;
        {
            const uint32_t xoff = (32 * (hg & 3) + (at >> 3)) * 128 + ((c7 ^ ((at >> 3) & 7)) << 4);
            const uint32_t jt = (rb >> 2) * 8 + rank * 4 + aw;
            const uint32_t coff = jt < 24 ? ST_BM + (jt >> 3) * 4096 + lane * 128 + (((jt ^ lane) & 7) << 4)
                                          : ST_BR + ((jt >> 1) & 3) * 1024 + lane * 32 + (((jt ^ g) & 1) << 4);
            float q[8], c8[8];
#pragma unroll
            for (int e = 0; e < 8; e++) q[e] = c8[e] = 0.f;
#pragma unroll 1
            for (uint32_t kb = 2; kb < 7; kb++) {
                const uint32_t st = sb + (kb & 3) * ST;
                const uint4 wv = lds128(sb + M_UPD - 256 + kb * 128 + c7 * 16);
                mbar_wait(sb + B_FULL + 8 * (kb & 3), kb == 6);
                const uint4 v = lds128(st + xoff), vn = lds128(st + xoff + 2048);
                const uint4 cv = lds128(st + coff), cn = lds128(st + coff + (jt < 24 ? 12288 : 3072));
                if (lane < 2) mbar_arrive_cl(empty_cl - (B_EMPTY + 16 - B_AX) + 8 * kb);
                const uint32_t u[4] = {v.x, v.y, v.z, v.w}, un[4] = {vn.x, vn.y, vn.z, vn.w}, ww[4] = {wv.x, wv.y, wv.z, wv.w};
                const uint32_t cc[4] = {cv.x, cv.y, cv.z, cv.w}, cd[4] = {cn.x, cn.y, cn.z, cn.w};
#pragma unroll
                for (int e = 0; e < 4; e++) {
                    const float a0 = bflo(u[e]), a1 = bfhi(u[e]), b0 = bflo(un[e]), b1 = bfhi(un[e]), w0 = bflo(ww[e]), w1 = bfhi(ww[e]);
                    q[0] += a0 + a1; q[4] += b0 + b1; q[3] += w0 + w1;
                    q[1] = fmaf(a0, a0, fmaf(a1, a1, q[1])); q[5] = fmaf(b0, b0, fmaf(b1, b1, q[5]));
                    q[2] = fmaf(a0, w0, fmaf(a1, w1, q[2])); q[6] = fmaf(b0, w0, fmaf(b1, w1, q[6]));
                    c8[2 * e] += bflo(cc[e]) + bflo(cd[e]); c8[2 * e + 1] += bfhi(cc[e]) + bfhi(cd[e]);
                }
            }
            TR(r51);
            q[7] = q[3];
#pragma unroll
            for (int e = 0; e < 4; e++) {
                q[e] = ((lane & 4) ? q[e + 4] : q[e]) + shx((lane & 4) ? q[e] : q[e + 4], 4);
                q[e] += shx(q[e], 1); q[e] += shx(q[e], 2);
            }
            const float mh = q[0] * (1.0f / 320);
            if (t == 0) stg128(stw, U(mh), U(fmaf(-mh, q[0], q[1])), U(q[2]), (U(q[3]) & ~31u) | tag);
#define TSTEP(H) { const bool up = (lane & (4 * H)) != 0; _Pragma("unroll") for (int e = 0; e < H; e++) { \
            const float send = up ? c8[e] : c8[e + H]; const float keep = up ? c8[e + H] : c8[e]; \
            c8[e] = keep + shx(send, 4 * H); } }
            TSTEP(4) TSTEP(2) TSTEP(1)
#undef TSTEP
            c8[0] += shx(c8[0], 1); c8[0] += shx(c8[0], 2);
            if (t == 0) stg32(csw, (U(c8[0]) & ~31u) | tag);
            TR(r30);
            const uint8_t* csp = P.scr + (G_CS + (aw * 32 + (lane >> 4) * 8 + hg) * XB + (lane & 15) * 8);
            const uint8_t* stp = P.scr + (G_ST + (rb * 8 + aw) * XB + lane * 16);
            uint32_t ra[4], rc[4];
            uint2 ca, cc;
#pragma unroll 1
            while (clock32() - t0 < EX1T) __nanosleep(20);
#pragma unroll 1
            do {
                ldg128(stp, ra[0], ra[1], ra[2], ra[3]);
                ldg128(stp + 4 * XB, rc[0], rc[1], rc[2], rc[3]);
                ca = ldg64(csp); cc = ldg64(csp + 16 * XB);
            } while (any((ra[3] ^ tag | rc[3] ^ tag) & 31u) && ++spins < SPIN);
            TR(r20);
            const float dm = 0.5f * (F(ra[0]) - F(rc[0])), m = bf16r(F(rc[0]) + dm);
            const float sd = bf16r(sqrt_a(bf16r(bf16r(fmaxf(fmaf(dm, dm, (F(ra[1]) + F(rc[1])) * (1.0f / DM)), 0.f)) + 1e-5f)));
            const float rs = rcp(sd);
            uint32_t w1, w2;
            if ((hg & 3) == 3) {
                k1 = pack_bf16(0.f, fmaf(-m, F(ra[3]) + F(rc[3]), F(ra[2]) + F(rc[2])) * rs);
                k1 ^= ((int)k1 >> 31) | 0x80000000u;
                k1 = (k1 & 0xFFFF0000u) | ((2047 - (rb * 128 + 2 * (at & 63) + (at >> 6))) << 5) | tag;
                w1 = redux_max(k1); w2 = redux_max(k1 == w1 ? 0u : k1);
                sv = U(m) | (U(sd) >> 16);
                const uint32_t v1 = redux_max(k1 == w1 ? sv : 0u), v2 = redux_max(k1 == w2 ? sv : 0u);
                if (lane == 0) stg128(tpw, w1, v1, w2, v2);
            }
            sts64(sb + M_ST + at * 8, U(rs), U(m));
            sts32(sb + M_SEL + 8, (tag & 1) ? 1u : 0x10000u);
#pragma unroll 1
            while (any((ca.x ^ tag | ca.y ^ tag | cc.x ^ tag | cc.y ^ tag) & 31u) && ++spins < SPIN) { ca = ldg64(csp); cc = ldg64(csp + 16 * XB); }
            {
                const float c0 = at < 120 ? F(ca.x) + F(cc.x) : 0.f, c1 = at < 120 ? F(ca.y) + F(cc.y) : 0.f;
                const uint32_t hi = pack_bf16(c0, c1);
                sts32(sb + M_CS + (at >> 2) * 32 + t * 4, hi);
                sts32(sb + M_CS + (at >> 2) * 32 + t * 4 + 16, pack_bf16(c0 - bflo(hi), c1 - bfhi(hi)));
                fence_proxy_async_smem();
                __syncwarp();
                if (lane < 2) mbar_arrive(sb + B_PREP);
            }
            TR(r52);
            if (aw == 0) {
                uint32_t ka[4], kb[4];
#pragma unroll 1
                while (clock32() - t0 < EX1T + EX2D) __nanosleep(20);
#pragma unroll 1
                do {
                    const uint8_t* tp = P.scr + (G_TOP + lane * 16);
                    uint32_t kc[4], kd[4];
                    ldg128(tp, ka[0], ka[1], ka[2], ka[3]);
                    ldg128(tp + 512, kb[0], kb[1], kb[2], kb[3]);
                    ldg128(tp + XB, kc[0], kc[1], kc[2], kc[3]);
                    ldg128(tp + XB + 512, kd[0], kd[1], kd[2], kd[3]);
                    const bool ba = (ka[0] ^ tag) & 31u, bb = (kb[0] ^ tag) & 31u;
#pragma unroll
                    for (int e = 0; e < 4; e++) { ka[e] = ba ? kc[e] : ka[e]; kb[e] = bb ? kd[e] : kb[e]; }
                } while (any((ka[0] ^ tag | kb[0] ^ tag) & 31u) && ++spins < SPIN);
                TR(r22);
                if (kb[0] > ka[0]) {
#pragma unroll
                    for (int e = 0; e < 4; e++) { const uint32_t x = ka[e]; ka[e] = kb[e]; kb[e] = x; }
                }
                if (kb[0] > ka[2]) { ka[2] = kb[0]; ka[3] = kb[1]; }
                w1 = redux_max(ka[0]);
                const uint32_t t1 = redux_max(ka[0] == w1 ? ka[1] : 0u);
                if (ka[0] == w1) { ka[0] = ka[2]; ka[1] = ka[3]; }
                w2 = redux_max(ka[0]);
                const uint32_t t3 = redux_max(ka[0] == w2 ? ka[1] : 0u);
                sts128(sb + M_TOP, w1, t1, w2, t3);
            }
            bar_sync(4, 128);
            const float2 tv = lds64f(sb + M_TOP + (lane & 1) * 8);
            k1 = U(tv.x);
            sv = U(tv.y);
        }
        TR(r53);
        const uint32_t tok = ~(k1 >> 5) & 2047;
        const unsigned owns = __ballot_sync(0xffffffffu, (tok >> 7) == rb) & 3u;
        if (at < 2) sts32(sb + M_SEL + at * 4, (tok >> 7) == rb ? (tok & 1) * 64 + ((tok & 127) >> 1) : ~0u);
        if ((at | b) == 0) *reinterpret_cast<uint32_t*>(P.scr + G_EPOCH) = epoch;
        __syncwarp();
        if (at == 0) mbar_arrive(sb + B_SEL);
        if (fp < NFFN / 2) {
            uint4 xv = __ldg(reinterpret_cast<const uint4*>(P.x + (tok * 1280 + rank * 640 + min(at >> 1, 39u) * 16)));
            const uint32_t m2 = __byte_perm(sv, 0, 0x3232);
            asm("sub.rn.bf16x2 %0, %0, %4;\nsub.rn.bf16x2 %1, %1, %4;\nsub.rn.bf16x2 %2, %2, %4;\nsub.rn.bf16x2 %3, %3, %4;"
                : "+r"(xv.x), "+r"(xv.y), "+r"(xv.z), "+r"(xv.w) : "r"(m2));
            mbar_wait(sb + B_DN, 0);
            if (at < 80) sts128(sb + OFF_PART + at * 16, xv.x, xv.y, xv.z, xv.w);
            mbar_wait(sb + B_GU, 0);
            mbar_wait(sb + B_EMPTY + 24, 0);
            bar_sync(4, 128);
            float c[5][4];
#pragma unroll
            for (int i = 0; i < 5; i++) c[i][0] = c[i][1] = c[i][2] = c[i][3] = 0.f;
            const uint32_t mi = lane >> 3, kr = c7 + (mi >> 1) * 8;
            {
                const uint32_t wa = sb + OFF_GU + (aw >> 1) * 1024 + kr * 64 + ((((aw & 1) * 2 + (mi & 1)) ^ ((kr >> 1) & 3)) << 4);
#pragma unroll
                for (uint32_t i = 0; i < 10; i++) {
                    uint32_t xb[4], a0[4], a1[4];
                    ldsm_x4(xb, sb + OFF_PART + i * 128 + mi * 32 + (lane & 1) * 16);
                    ldsm_x4_t(a0, wa + i * 4096);
                    ldsm_x4_t(a1, wa + i * 4096 + 2048);
                    mma16816(c[(2 * i) & 3], a0[0], a0[1], a0[2], a0[3], xb[0], xb[1]);
                    mma16816(c[(2 * i + 1) & 3], a1[0], a1[1], a1[2], a1[3], xb[2], xb[3]);
                }
#pragma unroll
                for (int e = 0; e < 4; e++) { c[0][e] = (c[0][e] + c[1][e]) + (c[2][e] + c[3][e]); }
                const uint32_t rd = mapa(sb, rank ^ (t & 1));
                if (t < 2)
                    asm volatile("st.async.shared::cluster.mbarrier::complete_tx::bytes.v4.f32 [%0], {%1,%2,%3,%4}, [%5];"
                                 :: "r"(rd + (t ? OFF_PART + 1280 : M_UPD + 192) + aw * 128 + g * 16), "f"(c[0][0]), "f"(c[0][1]), "f"(c[0][2]), "f"(c[0][3]), "r"(rd + B_H) : "memory");
            }
            TR(r54);
            const float rs = rcp(bflo(sv));
            const uint32_t da = sb + OFF_DN + kr * 128 + (((2 * aw + (mi & 1)) ^ c7) << 4);
            uint8_t* yp = P.scr + (G_Y + (fp % 6) * 10240 + rank * 2560 + t * 512 + aw * 128 + g * 16);
#pragma unroll
            for (int i = 0; i < 5; i++) c[i][0] = c[i][1] = c[i][2] = c[i][3] = 0.f;
            mbar_wait(sb + B_H, 0);
#pragma unroll
            for (uint32_t ks = 0; ks < 2; ks++) {
                const uint32_t og = sb + ks * 128 + lane * 4 + P.up_first, ou = og ^ 256;
                const float gs = bf16r((F(lds32(og + M_UPD + 192)) + F(lds32(og + OFF_PART + 1280))) * rs);
                const float h = bf16r(gs * sigm(gs)) * bf16r((F(lds32(ou + M_UPD + 192)) + F(lds32(ou + OFF_PART + 1280))) * rs);
                const uint32_t hp = pack_bf16(h, __shfl_down_sync(0xffffffffu, h, 4));
                const uint32_t h0 = __shfl_sync(0xffffffffu, hp, t * 8 + (g & 1)), h1 = __shfl_sync(0xffffffffu, hp, t * 8 + (g & 1) + 2);
#pragma unroll
                for (uint32_t j = 0; j < 5; j++) {
                    uint32_t a[4];
                    ldsm_x4_t(a, da + j * 4096 + ks * 2048);
                    mma16816(c[j], a[0], a[1], a[2], a[3], h0, h1);
                }
            }
#pragma unroll
            for (int e = 0; e < 4; e++) {
                const float lo = (t & 1) ? c[1][e] : c[0][e], hi = (t & 1) ? c[3][e] : c[2][e];
                c[0][e] = (t & 2) ? hi : lo;
            }
            asm volatile("" : "+f"(c[0][0]), "+f"(c[4][0]) :: "memory");
            BLOCK_SPLIT(tag);
            bar_sync(8, 384);
            { red4(yp, c[0][0], c[0][2]); red4(yp + 5120, c[0][1], c[0][3]); }
            if (t == 0) { red4(yp + 2048, c[4][0], c[4][2]); red4(yp + 2048 + 5120, c[4][1], c[4][3]); }
            TR(r55);
        }
        else bar_arrive(8, 384);
        mbar_wait(sb + B_DN, 0); mbar_wait(sb + B_GU, 0);
        TRW(r51, 51); TRW(r30, 30); TRW(r52, 52); TRW(r53, 53); TRW(r54, 54); TRW(r55, 55); TRW(r20, 20); TRW(r22, 22);
        if (owns) {
            const uint32_t u = min(at >> 1, 39u), col = (u >> 3) * 32 + (u & 7) * 2;
            const bool mine = (tok >> 7) == rb && at < 80;
            k1 ^= ((~(int)k1) >> 31) | 0x80000000u;
            const float sg = bf16r(sigm(bfhi(k1))), rs = rcp(bflo(sv));
            uint32_t x0, x1, y0, y1, n0, n1;
            asm volatile("ld.global.nc.u16 %0, [%2];\nld.global.nc.u16 %1, [%2 + 16];" : "=r"(x0), "=r"(x1) : "l"(P.x + (tok * 1280 + hg * 160 + col)));
            const float a0 = (bflo(x0) - bfhi(sv)) * rs, a1 = (bflo(x1) - bfhi(sv)) * rs;
            bar_sync(4, 128);
#pragma unroll 1
            do {
                __nanosleep(YSL);
                uint32_t v[6][4];
#pragma unroll
                for (int r = 0; r < 6; r++) if (mine) ldg128(P.scr + (G_Y + (at & 1) * 5120 + hg * 640 + u * 16) + r * 10240, v[r][0], v[r][1], v[r][2], v[r][3]);
                y0 = U(((F(v[0][0]) + F(v[1][0])) + (F(v[2][0]) + F(v[3][0]))) + (F(v[4][0]) + F(v[5][0])));
                y1 = U(((F(v[0][1]) + F(v[1][1])) + (F(v[2][1]) + F(v[3][1]))) + (F(v[4][1]) + F(v[5][1])));
                n0 = U(((F(v[0][2]) + F(v[1][2])) + (F(v[2][2]) + F(v[3][2]))) + (F(v[4][2]) + F(v[5][2])));
                n1 = U(((F(v[0][3]) + F(v[1][3])) + (F(v[2][3]) + F(v[3][3]))) + (F(v[4][3]) + F(v[5][3])));
            } while (any(mine && (F(n0) != NFFN / 2 || F(n1) != NFFN / 2)) && ++spins < SPIN);
            const float v0 = a0 + bf16r(bf16r(F(y0)) * sg), v1 = a1 + bf16r(bf16r(F(y1)) * sg);
            const uint32_t gp = pack_bf16(v0 * sigm(v0), v1 * sigm(v1));
            if (mine) asm volatile("st.shared.u16 [%0], %1;\nst.shared.u16 [%0 + 16], %2;" :: "r"(sb + M_UPD + (at & 1) * 160 + col), "r"(gp), "r"(gp >> 16) : "memory");
            __syncwarp();
            if (lane < 2) mbar_arrive(sb + B_UPD);
            TS(56);
        }
    }
}

typedef CUresult (*EncodeFn)(CUtensorMap*, CUtensorMapDataType, cuuint32_t, void*, const cuuint64_t*, const cuuint64_t*,
                             const cuuint32_t*, const cuuint32_t*, CUtensorMapInterleave, CUtensorMapSwizzle,
                             CUtensorMapL2promotion, CUtensorMapFloatOOBfill);

bool encode(EncodeFn fn, CUtensorMap* tm, const void* ptr, cuuint64_t d0, cuuint64_t d1, cuuint64_t d2, cuuint64_t s1, cuuint64_t s2,
            cuuint32_t b0, cuuint32_t b1, cuuint32_t b2, CUtensorMapSwizzle sw) {
    const cuuint64_t dims[3] = {d0, d1, d2}, strides[2] = {s1, s2};
    const cuuint32_t box[3] = {b0, b1, b2}, es[3] = {1, 1, 1};
    return fn(tm, CU_TENSOR_MAP_DATA_TYPE_BFLOAT16, 3, const_cast<void*>(ptr), dims, strides, box, es,
              CU_TENSOR_MAP_INTERLEAVE_NONE, sw, CU_TENSOR_MAP_L2_PROMOTION_L2_128B,
              CU_TENSOR_MAP_FLOAT_OOB_FILL_NONE) == CUDA_SUCCESS;
}

}

extern "C" void kernel_launch(void* const* d_in, const int* in_sizes, int n_in, void* d_out, int out_size) {
    static Params P;
    static bool by_sm = false;
    static const void* cached[9] = {};
    bool same = cached[8] == d_out;
    for (int i = 0; i < 8; i++) same = same && cached[i] == d_in[i];
    if (!same) {
        const void *x = d_in[0], *wqkv = d_in[1], *wo = d_in[2], *wg = d_in[5], *wu = d_in[6], *wd = d_in[7];
        void* fnp = nullptr;
        cudaDriverEntryPointQueryResult qr;
        cudaGetDriverEntryPoint("cuTensorMapEncodeTiled", &fnp, cudaEnableDefault, &qr);
        EncodeFn fn = (EncodeFn)fnp;
        const CUtensorMapSwizzle S0 = CU_TENSOR_MAP_SWIZZLE_NONE, S32 = CU_TENSOR_MAP_SWIZZLE_32B, S64 = CU_TENSOR_MAP_SWIZZLE_64B,
                                 S128 = CU_TENSOR_MAP_SWIZZLE_128B;
        const bool ok = fn != nullptr &&
            encode(fn, &P.tm[T_X], x, 640, 1024, 2, 2560, 1280, 64, 64, 2, S128) &&
            encode(fn, &P.tm[T_OUT], d_out, 640, 1024, 2, 2560, 1280, 80, 16, 1, S0) &&
            encode(fn, &P.tm[T_W], wqkv, 640, 640, 3, 3840, 1280, 64, 32, 3, S128) &&
            encode(fn, &P.tm[T_WR], wqkv, 640, 640, 3, 3840, 1280, 16, 32, 3, S32) &&
            encode(fn, &P.tm[T_GU], wg < wu ? wg : wu, 1728, 640, 2, 3456, wg < wu ? (const char*)wu - (const char*)wg : (const char*)wg - (const char*)wu,
                   32, 16, 2, S64) &&
            encode(fn, &P.tm[T_D], wd, 64, 1728, 10, 1280, 128, 64, 32, 5, S128) &&
            encode(fn, &P.tm[T_WO], wo, 640, 640, 1, 1280, 1280 * 640, 32, 80, 1, S64) &&
            encode(fn, &P.tm[T_WOR], wo, 640, 640, 1, 1280, 1280 * 640, 16, 40, 1, S64);
        if (!ok) return;
        P.up_first = wg < wu ? 0 : 256;
        P.wo = (const uint8_t*)wo; P.wd = (const uint8_t*)wd;
        P.x = (const uint8_t*)x; P.w = (const uint8_t*)wqkv; P.w_r = (const uint8_t*)d_in[4];
        if (cudaGetSymbolAddress((void**)&P.scr, g_scr) != cudaSuccess) return;
        cudaFuncSetAttribute(fused_kernel<true>, cudaFuncAttributeMaxDynamicSharedMemorySize, SMEM_BYTES);
        cudaFuncSetAttribute(fused_kernel<false>, cudaFuncAttributeMaxDynamicSharedMemorySize, SMEM_BYTES);
        int ncl = 0, sms = 0, dev = 0;
        {
            cudaLaunchConfig_t cfg = {};
            cfg.gridDim = dim3(128); cfg.blockDim = dim3(NTHREADS); cfg.dynamicSmemBytes = SMEM_BYTES;
            cudaLaunchAttribute at[1];
            at[0].id = cudaLaunchAttributeClusterDimension;
            at[0].val.clusterDim.x = 2; at[0].val.clusterDim.y = 1; at[0].val.clusterDim.z = 1;
            cfg.attrs = at; cfg.numAttrs = 1;
            if (cudaOccupancyMaxActiveClusters(&ncl, fused_kernel<true>, &cfg) != cudaSuccess || ncl < 64) return;
            cudaGetDevice(&dev);
            cudaDeviceGetAttribute(&sms, cudaDevAttrMultiProcessorCount, dev);
        }
        by_sm = sms == 132 && ncl == 66;
        for (int i = 0; i < 8; i++) cached[i] = d_in[i];
        cached[8] = d_out;
    }
    if (by_sm) fused_kernel<true><<<132, NTHREADS, SMEM_BYTES>>>(P);
    else fused_kernel<false><<<128, NTHREADS, SMEM_BYTES>>>(P);
}
```

```cpp
#include <cuda_runtime.h>
#include <cuda_bf16.h>
#include <cuda.h>
#include <stdint.h>

namespace {

constexpr int DM = 640;
constexpr int NTHREADS = 512;
constexpr int NFFN = 108;
#define LEAD 2
#define PACE0 100
#define PACE1 950
#define PX0 1500
#define PX1 500
#define GU0 6000
#define GU1 220
#define GT0 2300
#define GT1 430
#define WOP 150
#define AUXS 500
#define EX1T 7800
#define EX2D 2200
#define SERAT 2
#define EFB 0
#define EFR 19
#define FFNS 400
#define REDS 0
#define NPRE 8
#define NPD 8
#define YSL 100
#define WSL 300

constexpr int ST = 47104;
constexpr int ST_BM = 16384, ST_BR = 40960;
constexpr int OFF_X = 0;
constexpr int OFF_DN = 20480;
constexpr int OFF_PART = 40960;
constexpr int OFF_WO = 43008;
constexpr int WO_SLOT = 15360;
constexpr int OFF_GU = 4 * ST;
constexpr int M_ST = OFF_GU + 40960;
constexpr int M_CS = M_ST + 1024;
constexpr int M_UPD = M_CS + 1024;
constexpr int M_TOP = M_UPD + 640;
constexpr int M_SEL = M_TOP + 64;
constexpr int B_AX = M_SEL + 16, B_PREP = B_AX + 40, B_UPD = B_PREP + 8,
              B_GU = B_AX + 64, B_DN = B_GU + 8, B_H = B_DN + 8, B_SEL = B_H + 8,
              B_FULL = B_GU + 32, B_EMPTY = B_FULL + 32, B_WO = B_EMPTY + 32;
constexpr int SMEM_BYTES = B_WO + 32;
static_assert(SMEM_BYTES <= 232448 && OFF_WO + 3 * WO_SLOT <= 2 * ST && OFF_WO + 6 * WO_SLOT <= 3 * ST && OFF_WO + 8 * WO_SLOT <= 4 * ST, "smem");

enum { T_X, T_W, T_WR, T_GU, T_D, T_WO, T_WOR, T_OUT, T_N };
struct Params {
    CUtensorMap tm[T_N];
    const uint8_t* x;
    const uint8_t* w_r;
    const uint8_t* w;
    const uint8_t* wo;
    const uint8_t* wd;
    uint8_t* scr;
    uint32_t up_first;
};

constexpr uint32_t XB = 27392;
constexpr uint32_t G_TOP = 25600;
constexpr uint32_t G_CS = G_TOP + 1024;
constexpr uint32_t G_ST = G_CS + 128;
constexpr uint32_t G_FLAG = G_ST + 512;
constexpr uint32_t G_Y = 128 * XB;
constexpr uint32_t G_EPOCH = G_Y + 128 * 512;
static_assert(G_FLAG + 128 == XB, "scratch");
__device__ __align__(1024) uint8_t g_scr[G_EPOCH + 1024];

#define TR(v)
#define TRD(v)
#define TRW(v, i)
#define TS(i)
#define TSG(i)
constexpr unsigned SPIN = 1u << 20;

__device__ __forceinline__ void mbar_init(uint32_t bar, int cnt) {
    asm volatile("mbarrier.init.shared::cta.b64 [%0], %1;" :: "r"(bar), "r"(cnt) : "memory");
}
__device__ __forceinline__ void mbar_expect_tx(uint32_t bar, int bytes) {
    asm volatile("mbarrier.arrive.expect_tx.shared::cta.b64 _, [%0], %1;" :: "r"(bar), "r"(bytes) : "memory");
}
__device__ __forceinline__ void mbar_arrive(uint32_t bar) {
    asm volatile("mbarrier.arrive.shared::cta.b64 _, [%0];" :: "r"(bar) : "memory");
}
__device__ __forceinline__ uint32_t mapa(uint32_t a, uint32_t cta) {
    uint32_t r;
    asm("mapa.shared::cluster.u32 %0, %1, %2;" : "=r"(r) : "r"(a), "r"(cta));
    return r;
}
__device__ __forceinline__ void mbar_arrive_cl(uint32_t cbar) {
    asm volatile("mbarrier.arrive.shared::cluster.b64 _, [%0];" :: "r"(cbar) : "memory");
}
__device__ __forceinline__ void mbar_wait(uint32_t bar, int parity) {
    asm volatile("{\n.reg .pred p;\nLAB_WAIT:\nmbarrier.try_wait.parity.shared::cta.b64 p, [%0], %1;\n@!p bra LAB_WAIT;\n}"
                 :: "r"(bar), "r"(parity) : "memory");
}
__device__ __forceinline__ bool mbar_try(uint32_t bar, int parity) {
    uint32_t r;
    asm volatile("{\n.reg .pred p;\nmbarrier.test_wait.parity.shared::cta.b64 p, [%1], %2;\nselp.u32 %0, 1, 0, p;\n}"
                 : "=r"(r) : "r"(bar), "r"(parity) : "memory");
    return r != 0;
}
__device__ __forceinline__ void tma(uint32_t dst, const CUtensorMap* tm, uint32_t bar, int c0, int c1, int c2 = 0) {
    asm volatile("cp.async.bulk.tensor.3d.shared::cluster.global.mbarrier::complete_tx::bytes [%0], [%1, {%3, %4, %5}], [%2];"
                 :: "r"(dst), "l"(tm), "r"(bar), "r"(c0), "r"(c1), "r"(c2) : "memory");
}
__device__ __forceinline__ void tma_mc(uint32_t dst, const CUtensorMap* tm, uint32_t bar, int c0, int c1) {
    asm volatile("cp.async.bulk.tensor.3d.shared::cluster.global.mbarrier::complete_tx::bytes.multicast::cluster [%0], [%1, {%3, %4, %5}], [%2], %6;"
                 :: "r"(dst), "l"(tm), "r"(bar), "r"(c0), "r"(c1), "r"(0), "h"((uint16_t)3) : "memory");
}
__device__ __forceinline__ void tma_st(const CUtensorMap* tm, uint32_t src, int c0, int c1, int c2) {
    asm volatile("cp.async.bulk.tensor.3d.global.shared::cta.bulk_group [%0, {%2, %3, %4}], [%1];\ncp.async.bulk.commit_group;"
                 :: "l"(tm), "r"(src), "r"(c0), "r"(c1), "r"(c2) : "memory");
}
__device__ __forceinline__ void l2_prefetch(const void* p, int bytes) {
    asm volatile("cp.async.bulk.prefetch.L2.global [%0], %1;" :: "l"(p), "r"(bytes) : "memory");
}
__device__ __forceinline__ void cluster_arrive() { asm volatile("barrier.cluster.arrive.relaxed.aligned;" ::: "memory"); }
__device__ __forceinline__ void cluster_wait() { asm volatile("barrier.cluster.wait.aligned;" ::: "memory"); }
__device__ __forceinline__ void bar_sync(int id, int n) { asm volatile("bar.sync %0, %1;" :: "r"(id), "r"(n) : "memory"); }
__device__ __forceinline__ void bar_arrive(int id, int n) { asm volatile("bar.arrive %0, %1;" :: "r"(id), "r"(n) : "memory"); }
__device__ __forceinline__ bool bar_or(int id, int n, bool v) {
    uint32_t r;
    asm volatile("{\n.reg .pred p, q;\nsetp.ne.u32 p, %3, 0;\nbar.red.or.pred q, %1, %2, p;\nselp.u32 %0, 1, 0, q;\n}"
                 : "=r"(r) : "r"(id), "r"(n), "r"((uint32_t)v) : "memory");
    return r != 0;
}
__device__ __forceinline__ void fence_proxy_async_smem() { asm volatile("fence.proxy.async.shared::cta;" ::: "memory"); }
__device__ __forceinline__ void stg128(void* p, uint32_t a, uint32_t b, uint32_t c, uint32_t d) {
    asm volatile("{\n.reg .b64 l, h;\n.reg .b128 q;\nmov.b64 l, {%1, %2};\nmov.b64 h, {%3, %4};\nmov.b128 q, {l, h};\n"
                 "st.relaxed.gpu.global.b128 [%0], q;\n}" :: "l"(p), "r"(a), "r"(b), "r"(c), "r"(d) : "memory");
}
__device__ __forceinline__ void ldg128(const void* p, uint32_t& a, uint32_t& b, uint32_t& c, uint32_t& d) {
    asm volatile("{\n.reg .b64 l, h;\n.reg .b128 q;\nld.relaxed.gpu.global.b128 q, [%4];\nmov.b128 {l, h}, q;\n"
                 "mov.b64 {%0, %1}, l;\nmov.b64 {%2, %3}, h;\n}" : "=r"(a), "=r"(b), "=r"(c), "=r"(d) : "l"(p) : "memory");
}
__device__ __forceinline__ void red4(void* p, float a, float b) {
    asm volatile("red.relaxed.gpu.global.add.v4.f32 [%0], {%1, %2, %3, %3};" :: "l"(p), "f"(a), "f"(b), "f"(1.0f) : "memory");
}
__device__ __forceinline__ void stg32(void* p, uint32_t a) {
    asm volatile("st.relaxed.gpu.global.u32 [%0], %1;" :: "l"(p), "r"(a) : "memory");
}
__device__ __forceinline__ uint2 ldg64(const void* p) {
    uint2 v;
    asm volatile("{\n.reg .b64 l;\nld.relaxed.gpu.global.b64 l, [%2];\nmov.b64 {%0, %1}, l;\n}" : "=r"(v.x), "=r"(v.y) : "l"(p) : "memory");
    return v;
}
__device__ __forceinline__ unsigned ldg32(const void* p) {
    unsigned v;
    asm volatile("ld.relaxed.gpu.global.u32 %0, [%1];" : "=r"(v) : "l"(p) : "memory");
    return v;
}
__device__ __forceinline__ void ldsm_x4(uint32_t (&r)[4], uint32_t a) {
    asm volatile("ldmatrix.sync.aligned.m8n8.x4.shared.b16 {%0,%1,%2,%3}, [%4];"
                 : "=r"(r[0]), "=r"(r[1]), "=r"(r[2]), "=r"(r[3]) : "r"(a));
}
__device__ __forceinline__ void ldsm_x4_t(uint32_t (&r)[4], uint32_t a) {
    asm volatile("ldmatrix.sync.aligned.m8n8.x4.trans.shared.b16 {%0,%1,%2,%3}, [%4];"
                 : "=r"(r[0]), "=r"(r[1]), "=r"(r[2]), "=r"(r[3]) : "r"(a));
}
__device__ __forceinline__ void stsm_x4(uint32_t a, const uint32_t (&r)[4]) {
    asm volatile("stmatrix.sync.aligned.m8n8.x4.shared.b16 [%0], {%1,%2,%3,%4};"
                 :: "r"(a), "r"(r[0]), "r"(r[1]), "r"(r[2]), "r"(r[3]));
}
__device__ __forceinline__ uint32_t movm(uint32_t a) {
    uint32_t d;
    asm("movmatrix.sync.aligned.m8n8.trans.b16 %0, %1;" : "=r"(d) : "r"(a));
    return d;
}
__device__ __forceinline__ void mma16816(float (&c)[4], uint32_t a0, uint32_t a1, uint32_t a2, uint32_t a3, uint32_t b0, uint32_t b1) {
    asm("mma.sync.aligned.m16n8k16.row.col.f32.bf16.bf16.f32 {%0,%1,%2,%3}, {%4,%5,%6,%7}, {%8,%9}, {%0,%1,%2,%3};"
        : "+f"(c[0]), "+f"(c[1]), "+f"(c[2]), "+f"(c[3]) : "r"(a0), "r"(a1), "r"(a2), "r"(a3), "r"(b0), "r"(b1));
}
__device__ __forceinline__ void mma1688(float (&c)[4], uint32_t a0, uint32_t a1, uint32_t b0) {
    asm("mma.sync.aligned.m16n8k8.row.col.f32.bf16.bf16.f32 {%0,%1,%2,%3}, {%4,%5}, {%6}, {%0,%1,%2,%3};"
        : "+f"(c[0]), "+f"(c[1]), "+f"(c[2]), "+f"(c[3]) : "r"(a0), "r"(a1), "r"(b0));
}
__device__ __forceinline__ void wgmma_fence() { asm volatile("wgmma.fence.sync.aligned;" ::: "memory"); }
__device__ __forceinline__ void wgmma_commit() { asm volatile("wgmma.commit_group.sync.aligned;" ::: "memory"); }
template <int N> __device__ __forceinline__ void wgmma_wait() { asm volatile("wgmma.wait_group.sync.aligned %0;" :: "n"(N) : "memory"); }
__device__ __forceinline__ uint64_t mk(uint32_t lo, uint32_t hi) { return (uint64_t)lo | ((uint64_t)hi << 32); }
constexpr uint32_t HI128 = (1024 >> 4) | (1u << 30), HI64 = (512 >> 4) | (2u << 30), HI32 = (256 >> 4) | (3u << 30);
__device__ __forceinline__ uint32_t pack_bf16(float lo, float hi) {
    uint32_t r;
    asm("cvt.rn.bf16x2.f32 %0, %1, %2;" : "=r"(r) : "f"(hi), "f"(lo));
    return r;
}
__device__ __forceinline__ float bflo(uint32_t u) { return __uint_as_float(u << 16); }
__device__ __forceinline__ float bfhi(uint32_t u) { return __uint_as_float(u & 0xFFFF0000u); }
__device__ __forceinline__ float bf16r(float v) { return __uint_as_float(pack_bf16(0.f, v)); }
__device__ __forceinline__ float ex2(float v) { float r; asm("ex2.approx.ftz.f32 %0, %1;" : "=f"(r) : "f"(v)); return r; }
__device__ __forceinline__ float rcp(float v) { float r; asm("rcp.approx.ftz.f32 %0, %1;" : "=f"(r) : "f"(v)); return r; }
__device__ __forceinline__ float sqrt_a(float v) { float r; asm("sqrt.approx.ftz.f32 %0, %1;" : "=f"(r) : "f"(v)); return r; }
__device__ __forceinline__ float tanh_a(float v) { float r; asm("tanh.approx.f32 %0, %1;" : "=f"(r) : "f"(v)); return r; }
constexpr float LOG2E = 1.4426950408889634f;
__device__ __forceinline__ float sigm(float v) { return rcp(1.0f + ex2(-LOG2E * v)); }
__device__ __forceinline__ uint4 lds128(uint32_t a) {
    uint4 v;
    asm volatile("ld.shared.v4.u32 {%0,%1,%2,%3}, [%4];" : "=r"(v.x), "=r"(v.y), "=r"(v.z), "=r"(v.w) : "r"(a));
    return v;
}
__device__ __forceinline__ float2 lds64f(uint32_t a) {
    float2 v;
    asm volatile("ld.shared.v2.f32 {%0,%1}, [%2];" : "=f"(v.x), "=f"(v.y) : "r"(a));
    return v;
}
__device__ __forceinline__ uint32_t lds32(uint32_t a) {
    uint32_t v;
    asm volatile("ld.shared.u32 %0, [%1];" : "=r"(v) : "r"(a));
    return v;
}
__device__ __forceinline__ void sts128(uint32_t a, uint32_t x, uint32_t y, uint32_t z, uint32_t w) {
    asm volatile("st.shared.v4.u32 [%0], {%1,%2,%3,%4};" :: "r"(a), "r"(x), "r"(y), "r"(z), "r"(w) : "memory");
}
__device__ __forceinline__ void sts64(uint32_t a, uint32_t x, uint32_t y) {
    asm volatile("st.shared.v2.u32 [%0], {%1,%2};" :: "r"(a), "r"(x), "r"(y) : "memory");
}
__device__ __forceinline__ void sts32(uint32_t a, uint32_t x) { asm volatile("st.shared.u32 [%0], %1;" :: "r"(a), "r"(x) : "memory"); }
__device__ __forceinline__ unsigned redux_max(unsigned v) {
    unsigned r;
    asm volatile("redux.sync.max.u32 %0, %1, 0xffffffff;" : "=r"(r) : "r"(v));
    return r;
}
__device__ __forceinline__ float shx(float v, int o) { return __shfl_xor_sync(0xffffffffu, v, o); }
__device__ __forceinline__ uint32_t U(float v) { return __float_as_uint(v); }
__device__ __forceinline__ float F(uint32_t v) { return __uint_as_float(v); }

__device__ __forceinline__ void wgmma_n192_lo(float (&d)[120], uint64_t da, uint64_t db, int scale_d) {
    asm volatile("{\n.reg .pred p;\nsetp.ne.b32 p, %98, 0;\n"
        "wgmma.mma_async.sync.aligned.m64n192k16.f32.bf16.bf16 "
        "{%0, %1, %2, %3, %4, %5, %6, %7, %8, %9, %10, %11, %12, %13, %14, %15, "
        "%16, %17, %18, %19, %20, %21, %22, %23, %24, %25, %26, %27, %28, %29, %30, %31, "
        "%32, %33, %34, %35, %36, %37, %38, %39, %40, %41, %42, %43, %44, %45, %46, %47, "
        "%48, %49, %50, %51, %52, %53, %54, %55, %56, %57, %58, %59, %60, %61, %62, %63, "
        "%64, %65, %66, %67, %68, %69, %70, %71, %72, %73, %74, %75, %76, %77, %78, %79, "
        "%80, %81, %82, %83, %84, %85, %86, %87, %88, %89, %90, %91, %92, %93, %94, %95}, "
        "%96, %97, p, 1, 1, 0, 1;\n}\n"
        : "+f"(d[0]), "+f"(d[1]), "+f"(d[2]), "+f"(d[3]), "+f"(d[4]), "+f"(d[5]), "+f"(d[6]), "+f"(d[7]),
          "+f"(d[8]), "+f"(d[9]), "+f"(d[10]), "+f"(d[11]), "+f"(d[12]), "+f"(d[13]), "+f"(d[14]), "+f"(d[15]),
          "+f"(d[16]), "+f"(d[17]), "+f"(d[18]), "+f"(d[19]), "+f"(d[20]), "+f"(d[21]), "+f"(d[22]), "+f"(d[23]),
          "+f"(d[24]), "+f"(d[25]), "+f"(d[26]), "+f"(d[27]), "+f"(d[28]), "+f"(d[29]), "+f"(d[30]), "+f"(d[31]),
          "+f"(d[32]), "+f"(d[33]), "+f"(d[34]), "+f"(d[35]), "+f"(d[36]), "+f"(d[37]), "+f"(d[38]), "+f"(d[39]),
          "+f"(d[40]), "+f"(d[41]), "+f"(d[42]), "+f"(d[43]), "+f"(d[44]), "+f"(d[45]), "+f"(d[46]), "+f"(d[47]),
          "+f"(d[48]), "+f"(d[49]), "+f"(d[50]), "+f"(d[51]), "+f"(d[52]), "+f"(d[53]), "+f"(d[54]), "+f"(d[55]),
          "+f"(d[56]), "+f"(d[57]), "+f"(d[58]), "+f"(d[59]), "+f"(d[60]), "+f"(d[61]), "+f"(d[62]), "+f"(d[63]),
          "+f"(d[64]), "+f"(d[65]), "+f"(d[66]), "+f"(d[67]), "+f"(d[68]), "+f"(d[69]), "+f"(d[70]), "+f"(d[71]),
          "+f"(d[72]), "+f"(d[73]), "+f"(d[74]), "+f"(d[75]), "+f"(d[76]), "+f"(d[77]), "+f"(d[78]), "+f"(d[79]),
          "+f"(d[80]), "+f"(d[81]), "+f"(d[82]), "+f"(d[83]), "+f"(d[84]), "+f"(d[85]), "+f"(d[86]), "+f"(d[87]),
          "+f"(d[88]), "+f"(d[89]), "+f"(d[90]), "+f"(d[91]), "+f"(d[92]), "+f"(d[93]), "+f"(d[94]), "+f"(d[95])
        : "l"(da), "l"(db), "r"(scale_d));
}
__device__ __forceinline__ void wgmma_n48_hi(float (&d)[120], uint64_t da, uint64_t db, int scale_d) {
    asm volatile("{\n.reg .pred p;\nsetp.ne.b32 p, %26, 0;\n"
        "wgmma.mma_async.sync.aligned.m64n48k16.f32.bf16.bf16 "
        "{%0, %1, %2, %3, %4, %5, %6, %7, %8, %9, %10, %11, %12, %13, %14, %15, "
        "%16, %17, %18, %19, %20, %21, %22, %23}, "
        "%24, %25, p, 1, 1, 0, 1;\n}\n"
        : "+f"(d[96]), "+f"(d[97]), "+f"(d[98]), "+f"(d[99]), "+f"(d[100]), "+f"(d[101]), "+f"(d[102]), "+f"(d[103]),
          "+f"(d[104]), "+f"(d[105]), "+f"(d[106]), "+f"(d[107]), "+f"(d[108]), "+f"(d[109]), "+f"(d[110]), "+f"(d[111]),
          "+f"(d[112]), "+f"(d[113]), "+f"(d[114]), "+f"(d[115]), "+f"(d[116]), "+f"(d[117]), "+f"(d[118]), "+f"(d[119])
        : "l"(da), "l"(db), "r"(scale_d));
}
__device__ __forceinline__ void wgmma_rs_n80(float (&d)[40], uint32_t a0, uint32_t a1, uint32_t a2, uint32_t a3, uint64_t db, int scale_d) {
    asm volatile("{\n.reg .pred p;\nsetp.ne.b32 p, %45, 0;\n"
        "wgmma.mma_async.sync.aligned.m64n80k16.f32.bf16.bf16 "
        "{%0, %1, %2, %3, %4, %5, %6, %7, %8, %9, %10, %11, %12, %13, %14, %15, "
        "%16, %17, %18, %19, %20, %21, %22, %23, %24, %25, %26, %27, %28, %29, %30, %31, "
        "%32, %33, %34, %35, %36, %37, %38, %39}, "
        "{%40, %41, %42, %43}, %44, p, 1, 1, 1;\n}\n"
        : "+f"(d[0]), "+f"(d[1]), "+f"(d[2]), "+f"(d[3]), "+f"(d[4]), "+f"(d[5]), "+f"(d[6]), "+f"(d[7]),
          "+f"(d[8]), "+f"(d[9]), "+f"(d[10]), "+f"(d[11]), "+f"(d[12]), "+f"(d[13]), "+f"(d[14]), "+f"(d[15]),
          "+f"(d[16]), "+f"(d[17]), "+f"(d[18]), "+f"(d[19]), "+f"(d[20]), "+f"(d[21]), "+f"(d[22]), "+f"(d[23]),
          "+f"(d[24]), "+f"(d[25]), "+f"(d[26]), "+f"(d[27]), "+f"(d[28]), "+f"(d[29]), "+f"(d[30]), "+f"(d[31]),
          "+f"(d[32]), "+f"(d[33]), "+f"(d[34]), "+f"(d[35]), "+f"(d[36]), "+f"(d[37]), "+f"(d[38]), "+f"(d[39])
        : "r"(a0), "r"(a1), "r"(a2), "r"(a3), "l"(db), "r"(scale_d));
}
__device__ __forceinline__ void wgmma_rs_n192_lo(float (&d)[120], uint32_t a0, uint32_t a1, uint32_t a2, uint32_t a3, uint64_t db, int scale_d) {
    asm volatile("{\n.reg .pred p;\nsetp.ne.b32 p, %101, 0;\n"
        "wgmma.mma_async.sync.aligned.m64n192k16.f32.bf16.bf16 "
        "{%0, %1, %2, %3, %4, %5, %6, %7, %8, %9, %10, %11, %12, %13, %14, %15, "
        "%16, %17, %18, %19, %20, %21, %22, %23, %24, %25, %26, %27, %28, %29, %30, %31, "
        "%32, %33, %34, %35, %36, %37, %38, %39, %40, %41, %42, %43, %44, %45, %46, %47, "
        "%48, %49, %50, %51, %52, %53, %54, %55, %56, %57, %58, %59, %60, %61, %62, %63, "
        "%64, %65, %66, %67, %68, %69, %70, %71, %72, %73, %74, %75, %76, %77, %78, %79, "
        "%80, %81, %82, %83, %84, %85, %86, %87, %88, %89, %90, %91, %92, %93, %94, %95}, "
        "{%96, %97, %98, %99}, %100, p, 1, 1, 1;\n}\n"
        : "+f"(d[0]), "+f"(d[1]), "+f"(d[2]), "+f"(d[3]), "+f"(d[4]), "+f"(d[5]), "+f"(d[6]), "+f"(d[7]),
          "+f"(d[8]), "+f"(d[9]), "+f"(d[10]), "+f"(d[11]), "+f"(d[12]), "+f"(d[13]), "+f"(d[14]), "+f"(d[15]),
          "+f"(d[16]), "+f"(d[17]), "+f"(d[18]), "+f"(d[19]), "+f"(d[20]), "+f"(d[21]), "+f"(d[22]), "+f"(d[23]),
          "+f"(d[24]), "+f"(d[25]), "+f"(d[26]), "+f"(d[27]), "+f"(d[28]), "+f"(d[29]), "+f"(d[30]), "+f"(d[31]),
          "+f"(d[32]), "+f"(d[33]), "+f"(d[34]), "+f"(d[35]), "+f"(d[36]), "+f"(d[37]), "+f"(d[38]), "+f"(d[39]),
          "+f"(d[40]), "+f"(d[41]), "+f"(d[42]), "+f"(d[43]), "+f"(d[44]), "+f"(d[45]), "+f"(d[46]), "+f"(d[47]),
          "+f"(d[48]), "+f"(d[49]), "+f"(d[50]), "+f"(d[51]), "+f"(d[52]), "+f"(d[53]), "+f"(d[54]), "+f"(d[55]),
          "+f"(d[56]), "+f"(d[57]), "+f"(d[58]), "+f"(d[59]), "+f"(d[60]), "+f"(d[61]), "+f"(d[62]), "+f"(d[63]),
          "+f"(d[64]), "+f"(d[65]), "+f"(d[66]), "+f"(d[67]), "+f"(d[68]), "+f"(d[69]), "+f"(d[70]), "+f"(d[71]),
          "+f"(d[72]), "+f"(d[73]), "+f"(d[74]), "+f"(d[75]), "+f"(d[76]), "+f"(d[77]), "+f"(d[78]), "+f"(d[79]),
          "+f"(d[80]), "+f"(d[81]), "+f"(d[82]), "+f"(d[83]), "+f"(d[84]), "+f"(d[85]), "+f"(d[86]), "+f"(d[87]),
          "+f"(d[88]), "+f"(d[89]), "+f"(d[90]), "+f"(d[91]), "+f"(d[92]), "+f"(d[93]), "+f"(d[94]), "+f"(d[95])
        : "r"(a0), "r"(a1), "r"(a2), "r"(a3), "l"(db), "r"(scale_d));
}
__device__ __forceinline__ void wgmma_rs_n48_hi(float (&d)[120], uint32_t a0, uint32_t a1, uint32_t a2, uint32_t a3, uint64_t db, int scale_d) {
    asm volatile("{\n.reg .pred p;\nsetp.ne.b32 p, %29, 0;\n"
        "wgmma.mma_async.sync.aligned.m64n48k16.f32.bf16.bf16 "
        "{%0, %1, %2, %3, %4, %5, %6, %7, %8, %9, %10, %11, %12, %13, %14, %15, "
        "%16, %17, %18, %19, %20, %21, %22, %23}, "
        "{%24, %25, %26, %27}, %28, p, 1, 1, 1;\n}\n"
        : "+f"(d[96]), "+f"(d[97]), "+f"(d[98]), "+f"(d[99]), "+f"(d[100]), "+f"(d[101]), "+f"(d[102]), "+f"(d[103]),
          "+f"(d[104]), "+f"(d[105]), "+f"(d[106]), "+f"(d[107]), "+f"(d[108]), "+f"(d[109]), "+f"(d[110]), "+f"(d[111]),
          "+f"(d[112]), "+f"(d[113]), "+f"(d[114]), "+f"(d[115]), "+f"(d[116]), "+f"(d[117]), "+f"(d[118]), "+f"(d[119])
        : "r"(a0), "r"(a1), "r"(a2), "r"(a3), "l"(db), "r"(scale_d));
}
__device__ __forceinline__ constexpr int jt_of(int sec, int c, bool odd) {
    return odd ? (c >= 2 ? sec * 8 + c - 2 : 24 + sec * 2 + c) : (c < 8 ? sec * 8 + c : 24 + sec * 2 + (c - 8));
}
#define BOTH(...) if (hg & 1) { constexpr bool odd = true; __VA_ARGS__ } else { constexpr bool odd = false; __VA_ARGS__ }

__device__ __forceinline__ bool elect() {
    uint32_t r;
    asm volatile("{\n.reg .pred p;\nelect.sync _|p, 0xffffffff;\nselp.u32 %0, 1, 0, p;\n}" : "=r"(r));
    return r != 0;
}
__device__ __forceinline__ uint32_t clock32() { uint32_t r; asm volatile("mov.u32 %0, %%clock;" : "=r"(r)); return r; }
#define BLOCK_SPLIT(v) asm volatile("{\n.reg .pred p;\nLAB_SPLIT:\nsetp.eq.u32 p, %0, 0;\n@p nanosleep.u32 1;\n@p bra LAB_SPLIT;\n}" :: "r"(v) : "memory")
__device__ __forceinline__ bool any(bool v) { return __any_sync(0xffffffffu, v); }
__device__ __forceinline__ uint32_t opaque_tid() { uint32_t r; asm volatile("mov.u32 %0, %%tid.x;" : "=r"(r)); return r; }

template <bool BY_SM>
__global__ void __cluster_dims__(2, 1, 1) __launch_bounds__(NTHREADS, 1)
fused_kernel(const __grid_constant__ Params P) {
    extern __shared__ __align__(1024) uint8_t smem[];
    const uint32_t sb = (uint32_t)__cvta_generic_to_shared(smem);
    const uint32_t warp = __shfl_sync(0xffffffffu, threadIdx.x >> 5, 0);
    const uint32_t rank = blockIdx.x & 1;
    constexpr uint32_t sbd = 1024 >> 4;
    const uint32_t t0 = clock32();
    if (warp >= 10 && elect()) {
        const uint32_t bb = sb + B_AX - 320 + warp * 32;
        const int cnt = warp < 12 ? 8 : (warp == 14 ? 16 : 1);
        mbar_init(bb, cnt); mbar_init(bb + 8, cnt); mbar_init(bb + 16, cnt); mbar_init(bb + 24, cnt);
        if (warp == 12) { mbar_expect_tx(sb + B_H, 1024); mbar_expect_tx(sb + B_GU, 40960); }
        if (warp == 13) mbar_expect_tx(sb + B_FULL + 16, ST);
        asm volatile("fence.mbarrier_init.release.cluster;" ::: "memory");
    }
    __syncwarp();
    cluster_arrive();
    if (warp < 3 && elect()) asm volatile("prefetch.tensormap [%0];" :: "l"(&P.tm[warp]) : "memory");
    if (warp - 3 < 2 && blockIdx.x < 128 && elect()) l2_prefetch(P.w + ((warp - 3) * 5 * 245760 + blockIdx.x * 1920), 1920);
    if ((sb & 0xFFFFFF) != 1024) __trap();
    uint32_t gpc = blockIdx.x >> 4, pos = (blockIdx.x >> 1) & 7;
    if (BY_SM) {
        uint32_t tpc;
        asm("mov.u32 %0, %%smid;" : "=r"(tpc));
        tpc >>= 1;
        if (tpc - 60 < 2) {
            __nanosleep(2000);
            return;
        }
        const uint32_t q = ((tpc - 32) * 37) >> 8;
        gpc = tpc < 32 ? tpc & 7 : (tpc < 60 ? tpc - 31 - 7 * q : 0);
        pos = tpc < 32 ? tpc >> 3 : (tpc < 60 ? 4 + q : tpc - 58);
    }
    const uint32_t hg = (0x62740351u >> (4 * pos)) & 7, rb = gpc * 2 + rank, fp = 8 * pos + gpc - 10;
    const uint32_t b = rb * 8 + hg;
    const uint32_t k0 = (((hg >> 2) ^ (rb >> 1)) & 1) * 320;

    if (warp == 13 && elect()) tma(sb + 2 * ST, &P.tm[T_X], sb + B_FULL + 16, k0, rb * 64);
    if (warp == 12) {
        cluster_wait();
        if (elect()) {
            tma_mc(sb + 2 * ST + ST_BM + rank * 12288, &P.tm[T_W], sb + B_FULL + 16, hg * 80 + (hg & 1) * 16, k0 + rank * 32);
            tma_mc(sb + 2 * ST + ST_BR + rank * 3072, &P.tm[T_WR], sb + B_FULL + 16, hg * 80 + 64 - (hg & 1) * 64, k0 + rank * 32);
        }
        __syncwarp();
    }

    if (warp < 8) {
        asm volatile("setmaxnreg.inc.sync.aligned.u32 208;");
        const uint32_t lane = opaque_tid() & 31, g = lane >> 2, t = lane & 3;
        const uint32_t p = warp >> 2, w = warp & 3;
        const uint32_t empty_cl = mapa(sb + B_EMPTY, lane & 1);
        uint8_t* const orow = P.scr + (rb * (8 * XB) + warp * 2560 + lane * 16);
        const uint32_t ta = sb + warp * 2560 + (lane & 15) * 160 + (lane >> 4) * 16;
        uint32_t A[5][20];
        uint32_t xr[5][4], gf[5][4];
        TRD(r12); TRD(r32); TRD(r34); TRD(r22); TRD(r44);
        uint32_t par;
        uint8_t* const halo = orow + (hg * XB + (8 + p - warp) * 2560);
        uint8_t* const flag = P.scr + (G_FLAG + b * XB + w * 8 + p * 4);
        cluster_wait();
        {
            float acc[120];
            bool ok, prep;
            float2 s0, s1;
            uint32_t xa[5], cap[2] = {0u, 0u};
#pragma unroll
            for (uint32_t j = 0; j < 5; j++) {
                const uint32_t cg = 5 * hg + (j < 4 ? j + (hg & 1) : (~hg & 1) * 4);
                xa[j] = (sb + (warp * 16 + (lane & 15)) * 128 + (((lane >> 4) ^ (lane & 7)) << 4)) ^ ((cg & 3) << 5);
                const uint32_t i = cg >> 2, late = (i >= 5) ^ (k0 != 0), bit = 1u << (5 * (i >= 5 ? i - 5 : i) + j);
                cap[0] |= late ? 0u : bit; cap[1] |= late ? bit : 0u;
            }
            uint32_t sta = sb + M_ST + (warp * 16 + g) * 8;
            asm volatile("" : "+r"(sta), "+r"(cap[0]), "+r"(cap[1]), "+r"(xa[0]), "+r"(xa[1]), "+r"(xa[2]), "+r"(xa[3]), "+r"(xa[4]));
            mbar_wait(sb + B_FULL + 16, 0);
#pragma unroll
            for (uint32_t kb = 2; kb < 12; kb++) {
                const uint32_t s = kb & 3;
                const bool hold = kb == 12 - LEAD && p;
                if (hold) {
                    wgmma_wait<0>();
                    if (lane < 2) mbar_arrive_cl(empty_cl + 8 * ((11 - LEAD) & 3));
                    bar_sync(1, 256);
                }
                wgmma_fence();
                const uint32_t st = sbd + s * (ST >> 4);
#pragma unroll
                for (int ks = 0; ks < 4; ks++) {
                    const uint64_t da = mk(st + p * 512 + ks * 2 + 0x10000, HI128);
                    wgmma_n48_hi(acc, da, mk(st + (ST_BR >> 4) + (ks >> 1) * 192 + (ks & 1) * 32 + (64 << 16), HI32), ks || kb > 2);
                    wgmma_n192_lo(acc, da, mk(st + (ST_BM >> 4) + (ks >> 1) * 768 + (ks & 1) * 128 + (256 << 16), HI128), ks || kb > 2);
                    if (ks == 0) {
                        wgmma_commit();
                        wgmma_wait<1>();
                        if (!hold && kb > 2 && lane < 2) mbar_arrive_cl(empty_cl + 8 * ((kb - 1) & 3));
                    }
                    if (ks == 1) {
#pragma unroll
                        for (uint32_t j = 0; j < 5; j++)
                            if ((cap[kb >= 7] >> (5 * ((kb - 2) % 5) + j)) & 1) ldsm_x4(xr[j], xa[j] + s * ST);
                        if (w == 3 && kb < 7) stg128(halo + (kb - 2) * 512, 0u, 0u, 0u, 0u);
                        if (lane == 0 && kb == 2) stg32(flag, 0u);
                        if (kb < 11) ok = mbar_try(sb + B_FULL + 8 * ((kb + 1) & 3), ((kb - 1) >> 2) & 1);
                        if (kb == 10) prep = mbar_try(sb + B_PREP, 0) & mbar_try(sb + B_EMPTY, 1);
                        if (kb == 11 && prep) {
                            s0 = lds64f(sta); s1 = lds64f(sta + 64);
                            par = lds32(sb + M_SEL + 8);
                        }
                    }
                }
                wgmma_commit();
                if (kb < 11 && !ok) mbar_wait(sb + B_FULL + 8 * ((kb + 1) & 3), ((kb - 1) >> 2) & 1);
            }
            if (!prep) {
                mbar_wait(sb + B_EMPTY, 1);
                mbar_wait(sb + B_PREP, 0);
                s0 = lds64f(sta); s1 = lds64f(sta + 64);
                par = lds32(sb + M_SEL + 8);
            }
            {
                const uint32_t a0 = t ? 0u : __byte_perm(U(-s0.y), 0, 0x3232), a1 = t ? 0u : __byte_perm(U(-s1.y), 0, 0x3232);
                wgmma_fence();
                wgmma_rs_n48_hi(acc, a0, a1, 0u, 0u, mk(sbd + (M_CS >> 4) + 48, 2), 1);
                wgmma_rs_n192_lo(acc, a0, a1, 0u, 0u, mk(sbd + (M_CS >> 4), 2), 1);
                wgmma_commit();
            }
            if (!p) bar_arrive(1, 256);
            wgmma_wait<1>();
            if (lane < 2) mbar_arrive_cl(empty_cl + 24);
            wgmma_wait<0>();
#pragma unroll
            for (int i = 0; i < 120; i++) asm volatile("" : "+f"(acc[i]) :: "memory");
            TR(r12);
            uint32_t Q[10], Ql[10], KX[10], VX[10], Y[20];
#define KI(c) ((c) == 2 ? 8 : (c) == 7 ? 9 : (c) - ((c) > 2) - ((c) > 7))
#define KY(c) Y[KI(c)]
#define VY(c) Y[10 + (c)]
            uint32_t Z[20];
            const bool start = w == 0 && rb == 0, remote = w == 0 && rb != 0;
            const uint32_t slot = sb + OFF_X + warp * 2560 + lane * 16;
            {
                BOTH(_Pragma("unroll") for (int c = 0; c < 10; c++) {
                    const int jk = jt_of(1, c, odd), jv = jt_of(2, c, odd);
                    VY(c) = movm(pack_bf16(acc[4 * jv + 2] * s1.x, acc[4 * jv + 3] * s1.x));
                    KY(c) = pack_bf16(acc[4 * jk + 2] * s1.x, acc[4 * jk + 3] * s1.x);
                    asm volatile("" : "+r"(KY(c)), "+r"(VY(c)));
                })
                if (w == 3) {
#pragma unroll
                    for (int j = 0; j < 5; j++) {
                        Y[4 * j] = (Y[4 * j] & ~0x10001u) | par;
                        stg128(halo + j * 512, Y[4 * j], Y[4 * j + 1], Y[4 * j + 2], Y[4 * j + 3]);
                    }
                } else {
#pragma unroll
                    for (int j = 0; j < 5; j++) sts128(slot + 2560 + j * 512, Y[4 * j], Y[4 * j + 1], Y[4 * j + 2], Y[4 * j + 3]);
                }
                BOTH(_Pragma("unroll") for (int c = 0; c < 10; c++) {
                    const int jk = jt_of(1, c, odd), jv = jt_of(2, c, odd);
                    KX[c] = pack_bf16(acc[4 * jk] * s0.x, acc[4 * jk + 1] * s0.x);
                    VX[c] = movm(pack_bf16(acc[4 * jv] * s0.x, acc[4 * jv + 1] * s0.x));
                    asm volatile("" : "+r"(KX[c]), "+r"(VX[c]));
                })
                bar_sync(2 + p, 128);
                if (remote) {
#pragma unroll
                    for (int j = 0; j < 5; j++) ldg128(halo - 8 * XB + j * 512, Z[4 * j], Z[4 * j + 1], Z[4 * j + 2], Z[4 * j + 3]);
                } else {
#pragma unroll
                    for (int j = 0; j < 5; j++) {
                        const uint4 v = lds128(slot + (w ? 0 : 2560) + j * 512);
                        Z[4 * j] = v.x; Z[4 * j + 1] = v.y; Z[4 * j + 2] = v.z; Z[4 * j + 3] = v.w;
                    }
                }
                BOTH(_Pragma("unroll") for (int c = 0; c < 10; c++) {
                    const int jq = jt_of(0, c, odd);
                    Ql[c] = pack_bf16(acc[4 * jq], acc[4 * jq + 1]);
                    Q[c] = pack_bf16(acc[4 * jq + 2], acc[4 * jq + 3]);
                    asm volatile("" : "+r"(Ql[c]), "+r"(Q[c]));
                })
            }
            auto scores = [&](float (&l)[4], const uint32_t (&q)[10], const uint32_t (&z)[20], const int c0, const uint32_t mx, const float nz) {
                const uint32_t qa = t < 2 ? q[c0 + 2] : 0u, qb = t < 2 ? 0u : q[c0 + 2];
                float xa[4] = {0.f, 0.f, 0.f, 0.f}, za[4] = {nz, nz, nz, nz}, xb[4], zb[4];
                mma1688(xa, qa, qb, KX[c0 + 2]);
                mma1688(za, qa, qb, z[KI(c0 + 2)]);
#pragma unroll
                for (int e = 0; e < 4; e++) { xb[e] = xa[e]; zb[e] = za[e]; }
                mma16816(xa, q[c0], q[c0 + 3], q[c0 + 1], q[c0 + 4], KX[c0], KX[c0 + 1]);
                mma16816(za, q[c0], q[c0 + 3], q[c0 + 1], q[c0 + 4], z[KI(c0)], z[KI(c0 + 1)]);
                mma16816(xb, q[c0], q[c0 + 3], q[c0 + 1], q[c0 + 4], KX[c0 + 3], KX[c0 + 4]);
                mma16816(zb, q[c0], q[c0 + 3], q[c0 + 1], q[c0 + 4], z[KI(c0 + 3)], z[KI(c0 + 4)]);
                const bool h0 = mx & 1u, h1 = (int)mx < 0;
                l[0] = h0 ? xa[0] : za[0]; l[1] = h1 ? xa[1] : za[1];
                l[2] = h0 ? xb[2] : zb[2]; l[3] = h1 ? xb[3] : zb[3];
                asm volatile("" : "+f"(l[0]), "+f"(l[1]), "+f"(l[2]), "+f"(l[3]));
            };
            auto soft = [&](uint32_t (&pr)[2], const float (&l)[4], const float sq) {
                float m0 = fmaxf(l[0], l[1]), m1 = fmaxf(l[2], l[3]);
                m0 = fmaxf(m0, shx(m0, 1)); m1 = fmaxf(m1, shx(m1, 1));
                m0 = fmaxf(m0, shx(m0, 2)) * -sq; m1 = fmaxf(m1, shx(m1, 2)) * -sq;
                pr[0] = pack_bf16(ex2(fmaf(l[0], sq, m0)), ex2(fmaf(l[1], sq, m0)));
                pr[1] = pack_bf16(ex2(fmaf(l[2], sq, m1)), ex2(fmaf(l[3], sq, m1)));
                asm volatile("" : "+r"(pr[0]), "+r"(pr[1]));
            };
            auto values = [&](const uint32_t (&pr)[2], const uint32_t (&z)[20], const int c0, const uint32_t mx, const int h) {
                float dn[4] = {0.f, 0.f, 0.f, 0.f};
                mma1688(dn, pr[0], pr[1], 0x3F803F80u);
                const float i0 = rcp(dn[0]), i1 = rcp(dn[2]), i2 = t < 2 ? i0 : i1;
#pragma unroll
                for (int c = 0; c < 5; c++) {
                    float oc[4] = {0.f, 0.f, 0.f, 0.f};
                    mma16816(oc, pr[0] & mx, pr[1] & mx, pr[0] & ~mx, pr[1] & ~mx, VX[c0 + c], z[10 + c0 + c]);
                    const bool first = c < 2 || (c == 2 && t < 2);
                    const float iv = c < 2 ? i0 : (c > 2 ? i1 : i2);
                    A[0][2 * (c0 + c) + h] = pack_bf16((first ? oc[0] : oc[2]) * iv, (first ? oc[1] : oc[3]) * iv);
                    asm volatile("" : "+r"(A[0][2 * (c0 + c) + h]));
                }
            };
            auto gate = [&]() {
                const float r0 = 0.5f * s0.x, r1 = 0.5f * s1.x, n0 = -r0 * s0.y, n1 = -r1 * s1.y;
#pragma unroll
                for (int j = 0; j < 5; j++) {
#pragma unroll
                    for (int q = 0; q < 4; q++) {
                        const float v0 = fmaf(bflo(xr[j][q]), q & 1 ? r1 : r0, q & 1 ? n1 : n0), v1 = fmaf(bfhi(xr[j][q]), q & 1 ? r1 : r0, q & 1 ? n1 : n0);
                        gf[j][q] = pack_bf16(fmaf(v0, tanh_a(v0), v0), fmaf(v1, tanh_a(v1), v1));
                        asm volatile("" : "+r"(gf[j][q]));
                    }
                }
            };
            const uint32_t mo = (2 * t > g ? 0xFFFFu : 0u) | (2 * t + 1 > g ? 0xFFFF0000u : 0u);
            constexpr float SC = 0.22360679774997896f * LOG2E;
            {
                float l[4][4];
                uint32_t pr[4][2];
                unsigned spins = 0;
#pragma unroll 1
                while (remote && any((Z[0] & Z[4] & Z[8] & Z[12] & Z[16] & par) == 0u) && ++spins < SPIN) {
#pragma unroll
                    for (int j = 0; j < 5; j++) ldg128(halo - 8 * XB + j * 512, Z[4 * j], Z[4 * j + 1], Z[4 * j + 2], Z[4 * j + 3]);
                }
                TR(r32);
                const float nz = start ? -INFINITY : 0.f;
                scores(l[0], Q, Y, 0, mo, 0.f);
                scores(l[1], Q, Y, 5, mo, 0.f);
                scores(l[2], Ql, Z, 0, ~mo, nz);
                scores(l[3], Ql, Z, 5, ~mo, nz);
                soft(pr[0], l[0], s1.x * SC);
                soft(pr[1], l[1], s1.x * SC);
                soft(pr[2], l[2], s0.x * SC);
                soft(pr[3], l[3], s0.x * SC);
                values(pr[0], Y, 0, mo, 1);
                values(pr[1], Y, 5, mo, 1);
                if (lane == 0 && (EFB || !p) && A[0][EFR] != 0x12345678u) stg32(flag, par);
                values(pr[2], Z, 0, ~mo, 0);
                values(pr[3], Z, 5, ~mo, 0);
            }
#pragma unroll
            for (int j = 0; j < 5; j++) {
                A[0][4 * j] = (A[0][4 * j] & ~0x10001u) | par;
                stg128(orow + hg * XB + j * 512, A[0][4 * j], A[0][4 * j + 1], A[0][4 * j + 2], A[0][4 * j + 3]);
            }
            if (lane == 0) stg32(flag, par);
            TR(r34);
            if (p) bar_arrive(8, 384);
            BLOCK_SPLIT(par);
            gate();
        }
        {
            float acc2[40];
            unsigned spins = 0;
            bool again, first = true;
            const uint8_t* src[7];
#pragma unroll
            for (uint32_t i = 0; i < 7; i++) { src[i] = orow + (i >= hg ? XB : 0u); asm volatile("" : "+l"(src[i])); }
            mbar_wait(sb + B_SEL, 0);
            const float2 sel = lds64f(sb + M_SEL);
            uint32_t routed = (U(sel.x) >> 4) == warp || (U(sel.y) >> 4) == warp;
            asm volatile("" : "+r"(routed));
            BLOCK_SPLIT(par);
            if (p) bar_sync(9, 288); else bar_sync(5, 160);
#pragma unroll 1
            do {
#pragma unroll
                for (uint32_t i = 1; i < 5; i++)
#pragma unroll
                    for (int j = 0; j < 5; j++)
                        ldg128(src[i - 1] + (i - 1) * XB + j * 512, A[i][4 * j], A[i][4 * j + 1], A[i][4 * j + 2], A[i][4 * j + 3]);
                if (!p && first) bar_sync(8, 384);
                uint32_t mn = par;
#pragma unroll
                for (int i = 0; i < 8; i++) {
                    const uint32_t (&a)[20] = A[i % 5];
                    if (i == 3 && !p && first) bar_sync(6, 160);
                    wgmma_fence();
#pragma unroll
                    for (int j = 0; j < 5; j++) {
                        wgmma_rs_n80(acc2, a[4 * j], a[4 * j + 1], a[4 * j + 2], a[4 * j + 3],
                                     mk(sbd + ((OFF_WO + i * WO_SLOT) >> 4) + j * 64 + (320 << 16), HI64), i || j);
                        if (i == 7 && j == 2) {
#pragma unroll
                            for (int q = 0; q < 5; q++) mn &= A[q][0] & A[q][4] & A[q][8] & A[q][12] & A[q][16];
                            again = bar_or(2 + p, 128, mn == 0u && ++spins < SPIN);
                        }
                    }
                    if (i < 4 || i == 7) wgmma_commit();
                    if (i == SERAT && !p && first) bar_arrive(9, 288);
                    if (i == 0) TR(r22);
                    if (i >= 1 && i < 4) {
                        uint32_t (&n)[20] = A[i - 1];
                        if (i > 1) mn &= n[0] & n[4] & n[8] & n[12] & n[16];
                        const uint8_t* q = src[i + 3] + (i > 1 ? mn & 256u : 0u);
                        wgmma_wait<1>();
                        bar_arrive(10, 32);
#pragma unroll
                        for (int j = 0; j < 5; j++) ldg128(q + (i + 3) * XB + j * 512, n[4 * j], n[4 * j + 1], n[4 * j + 2], n[4 * j + 3]);
                        bar_arrive(10, 32);
                    }
                }
                first = false;
                if (again) {
                    wgmma_wait<0>();
#pragma unroll
                    for (int j = 0; j < 5; j++)
                        ldg128(orow + hg * XB + j * 512, A[0][4 * j], A[0][4 * j + 1], A[0][4 * j + 2], A[0][4 * j + 3]);
                }
            } while (again);
            const uint32_t o0 = (hg & 1) * 32, o4 = (~hg & 1) * 128;
            if (routed) {
                const float2 sel = lds64f(sb + M_SEL);
                mbar_wait(sb + B_UPD, 0);
#pragma unroll
                for (uint32_t h = 0; h < 2; h++) {
                    const uint32_t row = warp * 16 + g + 8 * h, ga = sb + M_UPD + (row == U(sel.x) ? 0 : 160) + t * 4;
                    if (row == U(sel.x) || row == U(sel.y)) {
#pragma unroll
                        for (int c = 0; c < 5; c++) { gf[c][h] = lds32(ga + (c < 4 ? o0 + c * 32 : o4)); gf[c][h + 2] = lds32(ga + (c < 4 ? o0 + c * 32 : o4) + 16); }
                    }
                }
                __syncwarp();
            }
            wgmma_wait<0>();
#pragma unroll
            for (int i = 0; i < 40; i++) asm volatile("" : "+f"(acc2[i]) :: "memory");
            TR(r44);
#pragma unroll
            for (int c = 0; c < 5; c++) {
#pragma unroll
                for (int q = 0; q < 4; q++)
                    asm("fma.rn.bf16x2 %0, %1, %2, %0;" : "+r"(xr[c][q]) : "r"(pack_bf16(acc2[8 * c + 2 * q], acc2[8 * c + 2 * q + 1])), "r"(gf[c][q]));
                stsm_x4(ta + (c < 4 ? o0 + c * 32 : o4) + OFF_X, xr[c]);
            }
            fence_proxy_async_smem();
            __syncwarp();
            if (lane == 0) {
                tma_st(&P.tm[T_OUT], sb + OFF_X + warp * 2560, hg * 80, rb * 64 + 16 * w, p);
                asm volatile("cp.async.bulk.wait_group.read 0;" ::: "memory");
            }
        }
        TS(46);
        TRW(r12, 12); TRW(r32, 32); TRW(r34, 34); TRW(r22, 22); TRW(r44, 44);
    } else if (warp >= 12) {
        asm volatile("setmaxnreg.dec.sync.aligned.u32 24;");
        if (warp == 12) {
            uint32_t slot = t0 + PACE0;
            if (elect()) {
#pragma unroll 1
                for (uint32_t kb = 1; kb < 10; kb++) {
                    const uint32_t s = (kb + 2) & 3;
                    const uint32_t st = sb + s * ST, fb = sb + B_FULL + 8 * s;
                    const uint32_t kc = kb * 64 + (kb < 5 ? k0 : -k0);
                    if (kb >= 4) {
                        mbar_wait(fb + 32, kb >> 3);
                        if (kb < 9) mbar_wait(sb + B_AX - 32 + 8 * kb, 0);
                    }
                    {
                        slot += PACE1;
#pragma unroll 1
                        while ((int)(clock32() - slot) < 0) { }
                        mbar_expect_tx(fb, ST);
                        tma(st, &P.tm[T_X], fb, kc, rb * 64);
                    }
                    tma_mc(st + ST_BM + rank * 12288, &P.tm[T_W], fb, hg * 80 + (hg & 1) * 16, kc + rank * 32);
                    tma_mc(st + ST_BR + rank * 3072, &P.tm[T_WR], fb, hg * 80 + 64 - (hg & 1) * 64, kc + rank * 32);
                }
                mbar_wait(sb + B_EMPTY, 1);
                mbar_expect_tx(sb + B_DN, 20480);
                tma(sb + OFF_DN, &P.tm[T_D], sb + B_DN, 0, 32 * fp, 5 * rank);
                uint32_t wb = sb + B_WO - 8;
#pragma unroll 1
                for (uint32_t i = 0; i < 8; i++) {
                    if ((0x49 >> i) & 1) {
                        wb += 8;
                        mbar_wait(wb - (B_WO - B_EMPTY - 8), i == 0);
                        mbar_expect_tx(wb, i < 6 ? 3 * 12800 : 2 * 12800);
                    }
                    if (WOP) {
#pragma unroll 1
                        while ((int)(clock32() - slot) < 0) { }
                        slot = clock32() + WOP;
                    }
                    const uint32_t d = sb + OFF_WO + i * WO_SLOT;
                    const uint32_t kr = 80 * (i ? i - (i <= hg) : hg);
                    tma_mc(d + rank * 5120, &P.tm[T_WO], wb, hg * 80 + (hg & 1) * 16 + rank * 32, kr);
                    tma_mc(d + 10240 + rank * 2560, &P.tm[T_WOR], wb, hg * 80 + (~hg & 1) * 64, kr + rank * 40);
                }
            }
        } else if (warp == 13) {
            if (elect()) {
#pragma unroll 1
                for (uint32_t i = 0; i < 3; i++) {
#pragma unroll 1
                    while (clock32() - t0 < PX0 + i * PX1) __nanosleep(20);
                    l2_prefetch(P.w + ((i + 2) * 245760 + b * 1920), 1920);
                    l2_prefetch(P.w + ((i + 7) * 245760 + b * 1920), 1920);
                }
#pragma unroll 1
                for (uint32_t i = 0; i < 14; i++) {
#pragma unroll 1
                    while (clock32() - t0 < GU0 + i * GU1) __nanosleep(20);
                    if (i < 10) l2_prefetch(P.wd + (i * 128 + b) * 1728, 1728);
                    else l2_prefetch(P.wo + ((i - 10) * 128 + b) * 1600, 1600);
                }
            }
        } else if (warp == 15) {
            const uint32_t lane = opaque_tid() & 31;
            const uint8_t* fl = P.scr + (G_FLAG + (rb * 8 + (lane & 7)) * XB + (lane >> 3) * 8);
            cluster_wait();
            mbar_wait(sb + B_PREP, 0);
            const uint32_t par = lds32(sb + M_SEL + 8);
            mbar_wait(sb + B_WO, 0);
            mbar_wait(sb + B_EMPTY + 24, 0);
            __nanosleep(WSL);
            unsigned spins = 0;
            uint2 f;
#pragma unroll 1
            do f = ldg64(fl); while (any(f.x != par) && ++spins < SPIN);
            bar_arrive(5, 160);
            TS(24);
            mbar_wait(sb + B_WO + 8, 0); mbar_wait(sb + B_WO + 16, 0);
            bar_arrive(6, 160);
#pragma unroll 1
            while (any(f.y != par) && ++spins < SPIN) f.y = ldg32(fl + 4);
            bar_arrive(9, 288);
            TS(25);
        } else {
            uint32_t slot = t0 + GT0;
            cluster_wait();
            if (elect()) {
#pragma unroll 1
                for (uint32_t i = 0; i < 20; i++) {
                    slot += GT1;
#pragma unroll 1
                    while ((int)(clock32() - slot) < 0) __nanosleep(20);
                    tma(sb + OFF_GU + i * 2048, &P.tm[T_GU], sb + B_GU, 32 * fp, rank * 320 + i * 16);
                }
            }
        }
    } else {
        asm volatile("setmaxnreg.dec.sync.aligned.u32 72;");
        const uint32_t at = opaque_tid() - 256, lane = at & 31, g = lane >> 2, t = lane & 3, c7 = lane & 7, aw = warp - 8;
        uint8_t* const yz = P.scr + (G_Y + b * 512 + at * 4);
        stg32(yz, 0u);
        __nanosleep(AUXS);
        const uint32_t epoch = ldg32(P.scr + G_EPOCH) + 1 + ldg32(yz), tag = (epoch & 15u) | 16u;
        const uint32_t empty_cl = mapa(sb + B_EMPTY, lane & 1);
        unsigned spins = 0;
        TRD(r51); TRD(r30); TRD(r52); TRD(r53); TRD(r54); TRD(r55); TRD(r20); TRD(r22);
        {
            const uint2 wv = __ldg(reinterpret_cast<const uint2*>(P.w_r + k0 * 2 + min(at, 79u) * 8));
            if (at < 80) sts64(sb + M_UPD + at * 8, wv.x, wv.y);
        }
        uint8_t* const stw = P.scr + (b * XB + G_ST + (lane & 4) * 64 + (at >> 3) * 16);
        uint8_t* const csw = P.scr + (b * XB + G_CS + at);
        uint8_t* const tpw = P.scr + (G_TOP + (hg >> 2) * XB + rb * 64 + aw * 16);
        const bool tpub = lane == 0 && (hg & 3) == 3;
        cluster_wait();
        bar_sync(4, 128);
        mbar_wait(sb + B_FULL + 16, 0);
        if (t == 0) { stg128(stw, 0u, 0u, 0u, 0u); stg32(csw, 0u); }
        if (tpub) stg128(tpw, 0u, 0u, 0u, 0u);

        uint32_t k1, sv;
        {
            const uint32_t xoff = (32 * (hg & 3) + (at >> 3)) * 128 + ((c7 ^ ((at >> 3) & 7)) << 4);
            const uint32_t jt = (rb >> 2) * 8 + rank * 4 + aw;
            const uint32_t coff = jt < 24 ? ST_BM + (jt >> 3) * 4096 + lane * 128 + (((jt ^ lane) & 7) << 4)
                                          : ST_BR + ((jt >> 1) & 3) * 1024 + lane * 32 + (((jt ^ g) & 1) << 4);
            float q[8], c8[8];
#pragma unroll
            for (int e = 0; e < 8; e++) q[e] = c8[e] = 0.f;
#pragma unroll 1
            for (uint32_t kb = 2; kb < 7; kb++) {
                const uint32_t st = sb + (kb & 3) * ST;
                const uint4 wv = lds128(sb + M_UPD - 256 + kb * 128 + c7 * 16);
                mbar_wait(sb + B_FULL + 8 * (kb & 3), kb == 6);
                const uint4 v = lds128(st + xoff), vn = lds128(st + xoff + 2048);
                const uint4 cv = lds128(st + coff), cn = lds128(st + coff + (jt < 24 ? 12288 : 3072));
                if (lane < 2) mbar_arrive_cl(empty_cl - (B_EMPTY + 16 - B_AX) + 8 * kb);
                const uint32_t u[4] = {v.x, v.y, v.z, v.w}, un[4] = {vn.x, vn.y, vn.z, vn.w}, ww[4] = {wv.x, wv.y, wv.z, wv.w};
                const uint32_t cc[4] = {cv.x, cv.y, cv.z, cv.w}, cd[4] = {cn.x, cn.y, cn.z, cn.w};
#pragma unroll
                for (int e = 0; e < 4; e++) {
                    const float a0 = bflo(u[e]), a1 = bfhi(u[e]), b0 = bflo(un[e]), b1 = bfhi(un[e]), w0 = bflo(ww[e]), w1 = bfhi(ww[e]);
                    q[0] += a0 + a1; q[4] += b0 + b1; q[3] += w0 + w1;
                    q[1] = fmaf(a0, a0, fmaf(a1, a1, q[1])); q[5] = fmaf(b0, b0, fmaf(b1, b1, q[5]));
                    q[2] = fmaf(a0, w0, fmaf(a1, w1, q[2])); q[6] = fmaf(b0, w0, fmaf(b1, w1, q[6]));
                    c8[2 * e] += bflo(cc[e]) + bflo(cd[e]); c8[2 * e + 1] += bfhi(cc[e]) + bfhi(cd[e]);
                }
            }
            TR(r51);
            q[7] = q[3];
#pragma unroll
            for (int e = 0; e < 4; e++) {
                q[e] = ((lane & 4) ? q[e + 4] : q[e]) + shx((lane & 4) ? q[e] : q[e + 4], 4);
                q[e] += shx(q[e], 1); q[e] += shx(q[e], 2);
            }
            const float mh = q[0] * (1.0f / 320);
            if (t == 0) stg128(stw, U(mh), U(fmaf(-mh, q[0], q[1])), U(q[2]), (U(q[3]) & ~31u) | tag);
#define TSTEP(H) { const bool up = (lane & (4 * H)) != 0; _Pragma("unroll") for (int e = 0; e < H; e++) { \
            const float send = up ? c8[e] : c8[e + H]; const float keep = up ? c8[e + H] : c8[e]; \
            c8[e] = keep + shx(send, 4 * H); } }
            TSTEP(4) TSTEP(2) TSTEP(1)
#undef TSTEP
            c8[0] += shx(c8[0], 1); c8[0] += shx(c8[0], 2);
            if (t == 0) stg32(csw, (U(c8[0]) & ~31u) | tag);
            TR(r30);
            const uint8_t* csp = P.scr + (G_CS + (aw * 32 + (lane >> 4) * 8 + hg) * XB + (lane & 15) * 8);
            const uint8_t* stp = P.scr + (G_ST + (rb * 8 + aw) * XB + lane * 16);
            uint32_t ra[4], rc[4];
            uint2 ca, cc;
#pragma unroll 1
            while (clock32() - t0 < EX1T) __nanosleep(20);
#pragma unroll 1
            do {
                ldg128(stp, ra[0], ra[1], ra[2], ra[3]);
                ldg128(stp + 4 * XB, rc[0], rc[1], rc[2], rc[3]);
                ca = ldg64(csp); cc = ldg64(csp + 16 * XB);
            } while (any((ra[3] ^ tag | rc[3] ^ tag) & 31u) && ++spins < SPIN);
            TR(r20);
            const float dm = 0.5f * (F(ra[0]) - F(rc[0])), m = bf16r(F(rc[0]) + dm);
            const float sd = bf16r(sqrt_a(bf16r(bf16r(fmaxf(fmaf(dm, dm, (F(ra[1]) + F(rc[1])) * (1.0f / DM)), 0.f)) + 1e-5f)));
            const float rs = rcp(sd);
            uint32_t w1, w2;
            if ((hg & 3) == 3) {
                k1 = pack_bf16(0.f, fmaf(-m, F(ra[3]) + F(rc[3]), F(ra[2]) + F(rc[2])) * rs);
                k1 ^= ((int)k1 >> 31) | 0x80000000u;
                k1 = (k1 & 0xFFFF0000u) | ((2047 - (rb * 128 + 2 * (at & 63) + (at >> 6))) << 5) | tag;
                w1 = redux_max(k1); w2 = redux_max(k1 == w1 ? 0u : k1);
                sv = U(m) | (U(sd) >> 16);
                const uint32_t v1 = redux_max(k1 == w1 ? sv : 0u), v2 = redux_max(k1 == w2 ? sv : 0u);
                if (lane == 0) stg128(tpw, w1, v1, w2, v2);
            }
            sts64(sb + M_ST + at * 8, U(rs), U(m));
            sts32(sb + M_SEL + 8, (tag & 1) ? 1u : 0x10000u);
#pragma unroll 1
            while (any((ca.x ^ tag | ca.y ^ tag | cc.x ^ tag | cc.y ^ tag) & 31u) && ++spins < SPIN) { ca = ldg64(csp); cc = ldg64(csp + 16 * XB); }
            {
                const float c0 = at < 120 ? F(ca.x) + F(cc.x) : 0.f, c1 = at < 120 ? F(ca.y) + F(cc.y) : 0.f;
                const uint32_t hi = pack_bf16(c0, c1);
                sts32(sb + M_CS + (at >> 2) * 32 + t * 4, hi);
                sts32(sb + M_CS + (at >> 2) * 32 + t * 4 + 16, pack_bf16(c0 - bflo(hi), c1 - bfhi(hi)));
                fence_proxy_async_smem();
                __syncwarp();
                if (lane < 2) mbar_arrive(sb + B_PREP);
            }
            TR(r52);
            if (aw == 0) {
                uint32_t ka[4], kb[4];
#pragma unroll 1
                while (clock32() - t0 < EX1T + EX2D) __nanosleep(20);
#pragma unroll 1
                do {
                    const uint8_t* tp = P.scr + (G_TOP + lane * 16);
                    uint32_t kc[4], kd[4];
                    ldg128(tp, ka[0], ka[1], ka[2], ka[3]);
                    ldg128(tp + 512, kb[0], kb[1], kb[2], kb[3]);
                    ldg128(tp + XB, kc[0], kc[1], kc[2], kc[3]);
                    ldg128(tp + XB + 512, kd[0], kd[1], kd[2], kd[3]);
                    const bool ba = (ka[0] ^ tag) & 31u, bb = (kb[0] ^ tag) & 31u;
#pragma unroll
                    for (int e = 0; e < 4; e++) { ka[e] = ba ? kc[e] : ka[e]; kb[e] = bb ? kd[e] : kb[e]; }
                } while (any((ka[0] ^ tag | kb[0] ^ tag) & 31u) && ++spins < SPIN);
                TR(r22);
                if (kb[0] > ka[0]) {
#pragma unroll
                    for (int e = 0; e < 4; e++) { const uint32_t x = ka[e]; ka[e] = kb[e]; kb[e] = x; }
                }
                if (kb[0] > ka[2]) { ka[2] = kb[0]; ka[3] = kb[1]; }
                w1 = redux_max(ka[0]);
                const uint32_t t1 = redux_max(ka[0] == w1 ? ka[1] : 0u);
                if (ka[0] == w1) { ka[0] = ka[2]; ka[1] = ka[3]; }
                w2 = redux_max(ka[0]);
                const uint32_t t3 = redux_max(ka[0] == w2 ? ka[1] : 0u);
                sts128(sb + M_TOP, w1, t1, w2, t3);
            }
            bar_sync(4, 128);
            const float2 tv = lds64f(sb + M_TOP + (lane & 1) * 8);
            k1 = U(tv.x);
            sv = U(tv.y);
        }
        TR(r53);
        const uint32_t tok = ~(k1 >> 5) & 2047;
        const unsigned owns = __ballot_sync(0xffffffffu, (tok >> 7) == rb) & 3u;
        if (at < 2) sts32(sb + M_SEL + at * 4, (tok >> 7) == rb ? (tok & 1) * 64 + ((tok & 127) >> 1) : ~0u);
        if ((at | b) == 0) *reinterpret_cast<uint32_t*>(P.scr + G_EPOCH) = epoch;
        __syncwarp();
        if (at == 0) mbar_arrive(sb + B_SEL);
        if (fp < NFFN / 2) {
            uint4 xv = __ldg(reinterpret_cast<const uint4*>(P.x + (tok * 1280 + rank * 640 + min(at >> 1, 39u) * 16)));
            const uint32_t m2 = __byte_perm(sv, 0, 0x3232);
            asm("sub.rn.bf16x2 %0, %0, %4;\nsub.rn.bf16x2 %1, %1, %4;\nsub.rn.bf16x2 %2, %2, %4;\nsub.rn.bf16x2 %3, %3, %4;"
                : "+r"(xv.x), "+r"(xv.y), "+r"(xv.z), "+r"(xv.w) : "r"(m2));
            mbar_wait(sb + B_DN, 0);
            if (at < 80) sts128(sb + OFF_PART + at * 16, xv.x, xv.y, xv.z, xv.w);
            mbar_wait(sb + B_GU, 0);
            mbar_wait(sb + B_EMPTY + 24, 0);
            bar_sync(4, 128);
            float c[5][4];
            uint32_t wf[10][4];
#pragma unroll
            for (int i = 0; i < 5; i++) c[i][0] = c[i][1] = c[i][2] = c[i][3] = 0.f;
            const uint32_t mi = lane >> 3, kr = c7 + (mi >> 1) * 8;
            {
                const uint32_t wa = sb + OFF_GU + (aw >> 1) * 1024 + kr * 64 + ((((aw & 1) * 2 + (mi & 1)) ^ ((kr >> 1) & 3)) << 4);
#pragma unroll
                for (uint32_t i = 0; i < NPRE; i++) ldsm_x4_t(wf[i], wa + i * 2048);
                __nanosleep(FFNS);
                BLOCK_SPLIT(tag);
#pragma unroll
                for (uint32_t i = 0; i < 20; i += 2) {
                    uint32_t xb[4];
                    ldsm_x4(xb, sb + OFF_PART + i * 64 + mi * 32 + (lane & 1) * 16);
#pragma unroll
                    for (uint32_t j = i; j < i + 2; j++) {
                        const uint32_t (&a)[4] = wf[j % NPRE];
                        mma16816(c[j & 1], a[0], a[1], a[2], a[3], xb[2 * (j & 1)], xb[2 * (j & 1) + 1]);
                        if (j + NPRE < 20) ldsm_x4_t(wf[j % NPRE], wa + (j + NPRE) * 2048);
                    }
                }
#pragma unroll
                for (int e = 0; e < 4; e++) c[0][e] += c[1][e];
                const uint32_t rd = mapa(sb, rank ^ (t & 1));
                if (t < 2)
                    asm volatile("st.async.shared::cluster.mbarrier::complete_tx::bytes.v4.f32 [%0], {%1,%2,%3,%4}, [%5];"
                                 :: "r"(rd + (t ? OFF_PART + 1280 : M_UPD + 192) + aw * 128 + g * 16), "f"(c[0][0]), "f"(c[0][1]), "f"(c[0][2]), "f"(c[0][3]), "r"(rd + B_H) : "memory");
            }
            TR(r54);
            const float rs = rcp(bflo(sv));
            const uint32_t da = sb + OFF_DN + kr * 128 + (((2 * aw + (mi & 1)) ^ c7) << 4);
            uint8_t* yp = P.scr + (G_Y + (fp % 6) * 10240 + rank * 2560 + t * 512 + aw * 128 + g * 16);
#pragma unroll
            for (int i = 0; i < 5; i++) c[i][0] = c[i][1] = c[i][2] = c[i][3] = 0.f;
#pragma unroll
            for (uint32_t j = 0; j < NPD; j++) ldsm_x4_t(wf[j], da + (j % 5) * 4096 + (j / 5) * 2048);
            mbar_wait(sb + B_H, 0);
#pragma unroll
            for (uint32_t ks = 0; ks < 2; ks++) {
                const uint32_t og = sb + ks * 128 + lane * 4 + P.up_first, ou = og ^ 256;
                const float gs = bf16r((F(lds32(og + M_UPD + 192)) + F(lds32(og + OFF_PART + 1280))) * rs);
                const float h = bf16r(gs * sigm(gs)) * bf16r((F(lds32(ou + M_UPD + 192)) + F(lds32(ou + OFF_PART + 1280))) * rs);
                const uint32_t hp = pack_bf16(h, __shfl_down_sync(0xffffffffu, h, 4));
                const uint32_t h0 = __shfl_sync(0xffffffffu, hp, t * 8 + (g & 1)), h1 = __shfl_sync(0xffffffffu, hp, t * 8 + (g & 1) + 2);
#pragma unroll
                for (uint32_t j = 0; j < 5; j++) {
                    uint32_t (&a)[4] = wf[ks * 5 + j];
                    if (ks * 5 + j >= NPD) ldsm_x4_t(a, da + j * 4096 + ks * 2048);
                    mma16816(c[j], a[0], a[1], a[2], a[3], h0, h1);
                }
            }
#pragma unroll
            for (int e = 0; e < 4; e++) {
                const float lo = (t & 1) ? c[1][e] : c[0][e], hi = (t & 1) ? c[3][e] : c[2][e];
                c[0][e] = (t & 2) ? hi : lo;
            }
            asm volatile("" : "+f"(c[0][0]), "+f"(c[4][0]) :: "memory");
            BLOCK_SPLIT(tag);
            bar_sync(8, 384);
            if (REDS) __nanosleep(REDS);
            { red4(yp, c[0][0], c[0][2]); red4(yp + 5120, c[0][1], c[0][3]); }
            if (t == 0) { red4(yp + 2048, c[4][0], c[4][2]); red4(yp + 2048 + 5120, c[4][1], c[4][3]); }
            TR(r55);
        }
        else bar_arrive(8, 384);
        mbar_wait(sb + B_DN, 0); mbar_wait(sb + B_GU, 0);
        TRW(r51, 51); TRW(r30, 30); TRW(r52, 52); TRW(r53, 53); TRW(r54, 54); TRW(r55, 55); TRW(r20, 20); TRW(r22, 22);
        if (owns) {
            const uint32_t u = min(at >> 1, 39u), col = (u >> 3) * 32 + (u & 7) * 2;
            const bool mine = (tok >> 7) == rb && at < 80;
            k1 ^= ((~(int)k1) >> 31) | 0x80000000u;
            const float sg = bf16r(sigm(bfhi(k1))), rs = rcp(bflo(sv));
            uint32_t x0, x1, y0, y1, n0, n1;
            asm volatile("ld.global.nc.u16 %0, [%2];\nld.global.nc.u16 %1, [%2 + 16];" : "=r"(x0), "=r"(x1) : "l"(P.x + (tok * 1280 + hg * 160 + col)));
            const float a0 = (bflo(x0) - bfhi(sv)) * rs, a1 = (bflo(x1) - bfhi(sv)) * rs;
            bar_sync(4, 128);
#pragma unroll 1
            do {
                __nanosleep(YSL);
                uint32_t v[6][4];
#pragma unroll
                for (int r = 0; r < 6; r++) if (mine) ldg128(P.scr + (G_Y + (at & 1) * 5120 + hg * 640 + u * 16) + r * 10240, v[r][0], v[r][1], v[r][2], v[r][3]);
                y0 = U(((F(v[0][0]) + F(v[1][0])) + (F(v[2][0]) + F(v[3][0]))) + (F(v[4][0]) + F(v[5][0])));
                y1 = U(((F(v[0][1]) + F(v[1][1])) + (F(v[2][1]) + F(v[3][1]))) + (F(v[4][1]) + F(v[5][1])));
                n0 = U(((F(v[0][2]) + F(v[1][2])) + (F(v[2][2]) + F(v[3][2]))) + (F(v[4][2]) + F(v[5][2])));
                n1 = U(((F(v[0][3]) + F(v[1][3])) + (F(v[2][3]) + F(v[3][3]))) + (F(v[4][3]) + F(v[5][3])));
            } while (any(mine && (F(n0) != NFFN / 2 || F(n1) != NFFN / 2)) && ++spins < SPIN);
            const float v0 = a0 + bf16r(bf16r(F(y0)) * sg), v1 = a1 + bf16r(bf16r(F(y1)) * sg);
            const uint32_t gp = pack_bf16(v0 * sigm(v0), v1 * sigm(v1));
            if (mine) asm volatile("st.shared.u16 [%0], %1;\nst.shared.u16 [%0 + 16], %2;" :: "r"(sb + M_UPD + (at & 1) * 160 + col), "r"(gp), "r"(gp >> 16) : "memory");
            __syncwarp();
            if (lane < 2) mbar_arrive(sb + B_UPD);
            TS(56);
        }
    }
}

typedef CUresult (*EncodeFn)(CUtensorMap*, CUtensorMapDataType, cuuint32_t, void*, const cuuint64_t*, const cuuint64_t*,
                             const cuuint32_t*, const cuuint32_t*, CUtensorMapInterleave, CUtensorMapSwizzle,
                             CUtensorMapL2promotion, CUtensorMapFloatOOBfill);

bool encode(EncodeFn fn, CUtensorMap* tm, const void* ptr, cuuint64_t d0, cuuint64_t d1, cuuint64_t d2, cuuint64_t s1, cuuint64_t s2,
            cuuint32_t b0, cuuint32_t b1, cuuint32_t b2, CUtensorMapSwizzle sw) {
    const cuuint64_t dims[3] = {d0, d1, d2}, strides[2] = {s1, s2};
    const cuuint32_t box[3] = {b0, b1, b2}, es[3] = {1, 1, 1};
    return fn(tm, CU_TENSOR_MAP_DATA_TYPE_BFLOAT16, 3, const_cast<void*>(ptr), dims, strides, box, es,
              CU_TENSOR_MAP_INTERLEAVE_NONE, sw, CU_TENSOR_MAP_L2_PROMOTION_L2_128B,
              CU_TENSOR_MAP_FLOAT_OOB_FILL_NONE) == CUDA_SUCCESS;
}

}

extern "C" void kernel_launch(void* const* d_in, const int* in_sizes, int n_in, void* d_out, int out_size) {
    static Params P;
    static bool by_sm = false;
    static const void* cached[9] = {};
    bool same = cached[8] == d_out;
    for (int i = 0; i < 8; i++) same = same && cached[i] == d_in[i];
    if (!same) {
        const void *x = d_in[0], *wqkv = d_in[1], *wo = d_in[2], *wg = d_in[5], *wu = d_in[6], *wd = d_in[7];
        void* fnp = nullptr;
        cudaDriverEntryPointQueryResult qr;
        cudaGetDriverEntryPoint("cuTensorMapEncodeTiled", &fnp, cudaEnableDefault, &qr);
        EncodeFn fn = (EncodeFn)fnp;
        const CUtensorMapSwizzle S0 = CU_TENSOR_MAP_SWIZZLE_NONE, S32 = CU_TENSOR_MAP_SWIZZLE_32B, S64 = CU_TENSOR_MAP_SWIZZLE_64B,
                                 S128 = CU_TENSOR_MAP_SWIZZLE_128B;
        const bool ok = fn != nullptr &&
            encode(fn, &P.tm[T_X], x, 640, 1024, 2, 2560, 1280, 64, 64, 2, S128) &&
            encode(fn, &P.tm[T_OUT], d_out, 640, 1024, 2, 2560, 1280, 80, 16, 1, S0) &&
            encode(fn, &P.tm[T_W], wqkv, 640, 640, 3, 3840, 1280, 64, 32, 3, S128) &&
            encode(fn, &P.tm[T_WR], wqkv, 640, 640, 3, 3840, 1280, 16, 32, 3, S32) &&
            encode(fn, &P.tm[T_GU], wg < wu ? wg : wu, 1728, 640, 2, 3456, wg < wu ? (const char*)wu - (const char*)wg : (const char*)wg - (const char*)wu,
                   32, 16, 2, S64) &&
            encode(fn, &P.tm[T_D], wd, 64, 1728, 10, 1280, 128, 64, 32, 5, S128) &&
            encode(fn, &P.tm[T_WO], wo, 640, 640, 1, 1280, 1280 * 640, 32, 80, 1, S64) &&
            encode(fn, &P.tm[T_WOR], wo, 640, 640, 1, 1280, 1280 * 640, 16, 40, 1, S64);
        if (!ok) return;
        P.up_first = wg < wu ? 0 : 256;
        P.wo = (const uint8_t*)wo; P.wd = (const uint8_t*)wd;
        P.x = (const uint8_t*)x; P.w = (const uint8_t*)wqkv; P.w_r = (const uint8_t*)d_in[4];
        if (cudaGetSymbolAddress((void**)&P.scr, g_scr) != cudaSuccess) return;
        cudaFuncSetAttribute(fused_kernel<true>, cudaFuncAttributeMaxDynamicSharedMemorySize, SMEM_BYTES);
        cudaFuncSetAttribute(fused_kernel<false>, cudaFuncAttributeMaxDynamicSharedMemorySize, SMEM_BYTES);
        int ncl = 0, sms = 0, dev = 0;
        {
            cudaLaunchConfig_t cfg = {};
            cfg.gridDim = dim3(128); cfg.blockDim = dim3(NTHREADS); cfg.dynamicSmemBytes = SMEM_BYTES;
            cudaLaunchAttribute at[1];
            at[0].id = cudaLaunchAttributeClusterDimension;
            at[0].val.clusterDim.x = 2; at[0].val.clusterDim.y = 1; at[0].val.clusterDim.z = 1;
            cfg.attrs = at; cfg.numAttrs = 1;
            if (cudaOccupancyMaxActiveClusters(&ncl, fused_kernel<true>, &cfg) != cudaSuccess || ncl < 64) return;
            cudaGetDevice(&dev);
            cudaDeviceGetAttribute(&sms, cudaDevAttrMultiProcessorCount, dev);
        }
        by_sm = sms == 132 && ncl == 66;
        for (int i = 0; i < 8; i++) cached[i] = d_in[i];
        cached[8] = d_out;
    }
    if (by_sm) fused_kernel<true><<<132, NTHREADS, SMEM_BYTES>>>(P);
    else fused_kernel<false><<<128, NTHREADS, SMEM_BYTES>>>(P);
}
```

```cpp
#include <cuda_runtime.h>
#include <cuda_bf16.h>
#include <cuda.h>
#include <stdint.h>

namespace {

constexpr int DM = 640;
constexpr int NTHREADS = 512;
constexpr int NFFN = 108;
#define LEAD 2
#define PACE0 100
#define PACE1 950
#define PX0 1500
#define PX1 500
#define GU0 6000
#define GU1 220
#define GT0 2300
#define GT1 430
#define WOP 150
#define AUXS 500
#define EX1T 8100
#define EX2D 2500
#define SERAT 2
#define FFNS 400
#define NPRE 8
#define NPD 8
#define YSL 100
#define WSL 300

constexpr int ST = 47104;
constexpr int ST_BM = 16384, ST_BR = 40960;
constexpr int OFF_DN = 0;
constexpr int OFF_PART = 20480;
constexpr int OFF_WO = 22528;
constexpr int WO_SLOT = 15360;
constexpr int OFF_HO = 3 * ST;
__host__ __device__ constexpr int wo_slot(int i) { return i < 7 ? OFF_WO + i * WO_SLOT : 3 * ST + ST_BM; }
constexpr int OFF_GU = 4 * ST;
constexpr int M_ST = OFF_GU + 40960;
constexpr int M_CS = M_ST + 1024;
constexpr int M_UPD = M_CS + 1024;
constexpr int M_TOP = M_UPD + 640;
constexpr int M_SEL = M_TOP + 64;
constexpr int B_AX = M_SEL + 16, B_PREP = B_AX + 40, B_UPD = B_PREP + 8,
              B_GU = B_AX + 64, B_DN = B_GU + 8, B_H = B_DN + 8, B_SEL = B_H + 8,
              B_FULL = B_GU + 32, B_EMPTY = B_FULL + 32, B_WO = B_EMPTY + 32;
constexpr int SMEM_BYTES = B_WO + 32;
static_assert(SMEM_BYTES <= 232448 && wo_slot(1) <= ST && wo_slot(4) <= 2 * ST && wo_slot(6) + WO_SLOT <= 3 * ST, "smem");

enum { T_X, T_W, T_WR, T_GU, T_D, T_WO, T_WOR, T_OUT, T_N };
struct Params {
    CUtensorMap tm[T_N];
    const uint8_t* x;
    const uint8_t* w_r;
    const uint8_t* w;
    const uint8_t* wo;
    const uint8_t* wd;
    uint8_t* scr;
    uint32_t up_first;
};

constexpr uint32_t XB = 27392;
constexpr uint32_t G_TOP = 25600;
constexpr uint32_t G_CS = G_TOP + 1024;
constexpr uint32_t G_ST = G_CS + 128;
constexpr uint32_t G_FLAG = G_ST + 512;
constexpr uint32_t G_Y = 128 * XB;
constexpr uint32_t G_EPOCH = G_Y + 128 * 512;
static_assert(G_FLAG + 128 == XB, "scratch");
__device__ __align__(1024) uint8_t g_scr[G_EPOCH + 1024];

#define TR(v)
#define TRD(v)
#define TRW(v, i)
#define TS(i)
#define TSG(i)
constexpr unsigned SPIN = 1u << 20;

__device__ __forceinline__ void mbar_init(uint32_t bar, int cnt) {
    asm volatile("mbarrier.init.shared::cta.b64 [%0], %1;" :: "r"(bar), "r"(cnt) : "memory");
}
__device__ __forceinline__ void mbar_expect_tx(uint32_t bar, int bytes) {
    asm volatile("mbarrier.arrive.expect_tx.shared::cta.b64 _, [%0], %1;" :: "r"(bar), "r"(bytes) : "memory");
}
__device__ __forceinline__ void mbar_arrive(uint32_t bar) {
    asm volatile("mbarrier.arrive.shared::cta.b64 _, [%0];" :: "r"(bar) : "memory");
}
__device__ __forceinline__ uint32_t mapa(uint32_t a, uint32_t cta) {
    uint32_t r;
    asm("mapa.shared::cluster.u32 %0, %1, %2;" : "=r"(r) : "r"(a), "r"(cta));
    return r;
}
__device__ __forceinline__ void mbar_arrive_cl(uint32_t cbar) {
    asm volatile("mbarrier.arrive.shared::cluster.b64 _, [%0];" :: "r"(cbar) : "memory");
}
__device__ __forceinline__ void mbar_wait(uint32_t bar, int parity) {
    asm volatile("{\n.reg .pred p;\nLAB_WAIT:\nmbarrier.try_wait.parity.shared::cta.b64 p, [%0], %1;\n@!p bra LAB_WAIT;\n}"
                 :: "r"(bar), "r"(parity) : "memory");
}
__device__ __forceinline__ bool mbar_try(uint32_t bar, int parity) {
    uint32_t r;
    asm volatile("{\n.reg .pred p;\nmbarrier.test_wait.parity.shared::cta.b64 p, [%1], %2;\nselp.u32 %0, 1, 0, p;\n}"
                 : "=r"(r) : "r"(bar), "r"(parity) : "memory");
    return r != 0;
}
__device__ __forceinline__ void tma(uint32_t dst, const CUtensorMap* tm, uint32_t bar, int c0, int c1, int c2 = 0) {
    asm volatile("cp.async.bulk.tensor.3d.shared::cluster.global.mbarrier::complete_tx::bytes [%0], [%1, {%3, %4, %5}], [%2];"
                 :: "r"(dst), "l"(tm), "r"(bar), "r"(c0), "r"(c1), "r"(c2) : "memory");
}
__device__ __forceinline__ void tma_mc(uint32_t dst, const CUtensorMap* tm, uint32_t bar, int c0, int c1) {
    asm volatile("cp.async.bulk.tensor.3d.shared::cluster.global.mbarrier::complete_tx::bytes.multicast::cluster [%0], [%1, {%3, %4, %5}], [%2], %6;"
                 :: "r"(dst), "l"(tm), "r"(bar), "r"(c0), "r"(c1), "r"(0), "h"((uint16_t)3) : "memory");
}
__device__ __forceinline__ void tma_st(const CUtensorMap* tm, uint32_t src, int c0, int c1, int c2) {
    asm volatile("cp.async.bulk.tensor.3d.global.shared::cta.bulk_group [%0, {%2, %3, %4}], [%1];\ncp.async.bulk.commit_group;"
                 :: "l"(tm), "r"(src), "r"(c0), "r"(c1), "r"(c2) : "memory");
}
__device__ __forceinline__ void l2_prefetch(const void* p, int bytes) {
    asm volatile("cp.async.bulk.prefetch.L2.global [%0], %1;" :: "l"(p), "r"(bytes) : "memory");
}
__device__ __forceinline__ void cluster_arrive() { asm volatile("barrier.cluster.arrive.relaxed.aligned;" ::: "memory"); }
__device__ __forceinline__ void cluster_wait() { asm volatile("barrier.cluster.wait.aligned;" ::: "memory"); }
__device__ __forceinline__ void bar_sync(int id, int n) { asm volatile("bar.sync %0, %1;" :: "r"(id), "r"(n) : "memory"); }
__device__ __forceinline__ void bar_arrive(int id, int n) { asm volatile("bar.arrive %0, %1;" :: "r"(id), "r"(n) : "memory"); }
__device__ __forceinline__ bool bar_or(int id, int n, bool v) {
    uint32_t r;
    asm volatile("{\n.reg .pred p, q;\nsetp.ne.u32 p, %3, 0;\nbar.red.or.pred q, %1, %2, p;\nselp.u32 %0, 1, 0, q;\n}"
                 : "=r"(r) : "r"(id), "r"(n), "r"((uint32_t)v) : "memory");
    return r != 0;
}
__device__ __forceinline__ void fence_proxy_async_smem() { asm volatile("fence.proxy.async.shared::cta;" ::: "memory"); }
__device__ __forceinline__ void stg128(void* p, uint32_t a, uint32_t b, uint32_t c, uint32_t d) {
    asm volatile("{\n.reg .b64 l, h;\n.reg .b128 q;\nmov.b64 l, {%1, %2};\nmov.b64 h, {%3, %4};\nmov.b128 q, {l, h};\n"
                 "st.relaxed.gpu.global.b128 [%0], q;\n}" :: "l"(p), "r"(a), "r"(b), "r"(c), "r"(d) : "memory");
}
__device__ __forceinline__ void ldg128(const void* p, uint32_t& a, uint32_t& b, uint32_t& c, uint32_t& d) {
    asm volatile("{\n.reg .b64 l, h;\n.reg .b128 q;\nld.relaxed.gpu.global.b128 q, [%4];\nmov.b128 {l, h}, q;\n"
                 "mov.b64 {%0, %1}, l;\nmov.b64 {%2, %3}, h;\n}" : "=r"(a), "=r"(b), "=r"(c), "=r"(d) : "l"(p) : "memory");
}
__device__ __forceinline__ void red4(void* p, float a, float b) {
    asm volatile("red.relaxed.gpu.global.add.v4.f32 [%0], {%1, %2, %3, %3};" :: "l"(p), "f"(a), "f"(b), "f"(1.0f) : "memory");
}
__device__ __forceinline__ void stg32(void* p, uint32_t a) {
    asm volatile("st.relaxed.gpu.global.u32 [%0], %1;" :: "l"(p), "r"(a) : "memory");
}
__device__ __forceinline__ uint2 ldg64(const void* p) {
    uint2 v;
    asm volatile("{\n.reg .b64 l;\nld.relaxed.gpu.global.b64 l, [%2];\nmov.b64 {%0, %1}, l;\n}" : "=r"(v.x), "=r"(v.y) : "l"(p) : "memory");
    return v;
}
__device__ __forceinline__ unsigned ldg32(const void* p) {
    unsigned v;
    asm volatile("ld.relaxed.gpu.global.u32 %0, [%1];" : "=r"(v) : "l"(p) : "memory");
    return v;
}
__device__ __forceinline__ void ldsm_x4(uint32_t (&r)[4], uint32_t a) {
    asm volatile("ldmatrix.sync.aligned.m8n8.x4.shared.b16 {%0,%1,%2,%3}, [%4];"
                 : "=r"(r[0]), "=r"(r[1]), "=r"(r[2]), "=r"(r[3]) : "r"(a));
}
__device__ __forceinline__ void ldsm_x4_t(uint32_t (&r)[4], uint32_t a) {
    asm volatile("ldmatrix.sync.aligned.m8n8.x4.trans.shared.b16 {%0,%1,%2,%3}, [%4];"
                 : "=r"(r[0]), "=r"(r[1]), "=r"(r[2]), "=r"(r[3]) : "r"(a));
}
__device__ __forceinline__ void stsm_x4(uint32_t a, const uint32_t (&r)[4]) {
    asm volatile("stmatrix.sync.aligned.m8n8.x4.shared.b16 [%0], {%1,%2,%3,%4};"
                 :: "r"(a), "r"(r[0]), "r"(r[1]), "r"(r[2]), "r"(r[3]));
}
__device__ __forceinline__ uint32_t movm(uint32_t a) {
    uint32_t d;
    asm("movmatrix.sync.aligned.m8n8.trans.b16 %0, %1;" : "=r"(d) : "r"(a));
    return d;
}
__device__ __forceinline__ void mma16816(float (&c)[4], uint32_t a0, uint32_t a1, uint32_t a2, uint32_t a3, uint32_t b0, uint32_t b1) {
    asm("mma.sync.aligned.m16n8k16.row.col.f32.bf16.bf16.f32 {%0,%1,%2,%3}, {%4,%5,%6,%7}, {%8,%9}, {%0,%1,%2,%3};"
        : "+f"(c[0]), "+f"(c[1]), "+f"(c[2]), "+f"(c[3]) : "r"(a0), "r"(a1), "r"(a2), "r"(a3), "r"(b0), "r"(b1));
}
__device__ __forceinline__ void mma1688(float (&c)[4], uint32_t a0, uint32_t a1, uint32_t b0) {
    asm("mma.sync.aligned.m16n8k8.row.col.f32.bf16.bf16.f32 {%0,%1,%2,%3}, {%4,%5}, {%6}, {%0,%1,%2,%3};"
        : "+f"(c[0]), "+f"(c[1]), "+f"(c[2]), "+f"(c[3]) : "r"(a0), "r"(a1), "r"(b0));
}
__device__ __forceinline__ void wgmma_fence() { asm volatile("wgmma.fence.sync.aligned;" ::: "memory"); }
__device__ __forceinline__ void wgmma_commit() { asm volatile("wgmma.commit_group.sync.aligned;" ::: "memory"); }
template <int N> __device__ __forceinline__ void wgmma_wait() { asm volatile("wgmma.wait_group.sync.aligned %0;" :: "n"(N) : "memory"); }
__device__ __forceinline__ uint64_t mk(uint32_t lo, uint32_t hi) { return (uint64_t)lo | ((uint64_t)hi << 32); }
constexpr uint32_t HI128 = (1024 >> 4) | (1u << 30), HI64 = (512 >> 4) | (2u << 30), HI32 = (256 >> 4) | (3u << 30);
__device__ __forceinline__ uint32_t pack_bf16(float lo, float hi) {
    uint32_t r;
    asm("cvt.rn.bf16x2.f32 %0, %1, %2;" : "=r"(r) : "f"(hi), "f"(lo));
    return r;
}
__device__ __forceinline__ float bflo(uint32_t u) { return __uint_as_float(u << 16); }
__device__ __forceinline__ float bfhi(uint32_t u) { return __uint_as_float(u & 0xFFFF0000u); }
__device__ __forceinline__ float bf16r(float v) { return __uint_as_float(pack_bf16(0.f, v)); }
__device__ __forceinline__ float ex2(float v) { float r; asm("ex2.approx.ftz.f32 %0, %1;" : "=f"(r) : "f"(v)); return r; }
__device__ __forceinline__ float rcp(float v) { float r; asm("rcp.approx.ftz.f32 %0, %1;" : "=f"(r) : "f"(v)); return r; }
__device__ __forceinline__ float sqrt_a(float v) { float r; asm("sqrt.approx.ftz.f32 %0, %1;" : "=f"(r) : "f"(v)); return r; }
__device__ __forceinline__ float tanh_a(float v) { float r; asm("tanh.approx.f32 %0, %1;" : "=f"(r) : "f"(v)); return r; }
constexpr float LOG2E = 1.4426950408889634f;
__device__ __forceinline__ float sigm(float v) { return rcp(1.0f + ex2(-LOG2E * v)); }
__device__ __forceinline__ uint4 lds128(uint32_t a) {
    uint4 v;
    asm volatile("ld.shared.v4.u32 {%0,%1,%2,%3}, [%4];" : "=r"(v.x), "=r"(v.y), "=r"(v.z), "=r"(v.w) : "r"(a));
    return v;
}
__device__ __forceinline__ float2 lds64f(uint32_t a) {
    float2 v;
    asm volatile("ld.shared.v2.f32 {%0,%1}, [%2];" : "=f"(v.x), "=f"(v.y) : "r"(a));
    return v;
}
__device__ __forceinline__ uint32_t lds32(uint32_t a) {
    uint32_t v;
    asm volatile("ld.shared.u32 %0, [%1];" : "=r"(v) : "r"(a));
    return v;
}
__device__ __forceinline__ void sts128(uint32_t a, uint32_t x, uint32_t y, uint32_t z, uint32_t w) {
    asm volatile("st.shared.v4.u32 [%0], {%1,%2,%3,%4};" :: "r"(a), "r"(x), "r"(y), "r"(z), "r"(w) : "memory");
}
__device__ __forceinline__ void sts64(uint32_t a, uint32_t x, uint32_t y) {
    asm volatile("st.shared.v2.u32 [%0], {%1,%2};" :: "r"(a), "r"(x), "r"(y) : "memory");
}
__device__ __forceinline__ void sts32(uint32_t a, uint32_t x) { asm volatile("st.shared.u32 [%0], %1;" :: "r"(a), "r"(x) : "memory"); }
__device__ __forceinline__ unsigned redux_max(unsigned v) {
    unsigned r;
    asm volatile("redux.sync.max.u32 %0, %1, 0xffffffff;" : "=r"(r) : "r"(v));
    return r;
}
__device__ __forceinline__ float shx(float v, int o) { return __shfl_xor_sync(0xffffffffu, v, o); }
__device__ __forceinline__ uint32_t U(float v) { return __float_as_uint(v); }
__device__ __forceinline__ float F(uint32_t v) { return __uint_as_float(v); }

__device__ __forceinline__ void wgmma_n192_lo(float (&d)[120], uint64_t da, uint64_t db, int scale_d) {
    asm volatile("{\n.reg .pred p;\nsetp.ne.b32 p, %98, 0;\n"
        "wgmma.mma_async.sync.aligned.m64n192k16.f32.bf16.bf16 "
        "{%0, %1, %2, %3, %4, %5, %6, %7, %8, %9, %10, %11, %12, %13, %14, %15, "
        "%16, %17, %18, %19, %20, %21, %22, %23, %24, %25, %26, %27, %28, %29, %30, %31, "
        "%32, %33, %34, %35, %36, %37, %38, %39, %40, %41, %42, %43, %44, %45, %46, %47, "
        "%48, %49, %50, %51, %52, %53, %54, %55, %56, %57, %58, %59, %60, %61, %62, %63, "
        "%64, %65, %66, %67, %68, %69, %70, %71, %72, %73, %74, %75, %76, %77, %78, %79, "
        "%80, %81, %82, %83, %84, %85, %86, %87, %88, %89, %90, %91, %92, %93, %94, %95}, "
        "%96, %97, p, 1, 1, 0, 1;\n}\n"
        : "+f"(d[0]), "+f"(d[1]), "+f"(d[2]), "+f"(d[3]), "+f"(d[4]), "+f"(d[5]), "+f"(d[6]), "+f"(d[7]),
          "+f"(d[8]), "+f"(d[9]), "+f"(d[10]), "+f"(d[11]), "+f"(d[12]), "+f"(d[13]), "+f"(d[14]), "+f"(d[15]),
          "+f"(d[16]), "+f"(d[17]), "+f"(d[18]), "+f"(d[19]), "+f"(d[20]), "+f"(d[21]), "+f"(d[22]), "+f"(d[23]),
          "+f"(d[24]), "+f"(d[25]), "+f"(d[26]), "+f"(d[27]), "+f"(d[28]), "+f"(d[29]), "+f"(d[30]), "+f"(d[31]),
          "+f"(d[32]), "+f"(d[33]), "+f"(d[34]), "+f"(d[35]), "+f"(d[36]), "+f"(d[37]), "+f"(d[38]), "+f"(d[39]),
          "+f"(d[40]), "+f"(d[41]), "+f"(d[42]), "+f"(d[43]), "+f"(d[44]), "+f"(d[45]), "+f"(d[46]), "+f"(d[47]),
          "+f"(d[48]), "+f"(d[49]), "+f"(d[50]), "+f"(d[51]), "+f"(d[52]), "+f"(d[53]), "+f"(d[54]), "+f"(d[55]),
          "+f"(d[56]), "+f"(d[57]), "+f"(d[58]), "+f"(d[59]), "+f"(d[60]), "+f"(d[61]), "+f"(d[62]), "+f"(d[63]),
          "+f"(d[64]), "+f"(d[65]), "+f"(d[66]), "+f"(d[67]), "+f"(d[68]), "+f"(d[69]), "+f"(d[70]), "+f"(d[71]),
          "+f"(d[72]), "+f"(d[73]), "+f"(d[74]), "+f"(d[75]), "+f"(d[76]), "+f"(d[77]), "+f"(d[78]), "+f"(d[79]),
          "+f"(d[80]), "+f"(d[81]), "+f"(d[82]), "+f"(d[83]), "+f"(d[84]), "+f"(d[85]), "+f"(d[86]), "+f"(d[87]),
          "+f"(d[88]), "+f"(d[89]), "+f"(d[90]), "+f"(d[91]), "+f"(d[92]), "+f"(d[93]), "+f"(d[94]), "+f"(d[95])
        : "l"(da), "l"(db), "r"(scale_d));
}
__device__ __forceinline__ void wgmma_n48_hi(float (&d)[120], uint64_t da, uint64_t db, int scale_d) {
    asm volatile("{\n.reg .pred p;\nsetp.ne.b32 p, %26, 0;\n"
        "wgmma.mma_async.sync.aligned.m64n48k16.f32.bf16.bf16 "
        "{%0, %1, %2, %3, %4, %5, %6, %7, %8, %9, %10, %11, %12, %13, %14, %15, "
        "%16, %17, %18, %19, %20, %21, %22, %23}, "
        "%24, %25, p, 1, 1, 0, 1;\n}\n"
        : "+f"(d[96]), "+f"(d[97]), "+f"(d[98]), "+f"(d[99]), "+f"(d[100]), "+f"(d[101]), "+f"(d[102]), "+f"(d[103]),
          "+f"(d[104]), "+f"(d[105]), "+f"(d[106]), "+f"(d[107]), "+f"(d[108]), "+f"(d[109]), "+f"(d[110]), "+f"(d[111]),
          "+f"(d[112]), "+f"(d[113]), "+f"(d[114]), "+f"(d[115]), "+f"(d[116]), "+f"(d[117]), "+f"(d[118]), "+f"(d[119])
        : "l"(da), "l"(db), "r"(scale_d));
}
__device__ __forceinline__ void wgmma_rs_n80(float (&d)[40], uint32_t a0, uint32_t a1, uint32_t a2, uint32_t a3, uint64_t db, int scale_d) {
    asm volatile("{\n.reg .pred p;\nsetp.ne.b32 p, %45, 0;\n"
        "wgmma.mma_async.sync.aligned.m64n80k16.f32.bf16.bf16 "
        "{%0, %1, %2, %3, %4, %5, %6, %7, %8, %9, %10, %11, %12, %13, %14, %15, "
        "%16, %17, %18, %19, %20, %21, %22, %23, %24, %25, %26, %27, %28, %29, %30, %31, "
        "%32, %33, %34, %35, %36, %37, %38, %39}, "
        "{%40, %41, %42, %43}, %44, p, 1, 1, 1;\n}\n"
        : "+f"(d[0]), "+f"(d[1]), "+f"(d[2]), "+f"(d[3]), "+f"(d[4]), "+f"(d[5]), "+f"(d[6]), "+f"(d[7]),
          "+f"(d[8]), "+f"(d[9]), "+f"(d[10]), "+f"(d[11]), "+f"(d[12]), "+f"(d[13]), "+f"(d[14]), "+f"(d[15]),
          "+f"(d[16]), "+f"(d[17]), "+f"(d[18]), "+f"(d[19]), "+f"(d[20]), "+f"(d[21]), "+f"(d[22]), "+f"(d[23]),
          "+f"(d[24]), "+f"(d[25]), "+f"(d[26]), "+f"(d[27]), "+f"(d[28]), "+f"(d[29]), "+f"(d[30]), "+f"(d[31]),
          "+f"(d[32]), "+f"(d[33]), "+f"(d[34]), "+f"(d[35]), "+f"(d[36]), "+f"(d[37]), "+f"(d[38]), "+f"(d[39])
        : "r"(a0), "r"(a1), "r"(a2), "r"(a3), "l"(db), "r"(scale_d));
}
__device__ __forceinline__ void wgmma_rs_n192_lo(float (&d)[120], uint32_t a0, uint32_t a1, uint32_t a2, uint32_t a3, uint64_t db, int scale_d) {
    asm volatile("{\n.reg .pred p;\nsetp.ne.b32 p, %101, 0;\n"
        "wgmma.mma_async.sync.aligned.m64n192k16.f32.bf16.bf16 "
        "{%0, %1, %2, %3, %4, %5, %6, %7, %8, %9, %10, %11, %12, %13, %14, %15, "
        "%16, %17, %18, %19, %20, %21, %22, %23, %24, %25, %26, %27, %28, %29, %30, %31, "
        "%32, %33, %34, %35, %36, %37, %38, %39, %40, %41, %42, %43, %44, %45, %46, %47, "
        "%48, %49, %50, %51, %52, %53, %54, %55, %56, %57, %58, %59, %60, %61, %62, %63, "
        "%64, %65, %66, %67, %68, %69, %70, %71, %72, %73, %74, %75, %76, %77, %78, %79, "
        "%80, %81, %82, %83, %84, %85, %86, %87, %88, %89, %90, %91, %92, %93, %94, %95}, "
        "{%96, %97, %98, %99}, %100, p, 1, 1, 1;\n}\n"
        : "+f"(d[0]), "+f"(d[1]), "+f"(d[2]), "+f"(d[3]), "+f"(d[4]), "+f"(d[5]), "+f"(d[6]), "+f"(d[7]),
          "+f"(d[8]), "+f"(d[9]), "+f"(d[10]), "+f"(d[11]), "+f"(d[12]), "+f"(d[13]), "+f"(d[14]), "+f"(d[15]),
          "+f"(d[16]), "+f"(d[17]), "+f"(d[18]), "+f"(d[19]), "+f"(d[20]), "+f"(d[21]), "+f"(d[22]), "+f"(d[23]),
          "+f"(d[24]), "+f"(d[25]), "+f"(d[26]), "+f"(d[27]), "+f"(d[28]), "+f"(d[29]), "+f"(d[30]), "+f"(d[31]),
          "+f"(d[32]), "+f"(d[33]), "+f"(d[34]), "+f"(d[35]), "+f"(d[36]), "+f"(d[37]), "+f"(d[38]), "+f"(d[39]),
          "+f"(d[40]), "+f"(d[41]), "+f"(d[42]), "+f"(d[43]), "+f"(d[44]), "+f"(d[45]), "+f"(d[46]), "+f"(d[47]),
          "+f"(d[48]), "+f"(d[49]), "+f"(d[50]), "+f"(d[51]), "+f"(d[52]), "+f"(d[53]), "+f"(d[54]), "+f"(d[55]),
          "+f"(d[56]), "+f"(d[57]), "+f"(d[58]), "+f"(d[59]), "+f"(d[60]), "+f"(d[61]), "+f"(d[62]), "+f"(d[63]),
          "+f"(d[64]), "+f"(d[65]), "+f"(d[66]), "+f"(d[67]), "+f"(d[68]), "+f"(d[69]), "+f"(d[70]), "+f"(d[71]),
          "+f"(d[72]), "+f"(d[73]), "+f"(d[74]), "+f"(d[75]), "+f"(d[76]), "+f"(d[77]), "+f"(d[78]), "+f"(d[79]),
          "+f"(d[80]), "+f"(d[81]), "+f"(d[82]), "+f"(d[83]), "+f"(d[84]), "+f"(d[85]), "+f"(d[86]), "+f"(d[87]),
          "+f"(d[88]), "+f"(d[89]), "+f"(d[90]), "+f"(d[91]), "+f"(d[92]), "+f"(d[93]), "+f"(d[94]), "+f"(d[95])
        : "r"(a0), "r"(a1), "r"(a2), "r"(a3), "l"(db), "r"(scale_d));
}
__device__ __forceinline__ void wgmma_rs_n48_hi(float (&d)[120], uint32_t a0, uint32_t a1, uint32_t a2, uint32_t a3, uint64_t db, int scale_d) {
    asm volatile("{\n.reg .pred p;\nsetp.ne.b32 p, %29, 0;\n"
        "wgmma.mma_async.sync.aligned.m64n48k16.f32.bf16.bf16 "
        "{%0, %1, %2, %3, %4, %5, %6, %7, %8, %9, %10, %11, %12, %13, %14, %15, "
        "%16, %17, %18, %19, %20, %21, %22, %23}, "
        "{%24, %25, %26, %27}, %28, p, 1, 1, 1;\n}\n"
        : "+f"(d[96]), "+f"(d[97]), "+f"(d[98]), "+f"(d[99]), "+f"(d[100]), "+f"(d[101]), "+f"(d[102]), "+f"(d[103]),
          "+f"(d[104]), "+f"(d[105]), "+f"(d[106]), "+f"(d[107]), "+f"(d[108]), "+f"(d[109]), "+f"(d[110]), "+f"(d[111]),
          "+f"(d[112]), "+f"(d[113]), "+f"(d[114]), "+f"(d[115]), "+f"(d[116]), "+f"(d[117]), "+f"(d[118]), "+f"(d[119])
        : "r"(a0), "r"(a1), "r"(a2), "r"(a3), "l"(db), "r"(scale_d));
}
__device__ __forceinline__ constexpr int jt_of(int sec, int c, bool odd) {
    return odd ? (c >= 2 ? sec * 8 + c - 2 : 24 + sec * 2 + c) : (c < 8 ? sec * 8 + c : 24 + sec * 2 + (c - 8));
}
#define BOTH(...) if (hg & 1) { constexpr bool odd = true; __VA_ARGS__ } else { constexpr bool odd = false; __VA_ARGS__ }

__device__ __forceinline__ bool elect() {
    uint32_t r;
    asm volatile("{\n.reg .pred p;\nelect.sync _|p, 0xffffffff;\nselp.u32 %0, 1, 0, p;\n}" : "=r"(r));
    return r != 0;
}
__device__ __forceinline__ uint32_t clock32() { uint32_t r; asm volatile("mov.u32 %0, %%clock;" : "=r"(r)); return r; }
#define BLOCK_SPLIT(v) asm volatile("{\n.reg .pred p;\nLAB_SPLIT:\nsetp.eq.u32 p, %0, 0;\n@p nanosleep.u32 1;\n@p bra LAB_SPLIT;\n}" :: "r"(v) : "memory")
__device__ __forceinline__ bool any(bool v) { return __any_sync(0xffffffffu, v); }
__device__ __forceinline__ uint32_t opaque_tid() { uint32_t r; asm volatile("mov.u32 %0, %%tid.x;" : "=r"(r)); return r; }

template <bool BY_SM>
__global__ void __cluster_dims__(2, 1, 1) __launch_bounds__(NTHREADS, 1)
fused_kernel(const __grid_constant__ Params P) {
    extern __shared__ __align__(1024) uint8_t smem[];
    const uint32_t sb = (uint32_t)__cvta_generic_to_shared(smem);
    const uint32_t warp = __shfl_sync(0xffffffffu, threadIdx.x >> 5, 0);
    const uint32_t rank = blockIdx.x & 1;
    constexpr uint32_t sbd = 1024 >> 4;
    const uint32_t t0 = clock32();
    if (warp >= 10 && elect()) {
        const uint32_t bb = sb + B_AX - 320 + warp * 32;
        const int cnt = warp < 12 ? 8 : (warp == 14 ? 16 : 1);
        mbar_init(bb, cnt); mbar_init(bb + 8, cnt); mbar_init(bb + 16, cnt); mbar_init(bb + 24, cnt);
        if (warp == 12) { mbar_expect_tx(sb + B_H, 1024); mbar_expect_tx(sb + B_GU, 40960); }
        if (warp == 13) mbar_expect_tx(sb + B_FULL + 16, ST);
        asm volatile("fence.mbarrier_init.release.cluster;" ::: "memory");
    }
    __syncwarp();
    cluster_arrive();
    if (warp < 3 && elect()) asm volatile("prefetch.tensormap [%0];" :: "l"(&P.tm[warp]) : "memory");
    if (warp - 3 < 2 && blockIdx.x < 128 && elect()) l2_prefetch(P.w + ((warp - 3) * 5 * 245760 + blockIdx.x * 1920), 1920);
    if ((sb & 0xFFFFFF) != 1024) __trap();
    uint32_t gpc = blockIdx.x >> 4, pos = (blockIdx.x >> 1) & 7;
    if (BY_SM) {
        uint32_t tpc;
        asm("mov.u32 %0, %%smid;" : "=r"(tpc));
        tpc >>= 1;
        if (tpc - 60 < 2) {
            __nanosleep(2000);
            return;
        }
        const uint32_t q = ((tpc - 32) * 37) >> 8;
        gpc = tpc < 32 ? tpc & 7 : (tpc < 60 ? tpc - 31 - 7 * q : 0);
        pos = tpc < 32 ? tpc >> 3 : (tpc < 60 ? 4 + q : tpc - 58);
    }
    const uint32_t hg = (0x62740351u >> (4 * pos)) & 7, rb = gpc * 2 + rank, fp = 8 * pos + gpc - 10;
    const uint32_t b = rb * 8 + hg;
    const uint32_t k0 = (((hg >> 2) ^ (rb >> 1)) & 1) * 320;

    if (warp == 13 && elect()) tma(sb + 2 * ST, &P.tm[T_X], sb + B_FULL + 16, k0, rb * 64);
    if (warp == 12) {
        cluster_wait();
        if (elect()) {
            tma_mc(sb + 2 * ST + ST_BM + rank * 12288, &P.tm[T_W], sb + B_FULL + 16, hg * 80 + (hg & 1) * 16, k0 + rank * 32);
            tma_mc(sb + 2 * ST + ST_BR + rank * 3072, &P.tm[T_WR], sb + B_FULL + 16, hg * 80 + 64 - (hg & 1) * 64, k0 + rank * 32);
        }
        __syncwarp();
    }

    if (warp < 8) {
        asm volatile("setmaxnreg.inc.sync.aligned.u32 208;");
        const uint32_t lane = opaque_tid() & 31, g = lane >> 2, t = lane & 3;
        const uint32_t p = warp >> 2, w = warp & 3;
        const uint32_t empty_cl = mapa(sb + B_EMPTY, lane & 1);
        uint8_t* const orow = P.scr + (rb * (8 * XB) + warp * 2560 + lane * 16);
        const uint32_t ta = sb + warp * 2560 + (lane & 15) * 160 + (lane >> 4) * 16;
        uint32_t A[5][20];
        uint32_t xr[5][4], gf[5][4];
        TRD(r12); TRD(r32); TRD(r34); TRD(r22); TRD(r44);
        uint32_t par;
        uint8_t* const halo = orow + (hg * XB + (8 + p - warp) * 2560);
        uint8_t* const flag = P.scr + (G_FLAG + b * XB + w * 8 + p * 4);
        cluster_wait();
        {
            float acc[120];
            bool ok, prep;
            float2 s0, s1;
            uint32_t xa[5], cap[2] = {0u, 0u};
#pragma unroll
            for (uint32_t j = 0; j < 5; j++) {
                const uint32_t cg = 5 * hg + (j < 4 ? j + (hg & 1) : (~hg & 1) * 4);
                xa[j] = (sb + (warp * 16 + (lane & 15)) * 128 + (((lane >> 4) ^ (lane & 7)) << 4)) ^ ((cg & 3) << 5);
                const uint32_t i = cg >> 2, late = (i >= 5) ^ (k0 != 0), bit = 1u << (5 * (i >= 5 ? i - 5 : i) + j);
                cap[0] |= late ? 0u : bit; cap[1] |= late ? bit : 0u;
            }
            uint32_t sta = sb + M_ST + (warp * 16 + g) * 8;
            asm volatile("" : "+r"(sta), "+r"(cap[0]), "+r"(cap[1]), "+r"(xa[0]), "+r"(xa[1]), "+r"(xa[2]), "+r"(xa[3]), "+r"(xa[4]));
            mbar_wait(sb + B_FULL + 16, 0);
#pragma unroll
            for (uint32_t kb = 2; kb < 12; kb++) {
                const uint32_t s = kb & 3;
                const bool hold = kb == 12 - LEAD && p;
                if (hold) {
                    wgmma_wait<0>();
                    if (lane < 2) mbar_arrive_cl(empty_cl + 8 * ((11 - LEAD) & 3));
                    bar_sync(1, 256);
                }
                wgmma_fence();
                const uint32_t st = sbd + s * (ST >> 4);
#pragma unroll
                for (int ks = 0; ks < 4; ks++) {
                    const uint64_t da = mk(st + p * 512 + ks * 2 + 0x10000, HI128);
                    wgmma_n48_hi(acc, da, mk(st + (ST_BR >> 4) + (ks >> 1) * 192 + (ks & 1) * 32 + (64 << 16), HI32), ks || kb > 2);
                    wgmma_n192_lo(acc, da, mk(st + (ST_BM >> 4) + (ks >> 1) * 768 + (ks & 1) * 128 + (256 << 16), HI128), ks || kb > 2);
                    if (ks == 0) {
                        wgmma_commit();
                        wgmma_wait<1>();
                        if (!hold && kb > 2 && lane < 2) mbar_arrive_cl(empty_cl + 8 * ((kb - 1) & 3));
                    }
                    if (ks == 1) {
#pragma unroll
                        for (uint32_t j = 0; j < 5; j++)
                            if ((cap[kb >= 7] >> (5 * ((kb - 2) % 5) + j)) & 1) ldsm_x4(xr[j], xa[j] + s * ST);
                        if (w == 3 && kb < 7) stg128(halo + (kb - 2) * 512, 0u, 0u, 0u, 0u);
                        if (lane == 0 && kb == 2) stg32(flag, 0u);
                        if (kb < 11) ok = mbar_try(sb + B_FULL + 8 * ((kb + 1) & 3), ((kb - 1) >> 2) & 1);
                        if (kb == 10) prep = mbar_try(sb + B_PREP, 0);
                        if (kb == 11 && prep) {
                            s0 = lds64f(sta); s1 = lds64f(sta + 64);
                            par = lds32(sb + M_SEL + 8);
                        }
                    }
                }
                wgmma_commit();
                if (kb < 11 && !ok) mbar_wait(sb + B_FULL + 8 * ((kb + 1) & 3), ((kb - 1) >> 2) & 1);
            }
            if (!prep) {
                mbar_wait(sb + B_PREP, 0);
                s0 = lds64f(sta); s1 = lds64f(sta + 64);
                par = lds32(sb + M_SEL + 8);
            }
            {
                const uint32_t a0 = t ? 0u : __byte_perm(U(-s0.y), 0, 0x3232), a1 = t ? 0u : __byte_perm(U(-s1.y), 0, 0x3232);
                wgmma_fence();
                wgmma_rs_n48_hi(acc, a0, a1, 0u, 0u, mk(sbd + (M_CS >> 4) + 48, 2), 1);
                wgmma_rs_n192_lo(acc, a0, a1, 0u, 0u, mk(sbd + (M_CS >> 4), 2), 1);
                wgmma_commit();
            }
            if (!p) bar_arrive(1, 256);
            wgmma_wait<1>();
            if (lane < 2) mbar_arrive_cl(empty_cl + 24);
            wgmma_wait<0>();
#pragma unroll
            for (int i = 0; i < 120; i++) asm volatile("" : "+f"(acc[i]) :: "memory");
            TR(r12);
            uint32_t Q[10], Ql[10], KX[10], VX[10], Y[20];
#define KI(c) ((c) == 2 ? 8 : (c) == 7 ? 9 : (c) - ((c) > 2) - ((c) > 7))
#define KY(c) Y[KI(c)]
#define VY(c) Y[10 + (c)]
            uint32_t Z[20];
            const bool start = w == 0 && rb == 0, remote = w == 0 && rb != 0;
            const uint32_t slot = sb + OFF_HO + p * 8192 + w * 2560 - 2560 + lane * 16;
            {
                BOTH(_Pragma("unroll") for (int c = 0; c < 10; c++) {
                    const int jk = jt_of(1, c, odd), jv = jt_of(2, c, odd);
                    VY(c) = movm(pack_bf16(acc[4 * jv + 2] * s1.x, acc[4 * jv + 3] * s1.x));
                    KY(c) = pack_bf16(acc[4 * jk + 2] * s1.x, acc[4 * jk + 3] * s1.x);
                    asm volatile("" : "+r"(KY(c)), "+r"(VY(c)));
                })
                if (w == 3) {
#pragma unroll
                    for (int j = 0; j < 5; j++) {
                        Y[4 * j] = (Y[4 * j] & ~0x10001u) | par;
                        stg128(halo + j * 512, Y[4 * j], Y[4 * j + 1], Y[4 * j + 2], Y[4 * j + 3]);
                    }
                } else {
#pragma unroll
                    for (int j = 0; j < 5; j++) sts128(slot + 2560 + j * 512, Y[4 * j], Y[4 * j + 1], Y[4 * j + 2], Y[4 * j + 3]);
                }
                BOTH(_Pragma("unroll") for (int c = 0; c < 10; c++) {
                    const int jk = jt_of(1, c, odd), jv = jt_of(2, c, odd);
                    KX[c] = pack_bf16(acc[4 * jk] * s0.x, acc[4 * jk + 1] * s0.x);
                    VX[c] = movm(pack_bf16(acc[4 * jv] * s0.x, acc[4 * jv + 1] * s0.x));
                    asm volatile("" : "+r"(KX[c]), "+r"(VX[c]));
                })
                bar_sync(2 + p, 128);
                if (remote) {
#pragma unroll
                    for (int j = 0; j < 5; j++) ldg128(halo - 8 * XB + j * 512, Z[4 * j], Z[4 * j + 1], Z[4 * j + 2], Z[4 * j + 3]);
                } else {
#pragma unroll
                    for (int j = 0; j < 5; j++) {
                        const uint4 v = lds128(slot + (w ? 0 : 2560) + j * 512);
                        Z[4 * j] = v.x; Z[4 * j + 1] = v.y; Z[4 * j + 2] = v.z; Z[4 * j + 3] = v.w;
                    }
                }
                BOTH(_Pragma("unroll") for (int c = 0; c < 10; c++) {
                    const int jq = jt_of(0, c, odd);
                    Ql[c] = pack_bf16(acc[4 * jq], acc[4 * jq + 1]);
                    Q[c] = pack_bf16(acc[4 * jq + 2], acc[4 * jq + 3]);
                    asm volatile("" : "+r"(Ql[c]), "+r"(Q[c]));
                })
            }
            auto scores = [&](float (&l)[4], const uint32_t (&q)[10], const uint32_t (&z)[20], const int c0, const uint32_t mx, const float nz) {
                const uint32_t qa = t < 2 ? q[c0 + 2] : 0u, qb = t < 2 ? 0u : q[c0 + 2];
                float xa[4] = {0.f, 0.f, 0.f, 0.f}, za[4] = {nz, nz, nz, nz}, xb[4], zb[4];
                mma1688(xa, qa, qb, KX[c0 + 2]);
                mma1688(za, qa, qb, z[KI(c0 + 2)]);
#pragma unroll
                for (int e = 0; e < 4; e++) { xb[e] = xa[e]; zb[e] = za[e]; }
                mma16816(xa, q[c0], q[c0 + 3], q[c0 + 1], q[c0 + 4], KX[c0], KX[c0 + 1]);
                mma16816(za, q[c0], q[c0 + 3], q[c0 + 1], q[c0 + 4], z[KI(c0)], z[KI(c0 + 1)]);
                mma16816(xb, q[c0], q[c0 + 3], q[c0 + 1], q[c0 + 4], KX[c0 + 3], KX[c0 + 4]);
                mma16816(zb, q[c0], q[c0 + 3], q[c0 + 1], q[c0 + 4], z[KI(c0 + 3)], z[KI(c0 + 4)]);
                const bool h0 = mx & 1u, h1 = (int)mx < 0;
                l[0] = h0 ? xa[0] : za[0]; l[1] = h1 ? xa[1] : za[1];
                l[2] = h0 ? xb[2] : zb[2]; l[3] = h1 ? xb[3] : zb[3];
                asm volatile("" : "+f"(l[0]), "+f"(l[1]), "+f"(l[2]), "+f"(l[3]));
            };
            auto soft = [&](uint32_t (&pr)[2], const float (&l)[4], const float sq) {
                float m0 = fmaxf(l[0], l[1]), m1 = fmaxf(l[2], l[3]);
                m0 = fmaxf(m0, shx(m0, 1)); m1 = fmaxf(m1, shx(m1, 1));
                m0 = fmaxf(m0, shx(m0, 2)) * -sq; m1 = fmaxf(m1, shx(m1, 2)) * -sq;
                pr[0] = pack_bf16(ex2(fmaf(l[0], sq, m0)), ex2(fmaf(l[1], sq, m0)));
                pr[1] = pack_bf16(ex2(fmaf(l[2], sq, m1)), ex2(fmaf(l[3], sq, m1)));
                asm volatile("" : "+r"(pr[0]), "+r"(pr[1]));
            };
            auto values = [&](const uint32_t (&pr)[2], const uint32_t (&z)[20], const int c0, const uint32_t mx, const int h) {
                float dn[4] = {0.f, 0.f, 0.f, 0.f};
                mma1688(dn, pr[0], pr[1], 0x3F803F80u);
                const float i0 = rcp(dn[0]), i1 = rcp(dn[2]), i2 = t < 2 ? i0 : i1;
#pragma unroll
                for (int c = 0; c < 5; c++) {
                    float oc[4] = {0.f, 0.f, 0.f, 0.f};
                    mma16816(oc, pr[0] & mx, pr[1] & mx, pr[0] & ~mx, pr[1] & ~mx, VX[c0 + c], z[10 + c0 + c]);
                    const bool first = c < 2 || (c == 2 && t < 2);
                    const float iv = c < 2 ? i0 : (c > 2 ? i1 : i2);
                    A[0][2 * (c0 + c) + h] = pack_bf16((first ? oc[0] : oc[2]) * iv, (first ? oc[1] : oc[3]) * iv);
                    asm volatile("" : "+r"(A[0][2 * (c0 + c) + h]));
                }
            };
            auto gate = [&]() {
                const float r0 = 0.5f * s0.x, r1 = 0.5f * s1.x, n0 = -r0 * s0.y, n1 = -r1 * s1.y;
#pragma unroll
                for (int j = 0; j < 5; j++) {
#pragma unroll
                    for (int q = 0; q < 4; q++) {
                        const float v0 = fmaf(bflo(xr[j][q]), q & 1 ? r1 : r0, q & 1 ? n1 : n0), v1 = fmaf(bfhi(xr[j][q]), q & 1 ? r1 : r0, q & 1 ? n1 : n0);
                        gf[j][q] = pack_bf16(fmaf(v0, tanh_a(v0), v0), fmaf(v1, tanh_a(v1), v1));
                        asm volatile("" : "+r"(gf[j][q]));
                    }
                }
            };
            const uint32_t mo = (2 * t > g ? 0xFFFFu : 0u) | (2 * t + 1 > g ? 0xFFFF0000u : 0u);
            constexpr float SC = 0.22360679774997896f * LOG2E;
            {
                float l[4][4];
                uint32_t pr[4][2];
                unsigned spins = 0;
#pragma unroll 1
                while (remote && any((Z[0] & Z[4] & Z[8] & Z[12] & Z[16] & par) == 0u) && ++spins < SPIN) {
#pragma unroll
                    for (int j = 0; j < 5; j++) ldg128(halo - 8 * XB + j * 512, Z[4 * j], Z[4 * j + 1], Z[4 * j + 2], Z[4 * j + 3]);
                }
                TR(r32);
                const float nz = start ? -INFINITY : 0.f;
                auto publish = [&](const int j) {
                    A[0][4 * j] = (A[0][4 * j] & ~0x10001u) | par;
                    stg128(orow + hg * XB + j * 512, A[0][4 * j], A[0][4 * j + 1], A[0][4 * j + 2], A[0][4 * j + 3]);
                };
                scores(l[0], Q, Y, 0, mo, 0.f);
                scores(l[2], Ql, Z, 0, ~mo, nz);
                scores(l[1], Q, Y, 5, mo, 0.f);
                scores(l[3], Ql, Z, 5, ~mo, nz);
                soft(pr[0], l[0], s1.x * SC);
                soft(pr[2], l[2], s0.x * SC);
                soft(pr[1], l[1], s1.x * SC);
                soft(pr[3], l[3], s0.x * SC);
                values(pr[0], Y, 0, mo, 1);
                values(pr[2], Z, 0, ~mo, 0);
                publish(0);
                if (lane == 0 && !p) stg32(flag, par);
                publish(1);
                values(pr[1], Y, 5, mo, 1);
                values(pr[3], Z, 5, ~mo, 0);
                publish(2); publish(3); publish(4);
            }
            if (lane == 0 && p) stg32(flag, par);
            TR(r34);
            if (p) bar_arrive(8, 384);
            BLOCK_SPLIT(par);
            gate();
        }
        {
            float acc2[40];
            unsigned spins = 0;
            bool again, first = true;
            const uint8_t* src[7];
#pragma unroll
            for (uint32_t i = 0; i < 7; i++) { src[i] = orow + (i >= hg ? XB : 0u); asm volatile("" : "+l"(src[i])); }
            mbar_wait(sb + B_SEL, 0);
            const float2 sel = lds64f(sb + M_SEL);
            uint32_t routed = (U(sel.x) >> 4) == warp || (U(sel.y) >> 4) == warp;
            asm volatile("" : "+r"(routed));
            BLOCK_SPLIT(par);
            if (p) bar_sync(9, 288); else bar_sync(5, 160);
#pragma unroll 1
            do {
#pragma unroll
                for (uint32_t i = 1; i < 5; i++)
#pragma unroll
                    for (int j = 0; j < 5; j++)
                        ldg128(src[i - 1] + (i - 1) * XB + j * 512, A[i][4 * j], A[i][4 * j + 1], A[i][4 * j + 2], A[i][4 * j + 3]);
                if (!p && first) bar_sync(8, 384);
                uint32_t mn = par;
#pragma unroll
                for (int i = 0; i < 8; i++) {
                    const uint32_t (&a)[20] = A[i % 5];
                    if (i == 4 && !p && first) bar_sync(6, 160);
                    wgmma_fence();
#pragma unroll
                    for (int j = 0; j < 5; j++) {
                        wgmma_rs_n80(acc2, a[4 * j], a[4 * j + 1], a[4 * j + 2], a[4 * j + 3],
                                     mk(sbd + (wo_slot(i) >> 4) + j * 64 + (320 << 16), HI64), i || j);
                        if (i == 7 && j == 2) {
#pragma unroll
                            for (int q = 0; q < 5; q++) mn &= A[q][0] & A[q][4] & A[q][8] & A[q][12] & A[q][16];
                            again = bar_or(2 + p, 128, mn == 0u && ++spins < SPIN);
                        }
                    }
                    if (i < 4 || i == 7) wgmma_commit();
                    if (i == SERAT && !p && first) bar_arrive(9, 288);
                    if (i == 0) TR(r22);
                    if (i >= 1 && i < 4) {
                        uint32_t (&n)[20] = A[i - 1];
                        if (i > 1) mn &= n[0] & n[4] & n[8] & n[12] & n[16];
                        const uint8_t* q = src[i + 3] + (i > 1 ? mn & 256u : 0u);
                        wgmma_wait<1>();
                        bar_arrive(10, 32);
#pragma unroll
                        for (int j = 0; j < 5; j++) ldg128(q + (i + 3) * XB + j * 512, n[4 * j], n[4 * j + 1], n[4 * j + 2], n[4 * j + 3]);
                        bar_arrive(10, 32);
                    }
                }
                first = false;
                if (again) {
                    wgmma_wait<0>();
#pragma unroll
                    for (int j = 0; j < 5; j++)
                        ldg128(orow + hg * XB + j * 512, A[0][4 * j], A[0][4 * j + 1], A[0][4 * j + 2], A[0][4 * j + 3]);
                }
            } while (again);
            const uint32_t o0 = (hg & 1) * 32, o4 = (~hg & 1) * 128;
            if (routed) {
                const float2 sel = lds64f(sb + M_SEL);
                mbar_wait(sb + B_UPD, 0);
#pragma unroll
                for (uint32_t h = 0; h < 2; h++) {
                    const uint32_t row = warp * 16 + g + 8 * h, ga = sb + M_UPD + (row == U(sel.x) ? 0 : 160) + t * 4;
                    if (row == U(sel.x) || row == U(sel.y)) {
#pragma unroll
                        for (int c = 0; c < 5; c++) { gf[c][h] = lds32(ga + (c < 4 ? o0 + c * 32 : o4)); gf[c][h + 2] = lds32(ga + (c < 4 ? o0 + c * 32 : o4) + 16); }
                    }
                }
                __syncwarp();
            }
            wgmma_wait<0>();
#pragma unroll
            for (int i = 0; i < 40; i++) asm volatile("" : "+f"(acc2[i]) :: "memory");
            TR(r44);
#pragma unroll
            for (int c = 0; c < 5; c++) {
#pragma unroll
                for (int q = 0; q < 4; q++)
                    asm("fma.rn.bf16x2 %0, %1, %2, %0;" : "+r"(xr[c][q]) : "r"(pack_bf16(acc2[8 * c + 2 * q], acc2[8 * c + 2 * q + 1])), "r"(gf[c][q]));
                stsm_x4(ta + (c < 4 ? o0 + c * 32 : o4) + OFF_DN, xr[c]);
            }
            fence_proxy_async_smem();
            __syncwarp();
            if (lane == 0) {
                tma_st(&P.tm[T_OUT], sb + OFF_DN + warp * 2560, hg * 80, rb * 64 + 16 * w, p);
                asm volatile("cp.async.bulk.wait_group.read 0;" ::: "memory");
            }
        }
        TS(46);
        TRW(r12, 12); TRW(r32, 32); TRW(r34, 34); TRW(r22, 22); TRW(r44, 44);
    } else if (warp >= 12) {
        asm volatile("setmaxnreg.dec.sync.aligned.u32 24;");
        if (warp == 12) {
            uint32_t slot = t0 + PACE0;
            if (elect()) {
#pragma unroll 1
                for (uint32_t kb = 1; kb < 10; kb++) {
                    const uint32_t s = (kb + 2) & 3;
                    const uint32_t st = sb + s * ST, fb = sb + B_FULL + 8 * s;
                    const uint32_t kc = kb * 64 + (kb < 5 ? k0 : -k0);
                    if (kb >= 4) {
                        mbar_wait(fb + 32, kb >> 3);
                        if (kb < 9) mbar_wait(sb + B_AX - 32 + 8 * kb, 0);
                    }
                    {
                        slot += PACE1;
#pragma unroll 1
                        while ((int)(clock32() - slot) < 0) { }
                        mbar_expect_tx(fb, ST);
                        tma(st, &P.tm[T_X], fb, kc, rb * 64);
                    }
                    tma_mc(st + ST_BM + rank * 12288, &P.tm[T_W], fb, hg * 80 + (hg & 1) * 16, kc + rank * 32);
                    tma_mc(st + ST_BR + rank * 3072, &P.tm[T_WR], fb, hg * 80 + 64 - (hg & 1) * 64, kc + rank * 32);
                }
                uint32_t wb = sb + B_WO - 8;
#pragma unroll 1
                for (uint32_t i = 0; i < 8; i++) {
                    if ((0x93 >> i) & 1) {
                        wb += 8;
                        mbar_wait(wb - (B_WO - B_EMPTY), i < 2);
                        mbar_expect_tx(wb, (i + 1) & 6 ? 3 * 12800 : 12800);
                    }
                    if (i == 0) {
                        mbar_expect_tx(sb + B_DN, 20480);
                        tma(sb + OFF_DN, &P.tm[T_D], sb + B_DN, 0, 32 * fp, 5 * rank);
                    }
                    if (WOP) {
#pragma unroll 1
                        while ((int)(clock32() - slot) < 0) { }
                        slot = clock32() + WOP;
                    }
                    const uint32_t d = sb + wo_slot(i);
                    const uint32_t kr = 80 * (i ? i - (i <= hg) : hg);
                    tma_mc(d + rank * 5120, &P.tm[T_WO], wb, hg * 80 + (hg & 1) * 16 + rank * 32, kr);
                    tma_mc(d + 10240 + rank * 2560, &P.tm[T_WOR], wb, hg * 80 + (~hg & 1) * 64, kr + rank * 40);
                }
            }
        } else if (warp == 13) {
            if (elect()) {
#pragma unroll 1
                for (uint32_t i = 0; i < 3; i++) {
#pragma unroll 1
                    while (clock32() - t0 < PX0 + i * PX1) __nanosleep(20);
                    l2_prefetch(P.w + ((i + 2) * 245760 + b * 1920), 1920);
                    l2_prefetch(P.w + ((i + 7) * 245760 + b * 1920), 1920);
                }
#pragma unroll 1
                for (uint32_t i = 0; i < 14; i++) {
#pragma unroll 1
                    while (clock32() - t0 < GU0 + i * GU1) __nanosleep(20);
                    if (i < 10) l2_prefetch(P.wd + (i * 128 + b) * 1728, 1728);
                    else l2_prefetch(P.wo + ((i - 10) * 128 + b) * 1600, 1600);
                }
            }
        } else if (warp == 15) {
            const uint32_t lane = opaque_tid() & 31;
            const uint8_t* fl = P.scr + (G_FLAG + (rb * 8 + (lane & 7)) * XB + (lane >> 3) * 8);
            cluster_wait();
            mbar_wait(sb + B_PREP, 0);
            const uint32_t par = lds32(sb + M_SEL + 8);
            mbar_wait(sb + B_WO, 0); mbar_wait(sb + B_WO + 8, 0);
            mbar_wait(sb + B_EMPTY + 24, 0);
            __nanosleep(WSL);
            unsigned spins = 0;
            uint2 f;
#pragma unroll 1
            do f = ldg64(fl); while (any(f.x != par) && ++spins < SPIN);
            bar_arrive(5, 160);
            TS(24);
            mbar_wait(sb + B_WO + 16, 0); mbar_wait(sb + B_WO + 24, 0);
            bar_arrive(6, 160);
#pragma unroll 1
            while (any(f.y != par) && ++spins < SPIN) f.y = ldg32(fl + 4);
            bar_arrive(9, 288);
            TS(25);
        } else {
            uint32_t slot = t0 + GT0;
            cluster_wait();
            if (elect()) {
#pragma unroll 1
                for (uint32_t i = 0; i < 20; i++) {
                    slot += GT1;
#pragma unroll 1
                    while ((int)(clock32() - slot) < 0) __nanosleep(20);
                    tma(sb + OFF_GU + i * 2048, &P.tm[T_GU], sb + B_GU, 32 * fp, rank * 320 + i * 16);
                }
            }
        }
    } else {
        asm volatile("setmaxnreg.dec.sync.aligned.u32 72;");
        const uint32_t at = opaque_tid() - 256, lane = at & 31, g = lane >> 2, t = lane & 3, c7 = lane & 7, aw = warp - 8;
        uint8_t* const yz = P.scr + (G_Y + b * 512 + at * 4);
        stg32(yz, 0u);
        __nanosleep(AUXS);
        const uint32_t epoch = ldg32(P.scr + G_EPOCH) + 1 + ldg32(yz), tag = (epoch & 15u) | 16u;
        const uint32_t empty_cl = mapa(sb + B_EMPTY, lane & 1);
        unsigned spins = 0;
        TRD(r51); TRD(r30); TRD(r52); TRD(r53); TRD(r54); TRD(r55); TRD(r20); TRD(r22);
        {
            const uint2 wv = __ldg(reinterpret_cast<const uint2*>(P.w_r + k0 * 2 + min(at, 79u) * 8));
            if (at < 80) sts64(sb + M_UPD + at * 8, wv.x, wv.y);
        }
        uint8_t* const stw = P.scr + (b * XB + G_ST + (lane & 4) * 64 + (at >> 3) * 16);
        uint8_t* const csw = P.scr + (b * XB + G_CS + at);
        uint8_t* const tpw = P.scr + (G_TOP + (hg >> 2) * XB + rb * 64 + aw * 16);
        const bool tpub = lane == 0 && (hg & 3) == 3;
        cluster_wait();
        bar_sync(4, 128);
        mbar_wait(sb + B_FULL + 16, 0);
        if (t == 0) { stg128(stw, 0u, 0u, 0u, 0u); stg32(csw, 0u); }
        if (tpub) stg128(tpw, 0u, 0u, 0u, 0u);

        uint32_t k1, sv;
        {
            const uint32_t xoff = (32 * (hg & 3) + (at >> 3)) * 128 + ((c7 ^ ((at >> 3) & 7)) << 4);
            const uint32_t jt = (rb >> 2) * 8 + rank * 4 + aw;
            const uint32_t coff = jt < 24 ? ST_BM + (jt >> 3) * 4096 + lane * 128 + (((jt ^ lane) & 7) << 4)
                                          : ST_BR + ((jt >> 1) & 3) * 1024 + lane * 32 + (((jt ^ g) & 1) << 4);
            float q[8], c8[8];
#pragma unroll
            for (int e = 0; e < 8; e++) q[e] = c8[e] = 0.f;
#pragma unroll 1
            for (uint32_t kb = 2; kb < 7; kb++) {
                const uint32_t st = sb + (kb & 3) * ST;
                const uint4 wv = lds128(sb + M_UPD - 256 + kb * 128 + c7 * 16);
                mbar_wait(sb + B_FULL + 8 * (kb & 3), kb == 6);
                const uint4 v = lds128(st + xoff), vn = lds128(st + xoff + 2048);
                const uint4 cv = lds128(st + coff), cn = lds128(st + coff + (jt < 24 ? 12288 : 3072));
                if (lane < 2) mbar_arrive_cl(empty_cl - (B_EMPTY + 16 - B_AX) + 8 * kb);
                const uint32_t u[4] = {v.x, v.y, v.z, v.w}, un[4] = {vn.x, vn.y, vn.z, vn.w}, ww[4] = {wv.x, wv.y, wv.z, wv.w};
                const uint32_t cc[4] = {cv.x, cv.y, cv.z, cv.w}, cd[4] = {cn.x, cn.y, cn.z, cn.w};
#pragma unroll
                for (int e = 0; e < 4; e++) {
                    const float a0 = bflo(u[e]), a1 = bfhi(u[e]), b0 = bflo(un[e]), b1 = bfhi(un[e]), w0 = bflo(ww[e]), w1 = bfhi(ww[e]);
                    q[0] += a0 + a1; q[4] += b0 + b1; q[3] += w0 + w1;
                    q[1] = fmaf(a0, a0, fmaf(a1, a1, q[1])); q[5] = fmaf(b0, b0, fmaf(b1, b1, q[5]));
                    q[2] = fmaf(a0, w0, fmaf(a1, w1, q[2])); q[6] = fmaf(b0, w0, fmaf(b1, w1, q[6]));
                    c8[2 * e] += bflo(cc[e]) + bflo(cd[e]); c8[2 * e + 1] += bfhi(cc[e]) + bfhi(cd[e]);
                }
            }
            TR(r51);
            q[7] = q[3];
#pragma unroll
            for (int e = 0; e < 4; e++) {
                q[e] = ((lane & 4) ? q[e + 4] : q[e]) + shx((lane & 4) ? q[e] : q[e + 4], 4);
                q[e] += shx(q[e], 1); q[e] += shx(q[e], 2);
            }
            const float mh = q[0] * (1.0f / 320);
            if (t == 0) stg128(stw, U(mh), U(fmaf(-mh, q[0], q[1])), U(q[2]), (U(q[3]) & ~31u) | tag);
#define TSTEP(H) { const bool up = (lane & (4 * H)) != 0; _Pragma("unroll") for (int e = 0; e < H; e++) { \
            const float send = up ? c8[e] : c8[e + H]; const float keep = up ? c8[e + H] : c8[e]; \
            c8[e] = keep + shx(send, 4 * H); } }
            TSTEP(4) TSTEP(2) TSTEP(1)
#undef TSTEP
            c8[0] += shx(c8[0], 1); c8[0] += shx(c8[0], 2);
            if (t == 0) stg32(csw, (U(c8[0]) & ~31u) | tag);
            TR(r30);
            const uint8_t* csp = P.scr + (G_CS + (aw * 32 + (lane >> 4) * 8 + hg) * XB + (lane & 15) * 8);
            const uint8_t* stp = P.scr + (G_ST + (rb * 8 + aw) * XB + lane * 16);
            uint32_t ra[4], rc[4];
            uint2 ca, cc;
#pragma unroll 1
            while (clock32() - t0 < EX1T) __nanosleep(20);
#pragma unroll 1
            do {
                ldg128(stp, ra[0], ra[1], ra[2], ra[3]);
                ldg128(stp + 4 * XB, rc[0], rc[1], rc[2], rc[3]);
                ca = ldg64(csp); cc = ldg64(csp + 16 * XB);
            } while (any((ra[3] ^ tag | rc[3] ^ tag) & 31u) && ++spins < SPIN);
            TR(r20);
            const float dm = 0.5f * (F(ra[0]) - F(rc[0])), m = bf16r(F(rc[0]) + dm);
            const float sd = bf16r(sqrt_a(bf16r(bf16r(fmaxf(fmaf(dm, dm, (F(ra[1]) + F(rc[1])) * (1.0f / DM)), 0.f)) + 1e-5f)));
            const float rs = rcp(sd);
            uint32_t w1, w2;
            if ((hg & 3) == 3) {
                k1 = pack_bf16(0.f, fmaf(-m, F(ra[3]) + F(rc[3]), F(ra[2]) + F(rc[2])) * rs);
                k1 ^= ((int)k1 >> 31) | 0x80000000u;
                k1 = (k1 & 0xFFFF0000u) | ((2047 - (rb * 128 + 2 * (at & 63) + (at >> 6))) << 5) | tag;
                w1 = redux_max(k1); w2 = redux_max(k1 == w1 ? 0u : k1);
                sv = U(m) | (U(sd) >> 16);
                const uint32_t v1 = redux_max(k1 == w1 ? sv : 0u), v2 = redux_max(k1 == w2 ? sv : 0u);
                if (lane == 0) stg128(tpw, w1, v1, w2, v2);
            }
            sts64(sb + M_ST + at * 8, U(rs), U(m));
            sts32(sb + M_SEL + 8, (tag & 1) ? 1u : 0x10000u);
#pragma unroll 1
            while (any((ca.x ^ tag | ca.y ^ tag | cc.x ^ tag | cc.y ^ tag) & 31u) && ++spins < SPIN) { ca = ldg64(csp); cc = ldg64(csp + 16 * XB); }
            {
                const float c0 = at < 120 ? F(ca.x) + F(cc.x) : 0.f, c1 = at < 120 ? F(ca.y) + F(cc.y) : 0.f;
                const uint32_t hi = pack_bf16(c0, c1);
                sts32(sb + M_CS + (at >> 2) * 32 + t * 4, hi);
                sts32(sb + M_CS + (at >> 2) * 32 + t * 4 + 16, pack_bf16(c0 - bflo(hi), c1 - bfhi(hi)));
                fence_proxy_async_smem();
                __syncwarp();
                if (lane < 2) mbar_arrive(sb + B_PREP);
            }
            TR(r52);
            if (aw == 0) {
                uint32_t ka[4], kb[4];
#pragma unroll 1
                while (clock32() - t0 < EX1T + EX2D) __nanosleep(20);
#pragma unroll 1
                do {
                    const uint8_t* tp = P.scr + (G_TOP + lane * 16);
                    uint32_t kc[4], kd[4];
                    ldg128(tp, ka[0], ka[1], ka[2], ka[3]);
                    ldg128(tp + 512, kb[0], kb[1], kb[2], kb[3]);
                    ldg128(tp + XB, kc[0], kc[1], kc[2], kc[3]);
                    ldg128(tp + XB + 512, kd[0], kd[1], kd[2], kd[3]);
                    const bool ba = (ka[0] ^ tag) & 31u, bb = (kb[0] ^ tag) & 31u;
#pragma unroll
                    for (int e = 0; e < 4; e++) { ka[e] = ba ? kc[e] : ka[e]; kb[e] = bb ? kd[e] : kb[e]; }
                } while (any((ka[0] ^ tag | kb[0] ^ tag) & 31u) && ++spins < SPIN);
                TR(r22);
                if (kb[0] > ka[0]) {
#pragma unroll
                    for (int e = 0; e < 4; e++) { const uint32_t x = ka[e]; ka[e] = kb[e]; kb[e] = x; }
                }
                if (kb[0] > ka[2]) { ka[2] = kb[0]; ka[3] = kb[1]; }
                w1 = redux_max(ka[0]);
                const uint32_t t1 = redux_max(ka[0] == w1 ? ka[1] : 0u);
                if (ka[0] == w1) { ka[0] = ka[2]; ka[1] = ka[3]; }
                w2 = redux_max(ka[0]);
                const uint32_t t3 = redux_max(ka[0] == w2 ? ka[1] : 0u);
                sts128(sb + M_TOP, w1, t1, w2, t3);
            }
            bar_sync(4, 128);
            const float2 tv = lds64f(sb + M_TOP + (lane & 1) * 8);
            k1 = U(tv.x);
            sv = U(tv.y);
        }
        TR(r53);
        const uint32_t tok = ~(k1 >> 5) & 2047;
        const unsigned owns = __ballot_sync(0xffffffffu, (tok >> 7) == rb) & 3u;
        if (at < 2) sts32(sb + M_SEL + at * 4, (tok >> 7) == rb ? (tok & 1) * 64 + ((tok & 127) >> 1) : ~0u);
        if ((at | b) == 0) *reinterpret_cast<uint32_t*>(P.scr + G_EPOCH) = epoch;
        __syncwarp();
        if (at == 0) mbar_arrive(sb + B_SEL);
        if (fp < NFFN / 2) {
            uint4 xv = __ldg(reinterpret_cast<const uint4*>(P.x + (tok * 1280 + rank * 640 + min(at >> 1, 39u) * 16)));
            const uint32_t m2 = __byte_perm(sv, 0, 0x3232);
            asm("sub.rn.bf16x2 %0, %0, %4;\nsub.rn.bf16x2 %1, %1, %4;\nsub.rn.bf16x2 %2, %2, %4;\nsub.rn.bf16x2 %3, %3, %4;"
                : "+r"(xv.x), "+r"(xv.y), "+r"(xv.z), "+r"(xv.w) : "r"(m2));
            mbar_wait(sb + B_DN, 0);
            if (at < 80) sts128(sb + OFF_PART + at * 16, xv.x, xv.y, xv.z, xv.w);
            mbar_wait(sb + B_GU, 0);
            mbar_wait(sb + B_EMPTY + 24, 0);
            bar_sync(4, 128);
            float c[5][4];
            uint32_t wf[10][4];
#pragma unroll
            for (int i = 0; i < 5; i++) c[i][0] = c[i][1] = c[i][2] = c[i][3] = 0.f;
            const uint32_t mi = lane >> 3, kr = c7 + (mi >> 1) * 8;
            {
                const uint32_t wa = sb + OFF_GU + (aw >> 1) * 1024 + kr * 64 + ((((aw & 1) * 2 + (mi & 1)) ^ ((kr >> 1) & 3)) << 4);
#pragma unroll
                for (uint32_t i = 0; i < NPRE; i++) ldsm_x4_t(wf[i], wa + i * 2048);
                __nanosleep(FFNS);
                BLOCK_SPLIT(tag);
#pragma unroll
                for (uint32_t i = 0; i < 20; i += 2) {
                    uint32_t xb[4];
                    ldsm_x4(xb, sb + OFF_PART + i * 64 + mi * 32 + (lane & 1) * 16);
#pragma unroll
                    for (uint32_t j = i; j < i + 2; j++) {
                        const uint32_t (&a)[4] = wf[j % NPRE];
                        mma16816(c[j & 1], a[0], a[1], a[2], a[3], xb[2 * (j & 1)], xb[2 * (j & 1) + 1]);
                        if (j + NPRE < 20) ldsm_x4_t(wf[j % NPRE], wa + (j + NPRE) * 2048);
                    }
                }
#pragma unroll
                for (int e = 0; e < 4; e++) c[0][e] += c[1][e];
                const uint32_t rd = mapa(sb, rank ^ (t & 1));
                if (t < 2)
                    asm volatile("st.async.shared::cluster.mbarrier::complete_tx::bytes.v4.f32 [%0], {%1,%2,%3,%4}, [%5];"
                                 :: "r"(rd + (t ? OFF_PART + 1280 : M_UPD + 192) + aw * 128 + g * 16), "f"(c[0][0]), "f"(c[0][1]), "f"(c[0][2]), "f"(c[0][3]), "r"(rd + B_H) : "memory");
            }
            TR(r54);
            const float rs = rcp(bflo(sv));
            const uint32_t da = sb + OFF_DN + kr * 128 + (((2 * aw + (mi & 1)) ^ c7) << 4);
            uint8_t* yp = P.scr + (G_Y + (fp % 6) * 10240 + rank * 2560 + t * 512 + aw * 128 + g * 16);
#pragma unroll
            for (int i = 0; i < 5; i++) c[i][0] = c[i][1] = c[i][2] = c[i][3] = 0.f;
#pragma unroll
            for (uint32_t j = 0; j < NPD; j++) ldsm_x4_t(wf[j], da + (j % 5) * 4096 + (j / 5) * 2048);
            mbar_wait(sb + B_H, 0);
#pragma unroll
            for (uint32_t ks = 0; ks < 2; ks++) {
                const uint32_t og = sb + ks * 128 + lane * 4 + P.up_first, ou = og ^ 256;
                const float gs = bf16r((F(lds32(og + M_UPD + 192)) + F(lds32(og + OFF_PART + 1280))) * rs);
                const float h = bf16r(gs * sigm(gs)) * bf16r((F(lds32(ou + M_UPD + 192)) + F(lds32(ou + OFF_PART + 1280))) * rs);
                const uint32_t hp = pack_bf16(h, __shfl_down_sync(0xffffffffu, h, 4));
                const uint32_t h0 = __shfl_sync(0xffffffffu, hp, t * 8 + (g & 1)), h1 = __shfl_sync(0xffffffffu, hp, t * 8 + (g & 1) + 2);
#pragma unroll
                for (uint32_t j = 0; j < 5; j++) {
                    uint32_t (&a)[4] = wf[ks * 5 + j];
                    if (ks * 5 + j >= NPD) ldsm_x4_t(a, da + j * 4096 + ks * 2048);
                    mma16816(c[j], a[0], a[1], a[2], a[3], h0, h1);
                }
            }
#pragma unroll
            for (int e = 0; e < 4; e++) {
                const float lo = (t & 1) ? c[1][e] : c[0][e], hi = (t & 1) ? c[3][e] : c[2][e];
                c[0][e] = (t & 2) ? hi : lo;
            }
            asm volatile("" : "+f"(c[0][0]), "+f"(c[4][0]) :: "memory");
            BLOCK_SPLIT(tag);
            bar_sync(8, 384);
            { red4(yp, c[0][0], c[0][2]); red4(yp + 5120, c[0][1], c[0][3]); }
            if (t == 0) { red4(yp + 2048, c[4][0], c[4][2]); red4(yp + 2048 + 5120, c[4][1], c[4][3]); }
            TR(r55);
        }
        else {
            mbar_wait(sb + B_DN, 0); mbar_wait(sb + B_GU, 0);
            bar_arrive(8, 384);
        }
        TRW(r51, 51); TRW(r30, 30); TRW(r52, 52); TRW(r53, 53); TRW(r54, 54); TRW(r55, 55); TRW(r20, 20); TRW(r22, 22);
        if (owns) {
            const uint32_t u = min(at >> 1, 39u), col = (u >> 3) * 32 + (u & 7) * 2;
            const bool mine = (tok >> 7) == rb && at < 80;
            k1 ^= ((~(int)k1) >> 31) | 0x80000000u;
            const float sg = bf16r(sigm(bfhi(k1))), rs = rcp(bflo(sv));
            uint32_t x0, x1, y0, y1, n0, n1;
            asm volatile("ld.global.nc.u16 %0, [%2];\nld.global.nc.u16 %1, [%2 + 16];" : "=r"(x0), "=r"(x1) : "l"(P.x + (tok * 1280 + hg * 160 + col)));
            const float a0 = (bflo(x0) - bfhi(sv)) * rs, a1 = (bflo(x1) - bfhi(sv)) * rs;
            bar_sync(4, 128);
#pragma unroll 1
            do {
                __nanosleep(YSL);
                uint32_t v[6][4];
#pragma unroll
                for (int r = 0; r < 6; r++) if (mine) ldg128(P.scr + (G_Y + (at & 1) * 5120 + hg * 640 + u * 16) + r * 10240, v[r][0], v[r][1], v[r][2], v[r][3]);
                y0 = U(((F(v[0][0]) + F(v[1][0])) + (F(v[2][0]) + F(v[3][0]))) + (F(v[4][0]) + F(v[5][0])));
                y1 = U(((F(v[0][1]) + F(v[1][1])) + (F(v[2][1]) + F(v[3][1]))) + (F(v[4][1]) + F(v[5][1])));
                n0 = U(((F(v[0][2]) + F(v[1][2])) + (F(v[2][2]) + F(v[3][2]))) + (F(v[4][2]) + F(v[5][2])));
                n1 = U(((F(v[0][3]) + F(v[1][3])) + (F(v[2][3]) + F(v[3][3]))) + (F(v[4][3]) + F(v[5][3])));
            } while (any(mine && (F(n0) != NFFN / 2 || F(n1) != NFFN / 2)) && ++spins < SPIN);
            const float v0 = a0 + bf16r(bf16r(F(y0)) * sg), v1 = a1 + bf16r(bf16r(F(y1)) * sg);
            const uint32_t gp = pack_bf16(v0 * sigm(v0), v1 * sigm(v1));
            if (mine) asm volatile("st.shared.u16 [%0], %1;\nst.shared.u16 [%0 + 16], %2;" :: "r"(sb + M_UPD + (at & 1) * 160 + col), "r"(gp), "r"(gp >> 16) : "memory");
            __syncwarp();
            if (lane < 2) mbar_arrive(sb + B_UPD);
            TS(56);
        }
    }
}

typedef CUresult (*EncodeFn)(CUtensorMap*, CUtensorMapDataType, cuuint32_t, void*, const cuuint64_t*, const cuuint64_t*,
                             const cuuint32_t*, const cuuint32_t*, CUtensorMapInterleave, CUtensorMapSwizzle,
                             CUtensorMapL2promotion, CUtensorMapFloatOOBfill);

bool encode(EncodeFn fn, CUtensorMap* tm, const void* ptr, cuuint64_t d0, cuuint64_t d1, cuuint64_t d2, cuuint64_t s1, cuuint64_t s2,
            cuuint32_t b0, cuuint32_t b1, cuuint32_t b2, CUtensorMapSwizzle sw) {
    const cuuint64_t dims[3] = {d0, d1, d2}, strides[2] = {s1, s2};
    const cuuint32_t box[3] = {b0, b1, b2}, es[3] = {1, 1, 1};
    return fn(tm, CU_TENSOR_MAP_DATA_TYPE_BFLOAT16, 3, const_cast<void*>(ptr), dims, strides, box, es,
              CU_TENSOR_MAP_INTERLEAVE_NONE, sw, CU_TENSOR_MAP_L2_PROMOTION_L2_128B,
              CU_TENSOR_MAP_FLOAT_OOB_FILL_NONE) == CUDA_SUCCESS;
}

}

extern "C" void kernel_launch(void* const* d_in, const int* in_sizes, int n_in, void* d_out, int out_size) {
    static Params P;
    static bool by_sm = false;
    static const void* cached[9] = {};
    bool same = cached[8] == d_out;
    for (int i = 0; i < 8; i++) same = same && cached[i] == d_in[i];
    if (!same) {
        const void *x = d_in[0], *wqkv = d_in[1], *wo = d_in[2], *wg = d_in[5], *wu = d_in[6], *wd = d_in[7];
        void* fnp = nullptr;
        cudaDriverEntryPointQueryResult qr;
        cudaGetDriverEntryPoint("cuTensorMapEncodeTiled", &fnp, cudaEnableDefault, &qr);
        EncodeFn fn = (EncodeFn)fnp;
        const CUtensorMapSwizzle S0 = CU_TENSOR_MAP_SWIZZLE_NONE, S32 = CU_TENSOR_MAP_SWIZZLE_32B, S64 = CU_TENSOR_MAP_SWIZZLE_64B,
                                 S128 = CU_TENSOR_MAP_SWIZZLE_128B;
        const bool ok = fn != nullptr &&
            encode(fn, &P.tm[T_X], x, 640, 1024, 2, 2560, 1280, 64, 64, 2, S128) &&
            encode(fn, &P.tm[T_OUT], d_out, 640, 1024, 2, 2560, 1280, 80, 16, 1, S0) &&
            encode(fn, &P.tm[T_W], wqkv, 640, 640, 3, 3840, 1280, 64, 32, 3, S128) &&
            encode(fn, &P.tm[T_WR], wqkv, 640, 640, 3, 3840, 1280, 16, 32, 3, S32) &&
            encode(fn, &P.tm[T_GU], wg < wu ? wg : wu, 1728, 640, 2, 3456, wg < wu ? (const char*)wu - (const char*)wg : (const char*)wg - (const char*)wu,
                   32, 16, 2, S64) &&
            encode(fn, &P.tm[T_D], wd, 64, 1728, 10, 1280, 128, 64, 32, 5, S128) &&
            encode(fn, &P.tm[T_WO], wo, 640, 640, 1, 1280, 1280 * 640, 32, 80, 1, S64) &&
            encode(fn, &P.tm[T_WOR], wo, 640, 640, 1, 1280, 1280 * 640, 16, 40, 1, S64);
        if (!ok) return;
        P.up_first = wg < wu ? 0 : 256;
        P.wo = (const uint8_t*)wo; P.wd = (const uint8_t*)wd;
        P.x = (const uint8_t*)x; P.w = (const uint8_t*)wqkv; P.w_r = (const uint8_t*)d_in[4];
        if (cudaGetSymbolAddress((void**)&P.scr, g_scr) != cudaSuccess) return;
        cudaFuncSetAttribute(fused_kernel<true>, cudaFuncAttributeMaxDynamicSharedMemorySize, SMEM_BYTES);
        cudaFuncSetAttribute(fused_kernel<false>, cudaFuncAttributeMaxDynamicSharedMemorySize, SMEM_BYTES);
        int ncl = 0, sms = 0, dev = 0;
        {
            cudaLaunchConfig_t cfg = {};
            cfg.gridDim = dim3(128); cfg.blockDim = dim3(NTHREADS); cfg.dynamicSmemBytes = SMEM_BYTES;
            cudaLaunchAttribute at[1];
            at[0].id = cudaLaunchAttributeClusterDimension;
            at[0].val.clusterDim.x = 2; at[0].val.clusterDim.y = 1; at[0].val.clusterDim.z = 1;
            cfg.attrs = at; cfg.numAttrs = 1;
            if (cudaOccupancyMaxActiveClusters(&ncl, fused_kernel<true>, &cfg) != cudaSuccess || ncl < 64) return;
            cudaGetDevice(&dev);
            cudaDeviceGetAttribute(&sms, cudaDevAttrMultiProcessorCount, dev);
        }
        by_sm = sms == 132 && ncl == 66;
        for (int i = 0; i < 8; i++) cached[i] = d_in[i];
        cached[8] = d_out;
    }
    if (by_sm) fused_kernel<true><<<132, NTHREADS, SMEM_BYTES>>>(P);
    else fused_kernel<false><<<128, NTHREADS, SMEM_BYTES>>>(P);
}
```

```cpp
#include <cuda_runtime.h>
#include <cuda_bf16.h>
#include <cuda.h>
#include <stdint.h>

namespace {

constexpr int DM = 640;
constexpr int NTHREADS = 512;
constexpr int NFFN = 108;
#define LEAD 3
#define PACE0 420
#define PACE1 880
#define PX0 2400
#define PX1 250
#define GU0 6000
#define GU1 220
#define GT0 2800
#define GT1 410
#define WOP 150
#define AUXS 500
#define EX1T 8100
#define EX2D 2500
#define SERAT 2
#define FFNS 400
#define NPRE 8
#define NPD 8
#define YSL 100
#define WSL 300

constexpr int ST = 47104;
constexpr int ST_BM = 16384, ST_BR = 40960;
constexpr int OFF_DN = 0;
constexpr int OFF_PART = 20480;
constexpr int OFF_WO = 22528;
constexpr int WO_SLOT = 15360;
constexpr int OFF_HO = 3 * ST;
__host__ __device__ constexpr int wo_slot(int i) { return i < 7 ? OFF_WO + i * WO_SLOT : 3 * ST + ST_BM; }
constexpr int OFF_GU = 4 * ST;
constexpr int M_ST = OFF_GU + 40960;
constexpr int M_CS = M_ST + 1024;
constexpr int M_UPD = M_CS + 1024;
constexpr int M_TOP = M_UPD + 640;
constexpr int M_SEL = M_TOP + 64;
constexpr int B_AX = M_SEL + 16, B_PREP = B_AX + 40, B_UPD = B_PREP + 8,
              B_GU = B_AX + 64, B_DN = B_GU + 8, B_H = B_DN + 8, B_SEL = B_H + 8,
              B_FULL = B_GU + 32, B_EMPTY = B_FULL + 32, B_WO = B_EMPTY + 32;
constexpr int SMEM_BYTES = B_WO + 32;
static_assert(SMEM_BYTES <= 232448 && wo_slot(1) <= ST && wo_slot(4) <= 2 * ST && wo_slot(6) + WO_SLOT <= 3 * ST, "smem");

enum { T_X, T_W, T_WR, T_GU, T_D, T_WO, T_WOR, T_OUT, T_N };
struct Params {
    CUtensorMap tm[T_N];
    const uint8_t* x;
    const uint8_t* w_r;
    const uint8_t* w;
    const uint8_t* wo;
    const uint8_t* wd;
    uint8_t* scr;
    uint32_t up_first;
};

constexpr uint32_t XB = 27392;
constexpr uint32_t G_TOP = 25600;
constexpr uint32_t G_CS = G_TOP + 1024;
constexpr uint32_t G_ST = G_CS + 128;
constexpr uint32_t G_FLAG = G_ST + 512;
constexpr uint32_t G_Y = 128 * XB;
constexpr uint32_t G_EPOCH = G_Y + 128 * 512;
static_assert(G_FLAG + 128 == XB, "scratch");
__device__ __align__(1024) uint8_t g_scr[G_EPOCH + 1024];

#define TR(v)
#define TRD(v)
#define TRW(v, i)
#define TS(i)
#define TSG(i)
constexpr unsigned SPIN = 1u << 20;

__device__ __forceinline__ void mbar_init(uint32_t bar, int cnt) {
    asm volatile("mbarrier.init.shared::cta.b64 [%0], %1;" :: "r"(bar), "r"(cnt) : "memory");
}
__device__ __forceinline__ void mbar_expect_tx(uint32_t bar, int bytes) {
    asm volatile("mbarrier.arrive.expect_tx.shared::cta.b64 _, [%0], %1;" :: "r"(bar), "r"(bytes) : "memory");
}
__device__ __forceinline__ void mbar_arrive(uint32_t bar) {
    asm volatile("mbarrier.arrive.shared::cta.b64 _, [%0];" :: "r"(bar) : "memory");
}
__device__ __forceinline__ uint32_t mapa(uint32_t a, uint32_t cta) {
    uint32_t r;
    asm("mapa.shared::cluster.u32 %0, %1, %2;" : "=r"(r) : "r"(a), "r"(cta));
    return r;
}
__device__ __forceinline__ void mbar_arrive_cl(uint32_t cbar) {
    asm volatile("mbarrier.arrive.shared::cluster.b64 _, [%0];" :: "r"(cbar) : "memory");
}
__device__ __forceinline__ void mbar_wait(uint32_t bar, int parity) {
    asm volatile("{\n.reg .pred p;\nLAB_WAIT:\nmbarrier.try_wait.parity.shared::cta.b64 p, [%0], %1;\n@!p bra LAB_WAIT;\n}"
                 :: "r"(bar), "r"(parity) : "memory");
}
__device__ __forceinline__ bool mbar_try(uint32_t bar, int parity) {
    uint32_t r;
    asm volatile("{\n.reg .pred p;\nmbarrier.test_wait.parity.shared::cta.b64 p, [%1], %2;\nselp.u32 %0, 1, 0, p;\n}"
                 : "=r"(r) : "r"(bar), "r"(parity) : "memory");
    return r != 0;
}
__device__ __forceinline__ void tma(uint32_t dst, const CUtensorMap* tm, uint32_t bar, int c0, int c1, int c2 = 0) {
    asm volatile("cp.async.bulk.tensor.3d.shared::cluster.global.mbarrier::complete_tx::bytes [%0], [%1, {%3, %4, %5}], [%2];"
                 :: "r"(dst), "l"(tm), "r"(bar), "r"(c0), "r"(c1), "r"(c2) : "memory");
}
__device__ __forceinline__ void tma_mc(uint32_t dst, const CUtensorMap* tm, uint32_t bar, int c0, int c1) {
    asm volatile("cp.async.bulk.tensor.3d.shared::cluster.global.mbarrier::complete_tx::bytes.multicast::cluster [%0], [%1, {%3, %4, %5}], [%2], %6;"
                 :: "r"(dst), "l"(tm), "r"(bar), "r"(c0), "r"(c1), "r"(0), "h"((uint16_t)3) : "memory");
}
__device__ __forceinline__ void tma_st(const CUtensorMap* tm, uint32_t src, int c0, int c1, int c2) {
    asm volatile("cp.async.bulk.tensor.3d.global.shared::cta.bulk_group [%0, {%2, %3, %4}], [%1];\ncp.async.bulk.commit_group;"
                 :: "l"(tm), "r"(src), "r"(c0), "r"(c1), "r"(c2) : "memory");
}
__device__ __forceinline__ void l2_prefetch(const void* p, int bytes) {
    asm volatile("cp.async.bulk.prefetch.L2.global [%0], %1;" :: "l"(p), "r"(bytes) : "memory");
}
__device__ __forceinline__ void cluster_arrive() { asm volatile("barrier.cluster.arrive.relaxed.aligned;" ::: "memory"); }
__device__ __forceinline__ void cluster_wait() { asm volatile("barrier.cluster.wait.aligned;" ::: "memory"); }
__device__ __forceinline__ void bar_sync(int id, int n) { asm volatile("bar.sync %0, %1;" :: "r"(id), "r"(n) : "memory"); }
__device__ __forceinline__ void bar_arrive(int id, int n) { asm volatile("bar.arrive %0, %1;" :: "r"(id), "r"(n) : "memory"); }
__device__ __forceinline__ bool bar_or(int id, int n, bool v) {
    uint32_t r;
    asm volatile("{\n.reg .pred p, q;\nsetp.ne.u32 p, %3, 0;\nbar.red.or.pred q, %1, %2, p;\nselp.u32 %0, 1, 0, q;\n}"
                 : "=r"(r) : "r"(id), "r"(n), "r"((uint32_t)v) : "memory");
    return r != 0;
}
__device__ __forceinline__ void fence_proxy_async_smem() { asm volatile("fence.proxy.async.shared::cta;" ::: "memory"); }
__device__ __forceinline__ void stg128(void* p, uint32_t a, uint32_t b, uint32_t c, uint32_t d) {
    asm volatile("{\n.reg .b64 l, h;\n.reg .b128 q;\nmov.b64 l, {%1, %2};\nmov.b64 h, {%3, %4};\nmov.b128 q, {l, h};\n"
                 "st.relaxed.gpu.global.b128 [%0], q;\n}" :: "l"(p), "r"(a), "r"(b), "r"(c), "r"(d) : "memory");
}
__device__ __forceinline__ void ldg128(const void* p, uint32_t& a, uint32_t& b, uint32_t& c, uint32_t& d) {
    asm volatile("{\n.reg .b64 l, h;\n.reg .b128 q;\nld.relaxed.gpu.global.b128 q, [%4];\nmov.b128 {l, h}, q;\n"
                 "mov.b64 {%0, %1}, l;\nmov.b64 {%2, %3}, h;\n}" : "=r"(a), "=r"(b), "=r"(c), "=r"(d) : "l"(p) : "memory");
}
__device__ __forceinline__ void red4(void* p, float a, float b) {
    asm volatile("red.relaxed.gpu.global.add.v4.f32 [%0], {%1, %2, %3, %3};" :: "l"(p), "f"(a), "f"(b), "f"(1.0f) : "memory");
}
__device__ __forceinline__ void stg32(void* p, uint32_t a) {
    asm volatile("st.relaxed.gpu.global.u32 [%0], %1;" :: "l"(p), "r"(a) : "memory");
}
__device__ __forceinline__ uint2 ldg64(const void* p) {
    uint2 v;
    asm volatile("{\n.reg .b64 l;\nld.relaxed.gpu.global.b64 l, [%2];\nmov.b64 {%0, %1}, l;\n}" : "=r"(v.x), "=r"(v.y) : "l"(p) : "memory");
    return v;
}
__device__ __forceinline__ unsigned ldg32(const void* p) {
    unsigned v;
    asm volatile("ld.relaxed.gpu.global.u32 %0, [%1];" : "=r"(v) : "l"(p) : "memory");
    return v;
}
__device__ __forceinline__ void ldsm_x4(uint32_t (&r)[4], uint32_t a) {
    asm volatile("ldmatrix.sync.aligned.m8n8.x4.shared.b16 {%0,%1,%2,%3}, [%4];"
                 : "=r"(r[0]), "=r"(r[1]), "=r"(r[2]), "=r"(r[3]) : "r"(a));
}
__device__ __forceinline__ void ldsm_x4_t(uint32_t (&r)[4], uint32_t a) {
    asm volatile("ldmatrix.sync.aligned.m8n8.x4.trans.shared.b16 {%0,%1,%2,%3}, [%4];"
                 : "=r"(r[0]), "=r"(r[1]), "=r"(r[2]), "=r"(r[3]) : "r"(a));
}
__device__ __forceinline__ void stsm_x4(uint32_t a, const uint32_t (&r)[4]) {
    asm volatile("stmatrix.sync.aligned.m8n8.x4.shared.b16 [%0], {%1,%2,%3,%4};"
                 :: "r"(a), "r"(r[0]), "r"(r[1]), "r"(r[2]), "r"(r[3]));
}
__device__ __forceinline__ uint32_t movm(uint32_t a) {
    uint32_t d;
    asm("movmatrix.sync.aligned.m8n8.trans.b16 %0, %1;" : "=r"(d) : "r"(a));
    return d;
}
__device__ __forceinline__ void mma16816(float (&c)[4], uint32_t a0, uint32_t a1, uint32_t a2, uint32_t a3, uint32_t b0, uint32_t b1) {
    asm("mma.sync.aligned.m16n8k16.row.col.f32.bf16.bf16.f32 {%0,%1,%2,%3}, {%4,%5,%6,%7}, {%8,%9}, {%0,%1,%2,%3};"
        : "+f"(c[0]), "+f"(c[1]), "+f"(c[2]), "+f"(c[3]) : "r"(a0), "r"(a1), "r"(a2), "r"(a3), "r"(b0), "r"(b1));
}
__device__ __forceinline__ void mma1688(float (&c)[4], uint32_t a0, uint32_t a1, uint32_t b0) {
    asm("mma.sync.aligned.m16n8k8.row.col.f32.bf16.bf16.f32 {%0,%1,%2,%3}, {%4,%5}, {%6}, {%0,%1,%2,%3};"
        : "+f"(c[0]), "+f"(c[1]), "+f"(c[2]), "+f"(c[3]) : "r"(a0), "r"(a1), "r"(b0));
}
__device__ __forceinline__ void wgmma_fence() { asm volatile("wgmma.fence.sync.aligned;" ::: "memory"); }
__device__ __forceinline__ void wgmma_commit() { asm volatile("wgmma.commit_group.sync.aligned;" ::: "memory"); }
template <int N> __device__ __forceinline__ void wgmma_wait() { asm volatile("wgmma.wait_group.sync.aligned %0;" :: "n"(N) : "memory"); }
__device__ __forceinline__ uint64_t mk(uint32_t lo, uint32_t hi) { return (uint64_t)lo | ((uint64_t)hi << 32); }
constexpr uint32_t HI128 = (1024 >> 4) | (1u << 30), HI64 = (512 >> 4) | (2u << 30), HI32 = (256 >> 4) | (3u << 30);
__device__ __forceinline__ uint32_t pack_bf16(float lo, float hi) {
    uint32_t r;
    asm("cvt.rn.bf16x2.f32 %0, %1, %2;" : "=r"(r) : "f"(hi), "f"(lo));
    return r;
}
__device__ __forceinline__ float bflo(uint32_t u) { return __uint_as_float(u << 16); }
__device__ __forceinline__ float bfhi(uint32_t u) { return __uint_as_float(u & 0xFFFF0000u); }
__device__ __forceinline__ float bf16r(float v) { return __uint_as_float(pack_bf16(0.f, v)); }
__device__ __forceinline__ float ex2(float v) { float r; asm("ex2.approx.ftz.f32 %0, %1;" : "=f"(r) : "f"(v)); return r; }
__device__ __forceinline__ float rcp(float v) { float r; asm("rcp.approx.ftz.f32 %0, %1;" : "=f"(r) : "f"(v)); return r; }
__device__ __forceinline__ float sqrt_a(float v) { float r; asm("sqrt.approx.ftz.f32 %0, %1;" : "=f"(r) : "f"(v)); return r; }
__device__ __forceinline__ float tanh_a(float v) { float r; asm("tanh.approx.f32 %0, %1;" : "=f"(r) : "f"(v)); return r; }
constexpr float LOG2E = 1.4426950408889634f;
__device__ __forceinline__ float sigm(float v) { return rcp(1.0f + ex2(-LOG2E * v)); }
__device__ __forceinline__ uint4 lds128(uint32_t a) {
    uint4 v;
    asm volatile("ld.shared.v4.u32 {%0,%1,%2,%3}, [%4];" : "=r"(v.x), "=r"(v.y), "=r"(v.z), "=r"(v.w) : "r"(a));
    return v;
}
__device__ __forceinline__ float2 lds64f(uint32_t a) {
    float2 v;
    asm volatile("ld.shared.v2.f32 {%0,%1}, [%2];" : "=f"(v.x), "=f"(v.y) : "r"(a));
    return v;
}
__device__ __forceinline__ uint32_t lds32(uint32_t a) {
    uint32_t v;
    asm volatile("ld.shared.u32 %0, [%1];" : "=r"(v) : "r"(a));
    return v;
}
__device__ __forceinline__ void sts128(uint32_t a, uint32_t x, uint32_t y, uint32_t z, uint32_t w) {
    asm volatile("st.shared.v4.u32 [%0], {%1,%2,%3,%4};" :: "r"(a), "r"(x), "r"(y), "r"(z), "r"(w) : "memory");
}
__device__ __forceinline__ void sts64(uint32_t a, uint32_t x, uint32_t y) {
    asm volatile("st.shared.v2.u32 [%0], {%1,%2};" :: "r"(a), "r"(x), "r"(y) : "memory");
}
__device__ __forceinline__ void sts32(uint32_t a, uint32_t x) { asm volatile("st.shared.u32 [%0], %1;" :: "r"(a), "r"(x) : "memory"); }
__device__ __forceinline__ unsigned redux_max(unsigned v) {
    unsigned r;
    asm volatile("redux.sync.max.u32 %0, %1, 0xffffffff;" : "=r"(r) : "r"(v));
    return r;
}
__device__ __forceinline__ float shx(float v, int o) { return __shfl_xor_sync(0xffffffffu, v, o); }
__device__ __forceinline__ uint32_t U(float v) { return __float_as_uint(v); }
__device__ __forceinline__ float F(uint32_t v) { return __uint_as_float(v); }

__device__ __forceinline__ void wgmma_n192_lo(float (&d)[120], uint64_t da, uint64_t db, int scale_d) {
    asm volatile("{\n.reg .pred p;\nsetp.ne.b32 p, %98, 0;\n"
        "wgmma.mma_async.sync.aligned.m64n192k16.f32.bf16.bf16 "
        "{%0, %1, %2, %3, %4, %5, %6, %7, %8, %9, %10, %11, %12, %13, %14, %15, "
        "%16, %17, %18, %19, %20, %21, %22, %23, %24, %25, %26, %27, %28, %29, %30, %31, "
        "%32, %33, %34, %35, %36, %37, %38, %39, %40, %41, %42, %43, %44, %45, %46, %47, "
        "%48, %49, %50, %51, %52, %53, %54, %55, %56, %57, %58, %59, %60, %61, %62, %63, "
        "%64, %65, %66, %67, %68, %69, %70, %71, %72, %73, %74, %75, %76, %77, %78, %79, "
        "%80, %81, %82, %83, %84, %85, %86, %87, %88, %89, %90, %91, %92, %93, %94, %95}, "
        "%96, %97, p, 1, 1, 0, 1;\n}\n"
        : "+f"(d[0]), "+f"(d[1]), "+f"(d[2]), "+f"(d[3]), "+f"(d[4]), "+f"(d[5]), "+f"(d[6]), "+f"(d[7]),
          "+f"(d[8]), "+f"(d[9]), "+f"(d[10]), "+f"(d[11]), "+f"(d[12]), "+f"(d[13]), "+f"(d[14]), "+f"(d[15]),
          "+f"(d[16]), "+f"(d[17]), "+f"(d[18]), "+f"(d[19]), "+f"(d[20]), "+f"(d[21]), "+f"(d[22]), "+f"(d[23]),
          "+f"(d[24]), "+f"(d[25]), "+f"(d[26]), "+f"(d[27]), "+f"(d[28]), "+f"(d[29]), "+f"(d[30]), "+f"(d[31]),
          "+f"(d[32]), "+f"(d[33]), "+f"(d[34]), "+f"(d[35]), "+f"(d[36]), "+f"(d[37]), "+f"(d[38]), "+f"(d[39]),
          "+f"(d[40]), "+f"(d[41]), "+f"(d[42]), "+f"(d[43]), "+f"(d[44]), "+f"(d[45]), "+f"(d[46]), "+f"(d[47]),
          "+f"(d[48]), "+f"(d[49]), "+f"(d[50]), "+f"(d[51]), "+f"(d[52]), "+f"(d[53]), "+f"(d[54]), "+f"(d[55]),
          "+f"(d[56]), "+f"(d[57]), "+f"(d[58]), "+f"(d[59]), "+f"(d[60]), "+f"(d[61]), "+f"(d[62]), "+f"(d[63]),
          "+f"(d[64]), "+f"(d[65]), "+f"(d[66]), "+f"(d[67]), "+f"(d[68]), "+f"(d[69]), "+f"(d[70]), "+f"(d[71]),
          "+f"(d[72]), "+f"(d[73]), "+f"(d[74]), "+f"(d[75]), "+f"(d[76]), "+f"(d[77]), "+f"(d[78]), "+f"(d[79]),
          "+f"(d[80]), "+f"(d[81]), "+f"(d[82]), "+f"(d[83]), "+f"(d[84]), "+f"(d[85]), "+f"(d[86]), "+f"(d[87]),
          "+f"(d[88]), "+f"(d[89]), "+f"(d[90]), "+f"(d[91]), "+f"(d[92]), "+f"(d[93]), "+f"(d[94]), "+f"(d[95])
        : "l"(da), "l"(db), "r"(scale_d));
}
__device__ __forceinline__ void wgmma_n48_hi(float (&d)[120], uint64_t da, uint64_t db, int scale_d) {
    asm volatile("{\n.reg .pred p;\nsetp.ne.b32 p, %26, 0;\n"
        "wgmma.mma_async.sync.aligned.m64n48k16.f32.bf16.bf16 "
        "{%0, %1, %2, %3, %4, %5, %6, %7, %8, %9, %10, %11, %12, %13, %14, %15, "
        "%16, %17, %18, %19, %20, %21, %22, %23}, "
        "%24, %25, p, 1, 1, 0, 1;\n}\n"
        : "+f"(d[96]), "+f"(d[97]), "+f"(d[98]), "+f"(d[99]), "+f"(d[100]), "+f"(d[101]), "+f"(d[102]), "+f"(d[103]),
          "+f"(d[104]), "+f"(d[105]), "+f"(d[106]), "+f"(d[107]), "+f"(d[108]), "+f"(d[109]), "+f"(d[110]), "+f"(d[111]),
          "+f"(d[112]), "+f"(d[113]), "+f"(d[114]), "+f"(d[115]), "+f"(d[116]), "+f"(d[117]), "+f"(d[118]), "+f"(d[119])
        : "l"(da), "l"(db), "r"(scale_d));
}
__device__ __forceinline__ void wgmma_rs_n80(float (&d)[40], uint32_t a0, uint32_t a1, uint32_t a2, uint32_t a3, uint64_t db, int scale_d) {
    asm volatile("{\n.reg .pred p;\nsetp.ne.b32 p, %45, 0;\n"
        "wgmma.mma_async.sync.aligned.m64n80k16.f32.bf16.bf16 "
        "{%0, %1, %2, %3, %4, %5, %6, %7, %8, %9, %10, %11, %12, %13, %14, %15, "
        "%16, %17, %18, %19, %20, %21, %22, %23, %24, %25, %26, %27, %28, %29, %30, %31, "
        "%32, %33, %34, %35, %36, %37, %38, %39}, "
        "{%40, %41, %42, %43}, %44, p, 1, 1, 1;\n}\n"
        : "+f"(d[0]), "+f"(d[1]), "+f"(d[2]), "+f"(d[3]), "+f"(d[4]), "+f"(d[5]), "+f"(d[6]), "+f"(d[7]),
          "+f"(d[8]), "+f"(d[9]), "+f"(d[10]), "+f"(d[11]), "+f"(d[12]), "+f"(d[13]), "+f"(d[14]), "+f"(d[15]),
          "+f"(d[16]), "+f"(d[17]), "+f"(d[18]), "+f"(d[19]), "+f"(d[20]), "+f"(d[21]), "+f"(d[22]), "+f"(d[23]),
          "+f"(d[24]), "+f"(d[25]), "+f"(d[26]), "+f"(d[27]), "+f"(d[28]), "+f"(d[29]), "+f"(d[30]), "+f"(d[31]),
          "+f"(d[32]), "+f"(d[33]), "+f"(d[34]), "+f"(d[35]), "+f"(d[36]), "+f"(d[37]), "+f"(d[38]), "+f"(d[39])
        : "r"(a0), "r"(a1), "r"(a2), "r"(a3), "l"(db), "r"(scale_d));
}
__device__ __forceinline__ void wgmma_rs_n192_lo(float (&d)[120], uint32_t a0, uint32_t a1, uint32_t a2, uint32_t a3, uint64_t db, int scale_d) {
    asm volatile("{\n.reg .pred p;\nsetp.ne.b32 p, %101, 0;\n"
        "wgmma.mma_async.sync.aligned.m64n192k16.f32.bf16.bf16 "
        "{%0, %1, %2, %3, %4, %5, %6, %7, %8, %9, %10, %11, %12, %13, %14, %15, "
        "%16, %17, %18, %19, %20, %21, %22, %23, %24, %25, %26, %27, %28, %29, %30, %31, "
        "%32, %33, %34, %35, %36, %37, %38, %39, %40, %41, %42, %43, %44, %45, %46, %47, "
        "%48, %49, %50, %51, %52, %53, %54, %55, %56, %57, %58, %59, %60, %61, %62, %63, "
        "%64, %65, %66, %67, %68, %69, %70, %71, %72, %73, %74, %75, %76, %77, %78, %79, "
        "%80, %81, %82, %83, %84, %85, %86, %87, %88, %89, %90, %91, %92, %93, %94, %95}, "
        "{%96, %97, %98, %99}, %100, p, 1, 1, 1;\n}\n"
        : "+f"(d[0]), "+f"(d[1]), "+f"(d[2]), "+f"(d[3]), "+f"(d[4]), "+f"(d[5]), "+f"(d[6]), "+f"(d[7]),
          "+f"(d[8]), "+f"(d[9]), "+f"(d[10]), "+f"(d[11]), "+f"(d[12]), "+f"(d[13]), "+f"(d[14]), "+f"(d[15]),
          "+f"(d[16]), "+f"(d[17]), "+f"(d[18]), "+f"(d[19]), "+f"(d[20]), "+f"(d[21]), "+f"(d[22]), "+f"(d[23]),
          "+f"(d[24]), "+f"(d[25]), "+f"(d[26]), "+f"(d[27]), "+f"(d[28]), "+f"(d[29]), "+f"(d[30]), "+f"(d[31]),
          "+f"(d[32]), "+f"(d[33]), "+f"(d[34]), "+f"(d[35]), "+f"(d[36]), "+f"(d[37]), "+f"(d[38]), "+f"(d[39]),
          "+f"(d[40]), "+f"(d[41]), "+f"(d[42]), "+f"(d[43]), "+f"(d[44]), "+f"(d[45]), "+f"(d[46]), "+f"(d[47]),
          "+f"(d[48]), "+f"(d[49]), "+f"(d[50]), "+f"(d[51]), "+f"(d[52]), "+f"(d[53]), "+f"(d[54]), "+f"(d[55]),
          "+f"(d[56]), "+f"(d[57]), "+f"(d[58]), "+f"(d[59]), "+f"(d[60]), "+f"(d[61]), "+f"(d[62]), "+f"(d[63]),
          "+f"(d[64]), "+f"(d[65]), "+f"(d[66]), "+f"(d[67]), "+f"(d[68]), "+f"(d[69]), "+f"(d[70]), "+f"(d[71]),
          "+f"(d[72]), "+f"(d[73]), "+f"(d[74]), "+f"(d[75]), "+f"(d[76]), "+f"(d[77]), "+f"(d[78]), "+f"(d[79]),
          "+f"(d[80]), "+f"(d[81]), "+f"(d[82]), "+f"(d[83]), "+f"(d[84]), "+f"(d[85]), "+f"(d[86]), "+f"(d[87]),
          "+f"(d[88]), "+f"(d[89]), "+f"(d[90]), "+f"(d[91]), "+f"(d[92]), "+f"(d[93]), "+f"(d[94]), "+f"(d[95])
        : "r"(a0), "r"(a1), "r"(a2), "r"(a3), "l"(db), "r"(scale_d));
}
__device__ __forceinline__ void wgmma_rs_n48_hi(float (&d)[120], uint32_t a0, uint32_t a1, uint32_t a2, uint32_t a3, uint64_t db, int scale_d) {
    asm volatile("{\n.reg .pred p;\nsetp.ne.b32 p, %29, 0;\n"
        "wgmma.mma_async.sync.aligned.m64n48k16.f32.bf16.bf16 "
        "{%0, %1, %2, %3, %4, %5, %6, %7, %8, %9, %10, %11, %12, %13, %14, %15, "
        "%16, %17, %18, %19, %20, %21, %22, %23}, "
        "{%24, %25, %26, %27}, %28, p, 1, 1, 1;\n}\n"
        : "+f"(d[96]), "+f"(d[97]), "+f"(d[98]), "+f"(d[99]), "+f"(d[100]), "+f"(d[101]), "+f"(d[102]), "+f"(d[103]),
          "+f"(d[104]), "+f"(d[105]), "+f"(d[106]), "+f"(d[107]), "+f"(d[108]), "+f"(d[109]), "+f"(d[110]), "+f"(d[111]),
          "+f"(d[112]), "+f"(d[113]), "+f"(d[114]), "+f"(d[115]), "+f"(d[116]), "+f"(d[117]), "+f"(d[118]), "+f"(d[119])
        : "r"(a0), "r"(a1), "r"(a2), "r"(a3), "l"(db), "r"(scale_d));
}
__device__ __forceinline__ constexpr int jt_of(int sec, int c, bool odd) {
    return odd ? (c >= 2 ? sec * 8 + c - 2 : 24 + sec * 2 + c) : (c < 8 ? sec * 8 + c : 24 + sec * 2 + (c - 8));
}
#define BOTH(...) if (hg & 1) { constexpr bool odd = true; __VA_ARGS__ } else { constexpr bool odd = false; __VA_ARGS__ }

__device__ __forceinline__ bool elect() {
    uint32_t r;
    asm volatile("{\n.reg .pred p;\nelect.sync _|p, 0xffffffff;\nselp.u32 %0, 1, 0, p;\n}" : "=r"(r));
    return r != 0;
}
__device__ __forceinline__ uint32_t clock32() { uint32_t r; asm volatile("mov.u32 %0, %%clock;" : "=r"(r)); return r; }
#define BLOCK_SPLIT(v) asm volatile("{\n.reg .pred p;\nLAB_SPLIT:\nsetp.eq.u32 p, %0, 0;\n@p nanosleep.u32 1;\n@p bra LAB_SPLIT;\n}" :: "r"(v) : "memory")
__device__ __forceinline__ bool any(bool v) { return __any_sync(0xffffffffu, v); }
__device__ __forceinline__ uint32_t opaque_tid() { uint32_t r; asm volatile("mov.u32 %0, %%tid.x;" : "=r"(r)); return r; }

template <bool BY_SM>
__global__ void __cluster_dims__(2, 1, 1) __launch_bounds__(NTHREADS, 1)
fused_kernel(const __grid_constant__ Params P) {
    extern __shared__ __align__(1024) uint8_t smem[];
    const uint32_t sb = (uint32_t)__cvta_generic_to_shared(smem);
    const uint32_t warp = __shfl_sync(0xffffffffu, threadIdx.x >> 5, 0);
    const uint32_t rank = blockIdx.x & 1;
    constexpr uint32_t sbd = 1024 >> 4;
    const uint32_t t0 = clock32();
    if (warp >= 10 && elect()) {
        const uint32_t bb = sb + B_AX - 320 + warp * 32;
        const int cnt = warp < 12 ? 8 : (warp == 14 ? 16 : 1);
        mbar_init(bb, cnt); mbar_init(bb + 8, cnt); mbar_init(bb + 16, cnt); mbar_init(bb + 24, cnt);
        if (warp == 12) { mbar_expect_tx(sb + B_H, 1024); mbar_expect_tx(sb + B_GU, 40960); }
        if (warp == 13) mbar_expect_tx(sb + B_FULL + 16, ST);
        asm volatile("fence.mbarrier_init.release.cluster;" ::: "memory");
    }
    __syncwarp();
    cluster_arrive();
    if (warp < 3 && elect()) asm volatile("prefetch.tensormap [%0];" :: "l"(&P.tm[warp]) : "memory");
    if (warp - 3 < 2 && blockIdx.x < 128 && elect()) l2_prefetch(P.w + ((warp - 3) * 5 * 245760 + blockIdx.x * 1920), 1920);
    if ((sb & 0xFFFFFF) != 1024) __trap();
    uint32_t gpc = blockIdx.x >> 4, pos = (blockIdx.x >> 1) & 7;
    if (BY_SM) {
        uint32_t tpc;
        asm("mov.u32 %0, %%smid;" : "=r"(tpc));
        tpc >>= 1;
        if (tpc - 60 < 2) {
            __nanosleep(2000);
            return;
        }
        const uint32_t q = ((tpc - 32) * 37) >> 8;
        gpc = tpc < 32 ? tpc & 7 : (tpc < 60 ? tpc - 31 - 7 * q : 0);
        pos = tpc < 32 ? tpc >> 3 : (tpc < 60 ? 4 + q : tpc - 58);
    }
    const uint32_t hg = (0x62740351u >> (4 * pos)) & 7, rb = gpc * 2 + rank, fp = 8 * pos + gpc - 10;
    const uint32_t b = rb * 8 + hg;
    const uint32_t k0 = (((hg >> 2) ^ (rb >> 1)) & 1) * 320;

    if (warp == 13 && elect()) tma(sb + 2 * ST, &P.tm[T_X], sb + B_FULL + 16, k0, rb * 64);
    if (warp == 12) {
        cluster_wait();
        if (elect()) {
            tma_mc(sb + 2 * ST + ST_BM + rank * 12288, &P.tm[T_W], sb + B_FULL + 16, hg * 80 + (hg & 1) * 16, k0 + rank * 32);
            tma_mc(sb + 2 * ST + ST_BR + rank * 3072, &P.tm[T_WR], sb + B_FULL + 16, hg * 80 + 64 - (hg & 1) * 64, k0 + rank * 32);
        }
        __syncwarp();
    }

    if (warp < 8) {
        asm volatile("setmaxnreg.inc.sync.aligned.u32 208;");
        const uint32_t lane = opaque_tid() & 31, g = lane >> 2, t = lane & 3;
        const uint32_t p = warp >> 2, w = warp & 3;
        const uint32_t empty_cl = mapa(sb + B_EMPTY, lane & 1);
        uint8_t* const orow = P.scr + (rb * (8 * XB) + warp * 2560 + lane * 16);
        const uint32_t ta = sb + warp * 2560 + (lane & 15) * 160 + (lane >> 4) * 16;
        uint32_t A[5][20];
        uint32_t xr[5][4], gf[5][4];
        TRD(r12); TRD(r32); TRD(r34); TRD(r22); TRD(r44);
        uint32_t par;
        uint8_t* const halo = orow + (hg * XB + (8 + p - warp) * 2560);
        uint8_t* const flag = P.scr + (G_FLAG + b * XB + w * 8 + p * 4);
        cluster_wait();
        {
            float acc[120];
            bool ok, prep;
            float2 s0, s1;
            uint32_t xa[5], cap[2] = {0u, 0u};
#pragma unroll
            for (uint32_t j = 0; j < 5; j++) {
                const uint32_t cg = 5 * hg + (j < 4 ? j + (hg & 1) : (~hg & 1) * 4);
                xa[j] = (sb + (warp * 16 + (lane & 15)) * 128 + (((lane >> 4) ^ (lane & 7)) << 4)) ^ ((cg & 3) << 5);
                const uint32_t i = cg >> 2, late = (i >= 5) ^ (k0 != 0), bit = 1u << (5 * (i >= 5 ? i - 5 : i) + j);
                cap[0] |= late ? 0u : bit; cap[1] |= late ? bit : 0u;
            }
            uint32_t sta = sb + M_ST + (warp * 16 + g) * 8;
            asm volatile("" : "+r"(sta), "+r"(cap[0]), "+r"(cap[1]), "+r"(xa[0]), "+r"(xa[1]), "+r"(xa[2]), "+r"(xa[3]), "+r"(xa[4]));
            mbar_wait(sb + B_FULL + 16, 0);
#pragma unroll
            for (uint32_t kb = 2; kb < 12; kb++) {
                const uint32_t s = kb & 3;
                const bool hold = kb == 12 - LEAD && p;
                if (hold) {
                    wgmma_wait<0>();
                    if (lane < 2) mbar_arrive_cl(empty_cl + 8 * ((11 - LEAD) & 3));
                    bar_sync(1, 256);
                }
                wgmma_fence();
                const uint32_t st = sbd + s * (ST >> 4);
#pragma unroll
                for (int ks = 0; ks < 4; ks++) {
                    const uint64_t da = mk(st + p * 512 + ks * 2 + 0x10000, HI128);
                    wgmma_n48_hi(acc, da, mk(st + (ST_BR >> 4) + (ks >> 1) * 192 + (ks & 1) * 32 + (64 << 16), HI32), ks || kb > 2);
                    wgmma_n192_lo(acc, da, mk(st + (ST_BM >> 4) + (ks >> 1) * 768 + (ks & 1) * 128 + (256 << 16), HI128), ks || kb > 2);
                    if (ks == 0) {
                        wgmma_commit();
                        wgmma_wait<1>();
                        if (!hold && kb > 2 && lane < 2) mbar_arrive_cl(empty_cl + 8 * ((kb - 1) & 3));
                    }
                    if (ks == 1) {
#pragma unroll
                        for (uint32_t j = 0; j < 5; j++)
                            if ((cap[kb >= 7] >> (5 * ((kb - 2) % 5) + j)) & 1) ldsm_x4(xr[j], xa[j] + s * ST);
                        if (w == 3 && kb < 7) stg128(halo + (kb - 2) * 512, 0u, 0u, 0u, 0u);
                        if (lane == 0 && kb == 2) stg32(flag, 0u);
                        if (kb < 11) ok = mbar_try(sb + B_FULL + 8 * ((kb + 1) & 3), ((kb - 1) >> 2) & 1);
                        if (kb == 10) prep = mbar_try(sb + B_PREP, 0);
                        if (kb == 11 && prep) {
                            s0 = lds64f(sta); s1 = lds64f(sta + 64);
                            par = lds32(sb + M_SEL + 8);
                        }
                    }
                }
                wgmma_commit();
                if (kb < 11 && !ok) mbar_wait(sb + B_FULL + 8 * ((kb + 1) & 3), ((kb - 1) >> 2) & 1);
            }
            if (!prep) {
                mbar_wait(sb + B_PREP, 0);
                s0 = lds64f(sta); s1 = lds64f(sta + 64);
                par = lds32(sb + M_SEL + 8);
            }
            {
                const uint32_t a0 = t ? 0u : __byte_perm(U(-s0.y), 0, 0x3232), a1 = t ? 0u : __byte_perm(U(-s1.y), 0, 0x3232);
                wgmma_fence();
                wgmma_rs_n48_hi(acc, a0, a1, 0u, 0u, mk(sbd + (M_CS >> 4) + 48, 2), 1);
                wgmma_rs_n192_lo(acc, a0, a1, 0u, 0u, mk(sbd + (M_CS >> 4), 2), 1);
                wgmma_commit();
            }
            if (!p) bar_arrive(1, 256);
            wgmma_wait<1>();
            if (lane < 2) mbar_arrive_cl(empty_cl + 24);
            wgmma_wait<0>();
#pragma unroll
            for (int i = 0; i < 120; i++) asm volatile("" : "+f"(acc[i]) :: "memory");
            TR(r12);
            uint32_t Q[10], Ql[10], KX[10], VX[10], Y[20];
#define KI(c) ((c) == 2 ? 8 : (c) == 7 ? 9 : (c) - ((c) > 2) - ((c) > 7))
#define KY(c) Y[KI(c)]
#define VY(c) Y[10 + (c)]
            uint32_t Z[20];
            const bool start = w == 0 && rb == 0, remote = w == 0 && rb != 0;
            const uint32_t slot = sb + OFF_HO + p * 8192 + w * 2560 - 2560 + lane * 16;
            {
                BOTH(_Pragma("unroll") for (int c = 0; c < 10; c++) {
                    const int jk = jt_of(1, c, odd), jv = jt_of(2, c, odd);
                    VY(c) = movm(pack_bf16(acc[4 * jv + 2] * s1.x, acc[4 * jv + 3] * s1.x));
                    KY(c) = pack_bf16(acc[4 * jk + 2] * s1.x, acc[4 * jk + 3] * s1.x);
                    asm volatile("" : "+r"(KY(c)), "+r"(VY(c)));
                })
                if (w == 3) {
#pragma unroll
                    for (int j = 0; j < 5; j++) {
                        Y[4 * j] = (Y[4 * j] & ~0x10001u) | par;
                        stg128(halo + j * 512, Y[4 * j], Y[4 * j + 1], Y[4 * j + 2], Y[4 * j + 3]);
                    }
                } else {
#pragma unroll
                    for (int j = 0; j < 5; j++) sts128(slot + 2560 + j * 512, Y[4 * j], Y[4 * j + 1], Y[4 * j + 2], Y[4 * j + 3]);
                }
                BOTH(_Pragma("unroll") for (int c = 0; c < 10; c++) {
                    const int jk = jt_of(1, c, odd), jv = jt_of(2, c, odd);
                    KX[c] = pack_bf16(acc[4 * jk] * s0.x, acc[4 * jk + 1] * s0.x);
                    VX[c] = movm(pack_bf16(acc[4 * jv] * s0.x, acc[4 * jv + 1] * s0.x));
                    asm volatile("" : "+r"(KX[c]), "+r"(VX[c]));
                })
                bar_sync(2 + p, 128);
                if (remote) {
#pragma unroll
                    for (int j = 0; j < 5; j++) ldg128(halo - 8 * XB + j * 512, Z[4 * j], Z[4 * j + 1], Z[4 * j + 2], Z[4 * j + 3]);
                } else {
#pragma unroll
                    for (int j = 0; j < 5; j++) {
                        const uint4 v = lds128(slot + (w ? 0 : 2560) + j * 512);
                        Z[4 * j] = v.x; Z[4 * j + 1] = v.y; Z[4 * j + 2] = v.z; Z[4 * j + 3] = v.w;
                    }
                }
                BOTH(_Pragma("unroll") for (int c = 0; c < 10; c++) {
                    const int jq = jt_of(0, c, odd);
                    Ql[c] = pack_bf16(acc[4 * jq], acc[4 * jq + 1]);
                    Q[c] = pack_bf16(acc[4 * jq + 2], acc[4 * jq + 3]);
                    asm volatile("" : "+r"(Ql[c]), "+r"(Q[c]));
                })
            }
            auto scores = [&](float (&l)[4], const uint32_t (&q)[10], const uint32_t (&z)[20], const int c0, const uint32_t mx, const float nz) {
                const uint32_t qa = t < 2 ? q[c0 + 2] : 0u, qb = t < 2 ? 0u : q[c0 + 2];
                float xa[4] = {0.f, 0.f, 0.f, 0.f}, za[4] = {nz, nz, nz, nz}, xb[4], zb[4];
                mma1688(xa, qa, qb, KX[c0 + 2]);
                mma1688(za, qa, qb, z[KI(c0 + 2)]);
#pragma unroll
                for (int e = 0; e < 4; e++) { xb[e] = xa[e]; zb[e] = za[e]; }
                mma16816(xa, q[c0], q[c0 + 3], q[c0 + 1], q[c0 + 4], KX[c0], KX[c0 + 1]);
                mma16816(za, q[c0], q[c0 + 3], q[c0 + 1], q[c0 + 4], z[KI(c0)], z[KI(c0 + 1)]);
                mma16816(xb, q[c0], q[c0 + 3], q[c0 + 1], q[c0 + 4], KX[c0 + 3], KX[c0 + 4]);
                mma16816(zb, q[c0], q[c0 + 3], q[c0 + 1], q[c0 + 4], z[KI(c0 + 3)], z[KI(c0 + 4)]);
                const bool h0 = mx & 1u, h1 = (int)mx < 0;
                l[0] = h0 ? xa[0] : za[0]; l[1] = h1 ? xa[1] : za[1];
                l[2] = h0 ? xb[2] : zb[2]; l[3] = h1 ? xb[3] : zb[3];
                asm volatile("" : "+f"(l[0]), "+f"(l[1]), "+f"(l[2]), "+f"(l[3]));
            };
            auto soft = [&](uint32_t (&pr)[2], const float (&l)[4], const float sq) {
                float m0 = fmaxf(l[0], l[1]), m1 = fmaxf(l[2], l[3]);
                m0 = fmaxf(m0, shx(m0, 1)); m1 = fmaxf(m1, shx(m1, 1));
                m0 = fmaxf(m0, shx(m0, 2)) * -sq; m1 = fmaxf(m1, shx(m1, 2)) * -sq;
                pr[0] = pack_bf16(ex2(fmaf(l[0], sq, m0)), ex2(fmaf(l[1], sq, m0)));
                pr[1] = pack_bf16(ex2(fmaf(l[2], sq, m1)), ex2(fmaf(l[3], sq, m1)));
                asm volatile("" : "+r"(pr[0]), "+r"(pr[1]));
            };
            auto values = [&](const uint32_t (&pr)[2], const uint32_t (&z)[20], const int c0, const uint32_t mx, const int h) {
                float dn[4] = {0.f, 0.f, 0.f, 0.f};
                mma1688(dn, pr[0], pr[1], 0x3F803F80u);
                const float i0 = rcp(dn[0]), i1 = rcp(dn[2]), i2 = t < 2 ? i0 : i1;
#pragma unroll
                for (int c = 0; c < 5; c++) {
                    float oc[4] = {0.f, 0.f, 0.f, 0.f};
                    mma16816(oc, pr[0] & mx, pr[1] & mx, pr[0] & ~mx, pr[1] & ~mx, VX[c0 + c], z[10 + c0 + c]);
                    const bool first = c < 2 || (c == 2 && t < 2);
                    const float iv = c < 2 ? i0 : (c > 2 ? i1 : i2);
                    A[0][2 * (c0 + c) + h] = pack_bf16((first ? oc[0] : oc[2]) * iv, (first ? oc[1] : oc[3]) * iv);
                    asm volatile("" : "+r"(A[0][2 * (c0 + c) + h]));
                }
            };
            auto gate = [&]() {
                const float r0 = 0.5f * s0.x, r1 = 0.5f * s1.x, n0 = -r0 * s0.y, n1 = -r1 * s1.y;
#pragma unroll
                for (int j = 0; j < 5; j++) {
#pragma unroll
                    for (int q = 0; q < 4; q++) {
                        const float v0 = fmaf(bflo(xr[j][q]), q & 1 ? r1 : r0, q & 1 ? n1 : n0), v1 = fmaf(bfhi(xr[j][q]), q & 1 ? r1 : r0, q & 1 ? n1 : n0);
                        gf[j][q] = pack_bf16(fmaf(v0, tanh_a(v0), v0), fmaf(v1, tanh_a(v1), v1));
                        asm volatile("" : "+r"(gf[j][q]));
                    }
                }
            };
            const uint32_t mo = (2 * t > g ? 0xFFFFu : 0u) | (2 * t + 1 > g ? 0xFFFF0000u : 0u);
            constexpr float SC = 0.22360679774997896f * LOG2E;
            {
                float l[4][4];
                uint32_t pr[4][2];
                unsigned spins = 0;
#pragma unroll 1
                while (remote && any((Z[0] & Z[4] & Z[8] & Z[12] & Z[16] & par) == 0u) && ++spins < SPIN) {
#pragma unroll
                    for (int j = 0; j < 5; j++) ldg128(halo - 8 * XB + j * 512, Z[4 * j], Z[4 * j + 1], Z[4 * j + 2], Z[4 * j + 3]);
                }
                TR(r32);
                const float nz = start ? -INFINITY : 0.f;
                auto publish = [&](const int j) {
                    A[0][4 * j] = (A[0][4 * j] & ~0x10001u) | par;
                    stg128(orow + hg * XB + j * 512, A[0][4 * j], A[0][4 * j + 1], A[0][4 * j + 2], A[0][4 * j + 3]);
                };
                scores(l[0], Q, Y, 0, mo, 0.f);
                scores(l[2], Ql, Z, 0, ~mo, nz);
                scores(l[1], Q, Y, 5, mo, 0.f);
                scores(l[3], Ql, Z, 5, ~mo, nz);
                soft(pr[0], l[0], s1.x * SC);
                soft(pr[2], l[2], s0.x * SC);
                soft(pr[1], l[1], s1.x * SC);
                soft(pr[3], l[3], s0.x * SC);
                values(pr[0], Y, 0, mo, 1);
                values(pr[2], Z, 0, ~mo, 0);
                publish(0);
                if (lane == 0 && !p) stg32(flag, par);
                publish(1);
                values(pr[1], Y, 5, mo, 1);
                values(pr[3], Z, 5, ~mo, 0);
                publish(2); publish(3); publish(4);
            }
            if (lane == 0 && p) stg32(flag, par);
            TR(r34);
            if (p) bar_arrive(8, 384);
            BLOCK_SPLIT(par);
            gate();
        }
        {
            float acc2[40];
            unsigned spins = 0;
            bool again, first = true;
            const uint8_t* src[7];
#pragma unroll
            for (uint32_t i = 0; i < 7; i++) { src[i] = orow + (i >= hg ? XB : 0u); asm volatile("" : "+l"(src[i])); }
            mbar_wait(sb + B_SEL, 0);
            const float2 sel = lds64f(sb + M_SEL);
            uint32_t routed = (U(sel.x) >> 4) == warp || (U(sel.y) >> 4) == warp;
            asm volatile("" : "+r"(routed));
            BLOCK_SPLIT(par);
            if (p) bar_sync(9, 288); else bar_sync(5, 160);
#pragma unroll 1
            do {
#pragma unroll
                for (uint32_t i = 1; i < 5; i++)
#pragma unroll
                    for (int j = 0; j < 5; j++)
                        ldg128(src[i - 1] + (i - 1) * XB + j * 512, A[i][4 * j], A[i][4 * j + 1], A[i][4 * j + 2], A[i][4 * j + 3]);
                if (!p && first) bar_sync(8, 384);
                uint32_t mn = par;
#pragma unroll
                for (int i = 0; i < 8; i++) {
                    const uint32_t (&a)[20] = A[i % 5];
                    if (i == 4 && !p && first) bar_sync(6, 160);
                    wgmma_fence();
#pragma unroll
                    for (int j = 0; j < 5; j++) {
                        wgmma_rs_n80(acc2, a[4 * j], a[4 * j + 1], a[4 * j + 2], a[4 * j + 3],
                                     mk(sbd + (wo_slot(i) >> 4) + j * 64 + (320 << 16), HI64), i || j);
                        if (i == 7 && j == 2) {
#pragma unroll
                            for (int q = 0; q < 5; q++) mn &= A[q][0] & A[q][4] & A[q][8] & A[q][12] & A[q][16];
                            again = bar_or(2 + p, 128, mn == 0u && ++spins < SPIN);
                        }
                    }
                    if (i < 4 || i == 7) wgmma_commit();
                    if (i == SERAT && !p && first) bar_arrive(9, 288);
                    if (i == 0) TR(r22);
                    if (i >= 1 && i < 4) {
                        uint32_t (&n)[20] = A[i - 1];
                        if (i > 1) mn &= n[0] & n[4] & n[8] & n[12] & n[16];
                        const uint8_t* q = src[i + 3] + (i > 1 ? mn & 256u : 0u);
                        wgmma_wait<1>();
                        bar_arrive(10, 32);
#pragma unroll
                        for (int j = 0; j < 5; j++) ldg128(q + (i + 3) * XB + j * 512, n[4 * j], n[4 * j + 1], n[4 * j + 2], n[4 * j + 3]);
                        bar_arrive(10, 32);
                    }
                }
                first = false;
                if (again) {
                    wgmma_wait<0>();
#pragma unroll
                    for (int j = 0; j < 5; j++)
                        ldg128(orow + hg * XB + j * 512, A[0][4 * j], A[0][4 * j + 1], A[0][4 * j + 2], A[0][4 * j + 3]);
                }
            } while (again);
            const uint32_t o0 = (hg & 1) * 32, o4 = (~hg & 1) * 128;
            if (routed) {
                const float2 sel = lds64f(sb + M_SEL);
                mbar_wait(sb + B_UPD, 0);
#pragma unroll
                for (uint32_t h = 0; h < 2; h++) {
                    const uint32_t row = warp * 16 + g + 8 * h, ga = sb + M_UPD + (row == U(sel.x) ? 0 : 160) + t * 4;
                    if (row == U(sel.x) || row == U(sel.y)) {
#pragma unroll
                        for (int c = 0; c < 5; c++) { gf[c][h] = lds32(ga + (c < 4 ? o0 + c * 32 : o4)); gf[c][h + 2] = lds32(ga + (c < 4 ? o0 + c * 32 : o4) + 16); }
                    }
                }
                __syncwarp();
            }
            wgmma_wait<0>();
#pragma unroll
            for (int i = 0; i < 40; i++) asm volatile("" : "+f"(acc2[i]) :: "memory");
            TR(r44);
#pragma unroll
            for (int c = 0; c < 5; c++) {
#pragma unroll
                for (int q = 0; q < 4; q++)
                    asm("fma.rn.bf16x2 %0, %1, %2, %0;" : "+r"(xr[c][q]) : "r"(pack_bf16(acc2[8 * c + 2 * q], acc2[8 * c + 2 * q + 1])), "r"(gf[c][q]));
                stsm_x4(ta + (c < 4 ? o0 + c * 32 : o4) + OFF_DN, xr[c]);
            }
            fence_proxy_async_smem();
            __syncwarp();
            if (lane == 0) {
                tma_st(&P.tm[T_OUT], sb + OFF_DN + warp * 2560, hg * 80, rb * 64 + 16 * w, p);
                asm volatile("cp.async.bulk.wait_group.read 0;" ::: "memory");
            }
        }
        TS(46);
        TRW(r12, 12); TRW(r32, 32); TRW(r34, 34); TRW(r22, 22); TRW(r44, 44);
    } else if (warp >= 12) {
        asm volatile("setmaxnreg.dec.sync.aligned.u32 24;");
        if (warp == 12) {
            uint32_t slot = t0 + PACE0;
            if (elect()) {
#pragma unroll 1
                for (uint32_t kb = 1; kb < 10; kb++) {
                    const uint32_t s = (kb + 2) & 3;
                    const uint32_t st = sb + s * ST, fb = sb + B_FULL + 8 * s;
                    const uint32_t kc = kb * 64 + (kb < 5 ? k0 : -k0);
                    if (kb >= 4) {
                        mbar_wait(fb + 32, kb >> 3);
                        if (kb < 9) mbar_wait(sb + B_AX - 32 + 8 * kb, 0);
                    }
                    {
                        slot += PACE1;
#pragma unroll 1
                        while ((int)(clock32() - slot) < 0) { }
                        mbar_expect_tx(fb, ST);
                        tma(st, &P.tm[T_X], fb, kc, rb * 64);
                    }
                    tma_mc(st + ST_BM + rank * 12288, &P.tm[T_W], fb, hg * 80 + (hg & 1) * 16, kc + rank * 32);
                    tma_mc(st + ST_BR + rank * 3072, &P.tm[T_WR], fb, hg * 80 + 64 - (hg & 1) * 64, kc + rank * 32);
                }
                uint32_t wb = sb + B_WO - 8;
#pragma unroll 1
                for (uint32_t i = 0; i < 8; i++) {
                    if ((0x93 >> i) & 1) {
                        wb += 8;
                        mbar_wait(wb - (B_WO - B_EMPTY), i < 2);
                        mbar_expect_tx(wb, (i + 1) & 6 ? 3 * 12800 : 12800);
                    }
                    if (i == 0) {
                        mbar_expect_tx(sb + B_DN, 20480);
                        tma(sb + OFF_DN, &P.tm[T_D], sb + B_DN, 0, 32 * fp, 5 * rank);
                    }
                    if (WOP) {
#pragma unroll 1
                        while ((int)(clock32() - slot) < 0) { }
                        slot = clock32() + WOP;
                    }
                    const uint32_t d = sb + wo_slot(i);
                    const uint32_t kr = 80 * (i ? i - (i <= hg) : hg);
                    tma_mc(d + rank * 5120, &P.tm[T_WO], wb, hg * 80 + (hg & 1) * 16 + rank * 32, kr);
                    tma_mc(d + 10240 + rank * 2560, &P.tm[T_WOR], wb, hg * 80 + (~hg & 1) * 64, kr + rank * 40);
                }
            }
        } else if (warp == 13) {
            if (elect()) {
#pragma unroll 1
                for (uint32_t i = 0; i < 3; i++) {
#pragma unroll 1
                    while (clock32() - t0 < PX0 + i * PX1) __nanosleep(20);
                    l2_prefetch(P.w + ((i + 2) * 245760 + b * 1920), 1920);
                    l2_prefetch(P.w + ((i + 7) * 245760 + b * 1920), 1920);
                }
#pragma unroll 1
                for (uint32_t i = 0; i < 14; i++) {
#pragma unroll 1
                    while (clock32() - t0 < GU0 + i * GU1) __nanosleep(20);
                    if (i < 10) l2_prefetch(P.wd + (i * 128 + b) * 1728, 1728);
                    else l2_prefetch(P.wo + ((i - 10) * 128 + b) * 1600, 1600);
                }
            }
        } else if (warp == 15) {
            const uint32_t lane = opaque_tid() & 31;
            const uint8_t* fl = P.scr + (G_FLAG + (rb * 8 + (lane & 7)) * XB + (lane >> 3) * 8);
            cluster_wait();
            mbar_wait(sb + B_PREP, 0);
            const uint32_t par = lds32(sb + M_SEL + 8);
            mbar_wait(sb + B_WO, 0); mbar_wait(sb + B_WO + 8, 0);
            mbar_wait(sb + B_EMPTY + 24, 0);
            __nanosleep(WSL);
            unsigned spins = 0;
            uint2 f;
#pragma unroll 1
            do f = ldg64(fl); while (any(f.x != par) && ++spins < SPIN);
            bar_arrive(5, 160);
            TS(24);
            mbar_wait(sb + B_WO + 16, 0); mbar_wait(sb + B_WO + 24, 0);
            bar_arrive(6, 160);
#pragma unroll 1
            while (any(f.y != par) && ++spins < SPIN) f.y = ldg32(fl + 4);
            bar_arrive(9, 288);
            TS(25);
        } else {
            uint32_t slot = t0 + GT0;
            cluster_wait();
            if (elect()) {
#pragma unroll 1
                for (uint32_t i = 0; i < 20; i++) {
                    slot += GT1;
#pragma unroll 1
                    while ((int)(clock32() - slot) < 0) __nanosleep(20);
                    tma(sb + OFF_GU + i * 2048, &P.tm[T_GU], sb + B_GU, 32 * fp, rank * 320 + i * 16);
                }
            }
        }
    } else {
        asm volatile("setmaxnreg.dec.sync.aligned.u32 72;");
        const uint32_t at = opaque_tid() - 256, lane = at & 31, g = lane >> 2, t = lane & 3, c7 = lane & 7, aw = warp - 8;
        uint8_t* const yz = P.scr + (G_Y + b * 512 + at * 4);
        stg32(yz, 0u);
        __nanosleep(AUXS);
        const uint32_t epoch = ldg32(P.scr + G_EPOCH) + 1 + ldg32(yz), tag = (epoch & 15u) | 16u;
        const uint32_t empty_cl = mapa(sb + B_EMPTY, lane & 1);
        unsigned spins = 0;
        TRD(r51); TRD(r30); TRD(r52); TRD(r53); TRD(r54); TRD(r55); TRD(r20); TRD(r22);
        {
            const uint2 wv = __ldg(reinterpret_cast<const uint2*>(P.w_r + k0 * 2 + min(at, 79u) * 8));
            if (at < 80) sts64(sb + M_UPD + at * 8, wv.x, wv.y);
        }
        uint8_t* const stw = P.scr + (b * XB + G_ST + (lane & 4) * 64 + (at >> 3) * 16);
        uint8_t* const csw = P.scr + (b * XB + G_CS + at);
        uint8_t* const tpw = P.scr + (G_TOP + (hg >> 2) * XB + rb * 64 + aw * 16);
        const bool tpub = lane == 0 && (hg & 3) == 3;
        cluster_wait();
        bar_sync(4, 128);
        mbar_wait(sb + B_FULL + 16, 0);
        if (t == 0) { stg128(stw, 0u, 0u, 0u, 0u); stg32(csw, 0u); }
        if (tpub) stg128(tpw, 0u, 0u, 0u, 0u);

        uint32_t k1, sv;
        {
            const uint32_t xoff = (32 * (hg & 3) + (at >> 3)) * 128 + ((c7 ^ ((at >> 3) & 7)) << 4);
            const uint32_t jt = (rb >> 2) * 8 + rank * 4 + aw;
            const uint32_t coff = jt < 24 ? ST_BM + (jt >> 3) * 4096 + lane * 128 + (((jt ^ lane) & 7) << 4)
                                          : ST_BR + ((jt >> 1) & 3) * 1024 + lane * 32 + (((jt ^ g) & 1) << 4);
            float q[8], c8[8];
#pragma unroll
            for (int e = 0; e < 8; e++) q[e] = c8[e] = 0.f;
#pragma unroll 1
            for (uint32_t kb = 2; kb < 7; kb++) {
                const uint32_t st = sb + (kb & 3) * ST;
                const uint4 wv = lds128(sb + M_UPD - 256 + kb * 128 + c7 * 16);
                mbar_wait(sb + B_FULL + 8 * (kb & 3), kb == 6);
                const uint4 v = lds128(st + xoff), vn = lds128(st + xoff + 2048);
                const uint4 cv = lds128(st + coff), cn = lds128(st + coff + (jt < 24 ? 12288 : 3072));
                if (lane < 2) mbar_arrive_cl(empty_cl - (B_EMPTY + 16 - B_AX) + 8 * kb);
                const uint32_t u[4] = {v.x, v.y, v.z, v.w}, un[4] = {vn.x, vn.y, vn.z, vn.w}, ww[4] = {wv.x, wv.y, wv.z, wv.w};
                const uint32_t cc[4] = {cv.x, cv.y, cv.z, cv.w}, cd[4] = {cn.x, cn.y, cn.z, cn.w};
#pragma unroll
                for (int e = 0; e < 4; e++) {
                    const float a0 = bflo(u[e]), a1 = bfhi(u[e]), b0 = bflo(un[e]), b1 = bfhi(un[e]), w0 = bflo(ww[e]), w1 = bfhi(ww[e]);
                    q[0] += a0 + a1; q[4] += b0 + b1; q[3] += w0 + w1;
                    q[1] = fmaf(a0, a0, fmaf(a1, a1, q[1])); q[5] = fmaf(b0, b0, fmaf(b1, b1, q[5]));
                    q[2] = fmaf(a0, w0, fmaf(a1, w1, q[2])); q[6] = fmaf(b0, w0, fmaf(b1, w1, q[6]));
                    c8[2 * e] += bflo(cc[e]) + bflo(cd[e]); c8[2 * e + 1] += bfhi(cc[e]) + bfhi(cd[e]);
                }
            }
            TR(r51);
            q[7] = q[3];
#pragma unroll
            for (int e = 0; e < 4; e++) {
                q[e] = ((lane & 4) ? q[e + 4] : q[e]) + shx((lane & 4) ? q[e] : q[e + 4], 4);
                q[e] += shx(q[e], 1); q[e] += shx(q[e], 2);
            }
            const float mh = q[0] * (1.0f / 320);
            if (t == 0) stg128(stw, U(mh), U(fmaf(-mh, q[0], q[1])), U(q[2]), (U(q[3]) & ~31u) | tag);
#define TSTEP(H) { const bool up = (lane & (4 * H)) != 0; _Pragma("unroll") for (int e = 0; e < H; e++) { \
            const float send = up ? c8[e] : c8[e + H]; const float keep = up ? c8[e + H] : c8[e]; \
            c8[e] = keep + shx(send, 4 * H); } }
            TSTEP(4) TSTEP(2) TSTEP(1)
#undef TSTEP
            c8[0] += shx(c8[0], 1); c8[0] += shx(c8[0], 2);
            if (t == 0) stg32(csw, (U(c8[0]) & ~31u) | tag);
            TR(r30);
            const uint8_t* csp = P.scr + (G_CS + (aw * 32 + (lane >> 4) * 8 + hg) * XB + (lane & 15) * 8);
            const uint8_t* stp = P.scr + (G_ST + (rb * 8 + aw) * XB + lane * 16);
            uint32_t ra[4], rc[4];
            uint2 ca, cc;
#pragma unroll 1
            while (clock32() - t0 < EX1T) __nanosleep(20);
#pragma unroll 1
            do {
                ldg128(stp, ra[0], ra[1], ra[2], ra[3]);
                ldg128(stp + 4 * XB, rc[0], rc[1], rc[2], rc[3]);
                ca = ldg64(csp); cc = ldg64(csp + 16 * XB);
            } while (any((ra[3] ^ tag | rc[3] ^ tag) & 31u) && ++spins < SPIN);
            TR(r20);
            const float dm = 0.5f * (F(ra[0]) - F(rc[0])), m = bf16r(F(rc[0]) + dm);
            const float sd = bf16r(sqrt_a(bf16r(bf16r(fmaxf(fmaf(dm, dm, (F(ra[1]) + F(rc[1])) * (1.0f / DM)), 0.f)) + 1e-5f)));
            const float rs = rcp(sd);
            uint32_t w1, w2;
            if ((hg & 3) == 3) {
                k1 = pack_bf16(0.f, fmaf(-m, F(ra[3]) + F(rc[3]), F(ra[2]) + F(rc[2])) * rs);
                k1 ^= ((int)k1 >> 31) | 0x80000000u;
                k1 = (k1 & 0xFFFF0000u) | ((2047 - (rb * 128 + 2 * (at & 63) + (at >> 6))) << 5) | tag;
                w1 = redux_max(k1); w2 = redux_max(k1 == w1 ? 0u : k1);
                sv = U(m) | (U(sd) >> 16);
                const uint32_t v1 = redux_max(k1 == w1 ? sv : 0u), v2 = redux_max(k1 == w2 ? sv : 0u);
                if (lane == 0) stg128(tpw, w1, v1, w2, v2);
            }
            sts64(sb + M_ST + at * 8, U(rs), U(m));
            sts32(sb + M_SEL + 8, (tag & 1) ? 1u : 0x10000u);
#pragma unroll 1
            while (any((ca.x ^ tag | ca.y ^ tag | cc.x ^ tag | cc.y ^ tag) & 31u) && ++spins < SPIN) { ca = ldg64(csp); cc = ldg64(csp + 16 * XB); }
            {
                const float c0 = at < 120 ? F(ca.x) + F(cc.x) : 0.f, c1 = at < 120 ? F(ca.y) + F(cc.y) : 0.f;
                const uint32_t hi = pack_bf16(c0, c1);
                sts32(sb + M_CS + (at >> 2) * 32 + t * 4, hi);
                sts32(sb + M_CS + (at >> 2) * 32 + t * 4 + 16, pack_bf16(c0 - bflo(hi), c1 - bfhi(hi)));
                fence_proxy_async_smem();
                __syncwarp();
                if (lane < 2) mbar_arrive(sb + B_PREP);
            }
            TR(r52);
            if (aw == 0) {
                uint32_t ka[4], kb[4];
#pragma unroll 1
                while (clock32() - t0 < EX1T + EX2D) __nanosleep(20);
#pragma unroll 1
                do {
                    const uint8_t* tp = P.scr + (G_TOP + lane * 16);
                    uint32_t kc[4], kd[4];
                    ldg128(tp, ka[0], ka[1], ka[2], ka[3]);
                    ldg128(tp + 512, kb[0], kb[1], kb[2], kb[3]);
                    ldg128(tp + XB, kc[0], kc[1], kc[2], kc[3]);
                    ldg128(tp + XB + 512, kd[0], kd[1], kd[2], kd[3]);
                    const bool ba = (ka[0] ^ tag) & 31u, bb = (kb[0] ^ tag) & 31u;
#pragma unroll
                    for (int e = 0; e < 4; e++) { ka[e] = ba ? kc[e] : ka[e]; kb[e] = bb ? kd[e] : kb[e]; }
                } while (any((ka[0] ^ tag | kb[0] ^ tag) & 31u) && ++spins < SPIN);
                TR(r22);
                if (kb[0] > ka[0]) {
#pragma unroll
                    for (int e = 0; e < 4; e++) { const uint32_t x = ka[e]; ka[e] = kb[e]; kb[e] = x; }
                }
                if (kb[0] > ka[2]) { ka[2] = kb[0]; ka[3] = kb[1]; }
                w1 = redux_max(ka[0]);
                const uint32_t t1 = redux_max(ka[0] == w1 ? ka[1] : 0u);
                if (ka[0] == w1) { ka[0] = ka[2]; ka[1] = ka[3]; }
                w2 = redux_max(ka[0]);
                const uint32_t t3 = redux_max(ka[0] == w2 ? ka[1] : 0u);
                sts128(sb + M_TOP, w1, t1, w2, t3);
            }
            bar_sync(4, 128);
            const float2 tv = lds64f(sb + M_TOP + (lane & 1) * 8);
            k1 = U(tv.x);
            sv = U(tv.y);
        }
        TR(r53);
        const uint32_t tok = ~(k1 >> 5) & 2047;
        const unsigned owns = __ballot_sync(0xffffffffu, (tok >> 7) == rb) & 3u;
        if (at < 2) sts32(sb + M_SEL + at * 4, (tok >> 7) == rb ? (tok & 1) * 64 + ((tok & 127) >> 1) : ~0u);
        if ((at | b) == 0) *reinterpret_cast<uint32_t*>(P.scr + G_EPOCH) = epoch;
        __syncwarp();
        if (at == 0) mbar_arrive(sb + B_SEL);
        if (fp < NFFN / 2) {
            uint4 xv = __ldg(reinterpret_cast<const uint4*>(P.x + (tok * 1280 + rank * 640 + min(at >> 1, 39u) * 16)));
            const uint32_t m2 = __byte_perm(sv, 0, 0x3232);
            asm("sub.rn.bf16x2 %0, %0, %4;\nsub.rn.bf16x2 %1, %1, %4;\nsub.rn.bf16x2 %2, %2, %4;\nsub.rn.bf16x2 %3, %3, %4;"
                : "+r"(xv.x), "+r"(xv.y), "+r"(xv.z), "+r"(xv.w) : "r"(m2));
            mbar_wait(sb + B_DN, 0);
            if (at < 80) sts128(sb + OFF_PART + at * 16, xv.x, xv.y, xv.z, xv.w);
            mbar_wait(sb + B_GU, 0);
            mbar_wait(sb + B_EMPTY + 24, 0);
            bar_sync(4, 128);
            float c[5][4];
            uint32_t wf[10][4];
#pragma unroll
            for (int i = 0; i < 5; i++) c[i][0] = c[i][1] = c[i][2] = c[i][3] = 0.f;
            const uint32_t mi = lane >> 3, kr = c7 + (mi >> 1) * 8;
            {
                const uint32_t wa = sb + OFF_GU + (aw >> 1) * 1024 + kr * 64 + ((((aw & 1) * 2 + (mi & 1)) ^ ((kr >> 1) & 3)) << 4);
#pragma unroll
                for (uint32_t i = 0; i < NPRE; i++) ldsm_x4_t(wf[i], wa + i * 2048);
                __nanosleep(FFNS);
                BLOCK_SPLIT(tag);
#pragma unroll
                for (uint32_t i = 0; i < 20; i += 2) {
                    uint32_t xb[4];
                    ldsm_x4(xb, sb + OFF_PART + i * 64 + mi * 32 + (lane & 1) * 16);
#pragma unroll
                    for (uint32_t j = i; j < i + 2; j++) {
                        const uint32_t (&a)[4] = wf[j % NPRE];
                        mma16816(c[j & 1], a[0], a[1], a[2], a[3], xb[2 * (j & 1)], xb[2 * (j & 1) + 1]);
                        if (j + NPRE < 20) ldsm_x4_t(wf[j % NPRE], wa + (j + NPRE) * 2048);
                    }
                }
#pragma unroll
                for (int e = 0; e < 4; e++) c[0][e] += c[1][e];
                const uint32_t rd = mapa(sb, rank ^ (t & 1));
                if (t < 2)
                    asm volatile("st.async.shared::cluster.mbarrier::complete_tx::bytes.v4.f32 [%0], {%1,%2,%3,%4}, [%5];"
                                 :: "r"(rd + (t ? OFF_PART + 1280 : M_UPD + 192) + aw * 128 + g * 16), "f"(c[0][0]), "f"(c[0][1]), "f"(c[0][2]), "f"(c[0][3]), "r"(rd + B_H) : "memory");
            }
            TR(r54);
            const float rs = rcp(bflo(sv));
            const uint32_t da = sb + OFF_DN + kr * 128 + (((2 * aw + (mi & 1)) ^ c7) << 4);
            uint8_t* yp = P.scr + (G_Y + (fp % 6) * 10240 + rank * 2560 + t * 512 + aw * 128 + g * 16);
#pragma unroll
            for (int i = 0; i < 5; i++) c[i][0] = c[i][1] = c[i][2] = c[i][3] = 0.f;
#pragma unroll
            for (uint32_t j = 0; j < NPD; j++) ldsm_x4_t(wf[j], da + (j % 5) * 4096 + (j / 5) * 2048);
            mbar_wait(sb + B_H, 0);
#pragma unroll
            for (uint32_t ks = 0; ks < 2; ks++) {
                const uint32_t og = sb + ks * 128 + lane * 4 + P.up_first, ou = og ^ 256;
                const float gs = bf16r((F(lds32(og + M_UPD + 192)) + F(lds32(og + OFF_PART + 1280))) * rs);
                const float h = bf16r(gs * sigm(gs)) * bf16r((F(lds32(ou + M_UPD + 192)) + F(lds32(ou + OFF_PART + 1280))) * rs);
                const uint32_t hp = pack_bf16(h, __shfl_down_sync(0xffffffffu, h, 4));
                const uint32_t h0 = __shfl_sync(0xffffffffu, hp, t * 8 + (g & 1)), h1 = __shfl_sync(0xffffffffu, hp, t * 8 + (g & 1) + 2);
#pragma unroll
                for (uint32_t j = 0; j < 5; j++) {
                    uint32_t (&a)[4] = wf[ks * 5 + j];
                    if (ks * 5 + j >= NPD) ldsm_x4_t(a, da + j * 4096 + ks * 2048);
                    mma16816(c[j], a[0], a[1], a[2], a[3], h0, h1);
                }
            }
#pragma unroll
            for (int e = 0; e < 4; e++) {
                const float lo = (t & 1) ? c[1][e] : c[0][e], hi = (t & 1) ? c[3][e] : c[2][e];
                c[0][e] = (t & 2) ? hi : lo;
            }
            asm volatile("" : "+f"(c[0][0]), "+f"(c[4][0]) :: "memory");
            BLOCK_SPLIT(tag);
            bar_sync(8, 384);
            { red4(yp, c[0][0], c[0][2]); red4(yp + 5120, c[0][1], c[0][3]); }
            if (t == 0) { red4(yp + 2048, c[4][0], c[4][2]); red4(yp + 2048 + 5120, c[4][1], c[4][3]); }
            TR(r55);
        }
        else {
            mbar_wait(sb + B_DN, 0); mbar_wait(sb + B_GU, 0);
            bar_arrive(8, 384);
        }
        TRW(r51, 51); TRW(r30, 30); TRW(r52, 52); TRW(r53, 53); TRW(r54, 54); TRW(r55, 55); TRW(r20, 20); TRW(r22, 22);
        if (owns) {
            const uint32_t u = min(at >> 1, 39u), col = (u >> 3) * 32 + (u & 7) * 2;
            const bool mine = (tok >> 7) == rb && at < 80;
            k1 ^= ((~(int)k1) >> 31) | 0x80000000u;
            const float sg = bf16r(sigm(bfhi(k1))), rs = rcp(bflo(sv));
            uint32_t x0, x1, y0, y1, n0, n1;
            asm volatile("ld.global.nc.u16 %0, [%2];\nld.global.nc.u16 %1, [%2 + 16];" : "=r"(x0), "=r"(x1) : "l"(P.x + (tok * 1280 + hg * 160 + col)));
            const float a0 = (bflo(x0) - bfhi(sv)) * rs, a1 = (bflo(x1) - bfhi(sv)) * rs;
            bar_sync(4, 128);
#pragma unroll 1
            do {
                __nanosleep(YSL);
                uint32_t v[6][4];
#pragma unroll
                for (int r = 0; r < 6; r++) if (mine) ldg128(P.scr + (G_Y + (at & 1) * 5120 + hg * 640 + u * 16) + r * 10240, v[r][0], v[r][1], v[r][2], v[r][3]);
                y0 = U(((F(v[0][0]) + F(v[1][0])) + (F(v[2][0]) + F(v[3][0]))) + (F(v[4][0]) + F(v[5][0])));
                y1 = U(((F(v[0][1]) + F(v[1][1])) + (F(v[2][1]) + F(v[3][1]))) + (F(v[4][1]) + F(v[5][1])));
                n0 = U(((F(v[0][2]) + F(v[1][2])) + (F(v[2][2]) + F(v[3][2]))) + (F(v[4][2]) + F(v[5][2])));
                n1 = U(((F(v[0][3]) + F(v[1][3])) + (F(v[2][3]) + F(v[3][3]))) + (F(v[4][3]) + F(v[5][3])));
            } while (any(mine && (F(n0) != NFFN / 2 || F(n1) != NFFN / 2)) && ++spins < SPIN);
            const float v0 = a0 + bf16r(bf16r(F(y0)) * sg), v1 = a1 + bf16r(bf16r(F(y1)) * sg);
            const uint32_t gp = pack_bf16(v0 * sigm(v0), v1 * sigm(v1));
            if (mine) asm volatile("st.shared.u16 [%0], %1;\nst.shared.u16 [%0 + 16], %2;" :: "r"(sb + M_UPD + (at & 1) * 160 + col), "r"(gp), "r"(gp >> 16) : "memory");
            __syncwarp();
            if (lane < 2) mbar_arrive(sb + B_UPD);
            TS(56);
        }
    }
}

typedef CUresult (*EncodeFn)(CUtensorMap*, CUtensorMapDataType, cuuint32_t, void*, const cuuint64_t*, const cuuint64_t*,
                             const cuuint32_t*, const cuuint32_t*, CUtensorMapInterleave, CUtensorMapSwizzle,
                             CUtensorMapL2promotion, CUtensorMapFloatOOBfill);

bool encode(EncodeFn fn, CUtensorMap* tm, const void* ptr, cuuint64_t d0, cuuint64_t d1, cuuint64_t d2, cuuint64_t s1, cuuint64_t s2,
            cuuint32_t b0, cuuint32_t b1, cuuint32_t b2, CUtensorMapSwizzle sw) {
    const cuuint64_t dims[3] = {d0, d1, d2}, strides[2] = {s1, s2};
    const cuuint32_t box[3] = {b0, b1, b2}, es[3] = {1, 1, 1};
    return fn(tm, CU_TENSOR_MAP_DATA_TYPE_BFLOAT16, 3, const_cast<void*>(ptr), dims, strides, box, es,
              CU_TENSOR_MAP_INTERLEAVE_NONE, sw, CU_TENSOR_MAP_L2_PROMOTION_L2_128B,
              CU_TENSOR_MAP_FLOAT_OOB_FILL_NONE) == CUDA_SUCCESS;
}

}

extern "C" void kernel_launch(void* const* d_in, const int* in_sizes, int n_in, void* d_out, int out_size) {
    static Params P;
    static bool by_sm = false;
    static const void* cached[9] = {};
    bool same = cached[8] == d_out;
    for (int i = 0; i < 8; i++) same = same && cached[i] == d_in[i];
    if (!same) {
        const void *x = d_in[0], *wqkv = d_in[1], *wo = d_in[2], *wg = d_in[5], *wu = d_in[6], *wd = d_in[7];
        void* fnp = nullptr;
        cudaDriverEntryPointQueryResult qr;
        cudaGetDriverEntryPoint("cuTensorMapEncodeTiled", &fnp, cudaEnableDefault, &qr);
        EncodeFn fn = (EncodeFn)fnp;
        const CUtensorMapSwizzle S0 = CU_TENSOR_MAP_SWIZZLE_NONE, S32 = CU_TENSOR_MAP_SWIZZLE_32B, S64 = CU_TENSOR_MAP_SWIZZLE_64B,
                                 S128 = CU_TENSOR_MAP_SWIZZLE_128B;
        const bool ok = fn != nullptr &&
            encode(fn, &P.tm[T_X], x, 640, 1024, 2, 2560, 1280, 64, 64, 2, S128) &&
            encode(fn, &P.tm[T_OUT], d_out, 640, 1024, 2, 2560, 1280, 80, 16, 1, S0) &&
            encode(fn, &P.tm[T_W], wqkv, 640, 640, 3, 3840, 1280, 64, 32, 3, S128) &&
            encode(fn, &P.tm[T_WR], wqkv, 640, 640, 3, 3840, 1280, 16, 32, 3, S32) &&
            encode(fn, &P.tm[T_GU], wg < wu ? wg : wu, 1728, 640, 2, 3456, wg < wu ? (const char*)wu - (const char*)wg : (const char*)wg - (const char*)wu,
                   32, 16, 2, S64) &&
            encode(fn, &P.tm[T_D], wd, 64, 1728, 10, 1280, 128, 64, 32, 5, S128) &&
            encode(fn, &P.tm[T_WO], wo, 640, 640, 1, 1280, 1280 * 640, 32, 80, 1, S64) &&
            encode(fn, &P.tm[T_WOR], wo, 640, 640, 1, 1280, 1280 * 640, 16, 40, 1, S64);
        if (!ok) return;
        P.up_first = wg < wu ? 0 : 256;
        P.wo = (const uint8_t*)wo; P.wd = (const uint8_t*)wd;
        P.x = (const uint8_t*)x; P.w = (const uint8_t*)wqkv; P.w_r = (const uint8_t*)d_in[4];
        if (cudaGetSymbolAddress((void**)&P.scr, g_scr) != cudaSuccess) return;
        cudaFuncSetAttribute(fused_kernel<true>, cudaFuncAttributeMaxDynamicSharedMemorySize, SMEM_BYTES);
        cudaFuncSetAttribute(fused_kernel<false>, cudaFuncAttributeMaxDynamicSharedMemorySize, SMEM_BYTES);
        int ncl = 0, sms = 0, dev = 0;
        {
            cudaLaunchConfig_t cfg = {};
            cfg.gridDim = dim3(128); cfg.blockDim = dim3(NTHREADS); cfg.dynamicSmemBytes = SMEM_BYTES;
            cudaLaunchAttribute at[1];
            at[0].id = cudaLaunchAttributeClusterDimension;
            at[0].val.clusterDim.x = 2; at[0].val.clusterDim.y = 1; at[0].val.clusterDim.z = 1;
            cfg.attrs = at; cfg.numAttrs = 1;
            if (cudaOccupancyMaxActiveClusters(&ncl, fused_kernel<true>, &cfg) != cudaSuccess || ncl < 64) return;
            cudaGetDevice(&dev);
            cudaDeviceGetAttribute(&sms, cudaDevAttrMultiProcessorCount, dev);
        }
        by_sm = sms == 132 && ncl == 66;
        for (int i = 0; i < 8; i++) cached[i] = d_in[i];
        cached[8] = d_out;
    }
    if (by_sm) fused_kernel<true><<<132, NTHREADS, SMEM_BYTES>>>(P);
    else fused_kernel<false><<<128, NTHREADS, SMEM_BYTES>>>(P);
}
```

```cpp
#include <cuda_runtime.h>
#include <cuda_bf16.h>
#include <cuda.h>
#include <stdint.h>

namespace {

constexpr int DM = 640;
constexpr int NTHREADS = 512;
constexpr int NFFN = 108;
#define LEAD 3
#define PACE0 420
#define PACE1 880
#define PX0 2400
#define PX1 250
#define GU0 6000
#define GU1 220
#define GT0 2800
#define GT1 410
#define WOP 150
#define AUXS 500
#define EX1T 8100
#define EX2D 2500
#define SERAT 2
#define FFNS 400
#define NPRE 8
#define NPD 8
#define YSL 100
#define WSL 300

constexpr int ST = 47104;
constexpr int ST_BM = 16384, ST_BR = 40960;
constexpr int OFF_DN = 0;
constexpr int OFF_PART = 20480;
constexpr int OFF_WO = 22528;
constexpr int WO_SLOT = 15360;
constexpr int OFF_HO = 3 * ST;
__host__ __device__ constexpr int wo_slot(int i) { return i < 7 ? OFF_WO + i * WO_SLOT : 3 * ST + ST_BM; }
constexpr int OFF_GU = 4 * ST;
constexpr int M_ST = OFF_GU + 40960;
constexpr int M_CS = M_ST + 1024;
constexpr int M_UPD = M_CS + 1024;
constexpr int M_TOP = M_UPD + 640;
constexpr int M_SEL = M_TOP + 64;
constexpr int B_AX = M_SEL + 16, B_PREP = B_AX + 40, B_UPD = B_PREP + 8,
              B_GU = B_AX + 64, B_DN = B_GU + 8, B_H = B_DN + 8, B_SEL = B_H + 8,
              B_FULL = B_GU + 32, B_EMPTY = B_FULL + 32, B_WO = B_EMPTY + 32;
constexpr int SMEM_BYTES = B_WO + 32;
static_assert(SMEM_BYTES <= 232448 && wo_slot(1) <= ST && wo_slot(4) <= 2 * ST && wo_slot(6) + WO_SLOT <= 3 * ST, "smem");

enum { T_X, T_W, T_WR, T_GU, T_D, T_WO, T_WOR, T_OUT, T_N };
struct Params {
    CUtensorMap tm[T_N];
    const uint8_t* x;
    const uint8_t* w_r;
    const uint8_t* w;
    const uint8_t* wo;
    const uint8_t* wd;
    uint8_t* scr;
    uint32_t up_first;
};

constexpr uint32_t XB = 27392;
constexpr uint32_t G_TOP = 25600;
constexpr uint32_t G_CS = G_TOP + 1024;
constexpr uint32_t G_ST = G_CS + 128;
constexpr uint32_t G_FLAG = G_ST + 512;
constexpr uint32_t G_Y = 128 * XB;
constexpr uint32_t G_EPOCH = G_Y + 128 * 512;
static_assert(G_FLAG + 128 == XB, "scratch");
__device__ __align__(1024) uint8_t g_scr[G_EPOCH + 1024];

#define TR(v)
#define TRD(v)
#define TRW(v, i)
#define TS(i)
#define TSG(i)
constexpr unsigned SPIN = 1u << 20;

__device__ __forceinline__ void mbar_init(uint32_t bar, int cnt) {
    asm volatile("mbarrier.init.shared::cta.b64 [%0], %1;" :: "r"(bar), "r"(cnt) : "memory");
}
__device__ __forceinline__ void mbar_expect_tx(uint32_t bar, int bytes) {
    asm volatile("mbarrier.arrive.expect_tx.shared::cta.b64 _, [%0], %1;" :: "r"(bar), "r"(bytes) : "memory");
}
__device__ __forceinline__ void mbar_arrive(uint32_t bar) {
    asm volatile("mbarrier.arrive.shared::cta.b64 _, [%0];" :: "r"(bar) : "memory");
}
__device__ __forceinline__ uint32_t mapa(uint32_t a, uint32_t cta) {
    uint32_t r;
    asm("mapa.shared::cluster.u32 %0, %1, %2;" : "=r"(r) : "r"(a), "r"(cta));
    return r;
}
__device__ __forceinline__ void mbar_arrive_cl(uint32_t cbar) {
    asm volatile("mbarrier.arrive.shared::cluster.b64 _, [%0];" :: "r"(cbar) : "memory");
}
__device__ __forceinline__ void mbar_wait(uint32_t bar, int parity) {
    asm volatile("{\n.reg .pred p;\nLAB_WAIT:\nmbarrier.try_wait.parity.shared::cta.b64 p, [%0], %1;\n@!p bra LAB_WAIT;\n}"
                 :: "r"(bar), "r"(parity) : "memory");
}
__device__ __forceinline__ bool mbar_try(uint32_t bar, int parity) {
    uint32_t r;
    asm volatile("{\n.reg .pred p;\nmbarrier.test_wait.parity.shared::cta.b64 p, [%1], %2;\nselp.u32 %0, 1, 0, p;\n}"
                 : "=r"(r) : "r"(bar), "r"(parity) : "memory");
    return r != 0;
}
__device__ __forceinline__ void tma(uint32_t dst, const CUtensorMap* tm, uint32_t bar, int c0, int c1, int c2 = 0) {
    asm volatile("cp.async.bulk.tensor.3d.shared::cluster.global.mbarrier::complete_tx::bytes [%0], [%1, {%3, %4, %5}], [%2];"
                 :: "r"(dst), "l"(tm), "r"(bar), "r"(c0), "r"(c1), "r"(c2) : "memory");
}
__device__ __forceinline__ void tma_mc(uint32_t dst, const CUtensorMap* tm, uint32_t bar, int c0, int c1) {
    asm volatile("cp.async.bulk.tensor.3d.shared::cluster.global.mbarrier::complete_tx::bytes.multicast::cluster [%0], [%1, {%3, %4, %5}], [%2], %6;"
                 :: "r"(dst), "l"(tm), "r"(bar), "r"(c0), "r"(c1), "r"(0), "h"((uint16_t)3) : "memory");
}
__device__ __forceinline__ void tma_st(const CUtensorMap* tm, uint32_t src, int c0, int c1, int c2) {
    asm volatile("cp.async.bulk.tensor.3d.global.shared::cta.bulk_group [%0, {%2, %3, %4}], [%1];\ncp.async.bulk.commit_group;"
                 :: "l"(tm), "r"(src), "r"(c0), "r"(c1), "r"(c2) : "memory");
}
__device__ __forceinline__ void l2_prefetch(const void* p, int bytes) {
    asm volatile("cp.async.bulk.prefetch.L2.global [%0], %1;" :: "l"(p), "r"(bytes) : "memory");
}
__device__ __forceinline__ void cluster_arrive() { asm volatile("barrier.cluster.arrive.relaxed.aligned;" ::: "memory"); }
__device__ __forceinline__ void cluster_wait() { asm volatile("barrier.cluster.wait.aligned;" ::: "memory"); }
__device__ __forceinline__ void bar_sync(int id, int n) { asm volatile("bar.sync %0, %1;" :: "r"(id), "r"(n) : "memory"); }
__device__ __forceinline__ void bar_arrive(int id, int n) { asm volatile("bar.arrive %0, %1;" :: "r"(id), "r"(n) : "memory"); }
__device__ __forceinline__ bool bar_or(int id, int n, bool v) {
    uint32_t r;
    asm volatile("{\n.reg .pred p, q;\nsetp.ne.u32 p, %3, 0;\nbar.red.or.pred q, %1, %2, p;\nselp.u32 %0, 1, 0, q;\n}"
                 : "=r"(r) : "r"(id), "r"(n), "r"((uint32_t)v) : "memory");
    return r != 0;
}
__device__ __forceinline__ void fence_proxy_async_smem() { asm volatile("fence.proxy.async.shared::cta;" ::: "memory"); }
__device__ __forceinline__ void stg128(void* p, uint32_t a, uint32_t b, uint32_t c, uint32_t d) {
    asm volatile("{\n.reg .b64 l, h;\n.reg .b128 q;\nmov.b64 l, {%1, %2};\nmov.b64 h, {%3, %4};\nmov.b128 q, {l, h};\n"
                 "st.relaxed.gpu.global.b128 [%0], q;\n}" :: "l"(p), "r"(a), "r"(b), "r"(c), "r"(d) : "memory");
}
__device__ __forceinline__ void ldg128(const void* p, uint32_t& a, uint32_t& b, uint32_t& c, uint32_t& d) {
    asm volatile("{\n.reg .b64 l, h;\n.reg .b128 q;\nld.relaxed.gpu.global.b128 q, [%4];\nmov.b128 {l, h}, q;\n"
                 "mov.b64 {%0, %1}, l;\nmov.b64 {%2, %3}, h;\n}" : "=r"(a), "=r"(b), "=r"(c), "=r"(d) : "l"(p) : "memory");
}
__device__ __forceinline__ void red4(void* p, float a, float b) {
    asm volatile("red.relaxed.gpu.global.add.v4.f32 [%0], {%1, %2, %3, %3};" :: "l"(p), "f"(a), "f"(b), "f"(1.0f) : "memory");
}
__device__ __forceinline__ void stg32(void* p, uint32_t a) {
    asm volatile("st.relaxed.gpu.global.u32 [%0], %1;" :: "l"(p), "r"(a) : "memory");
}
__device__ __forceinline__ uint2 ldg64(const void* p) {
    uint2 v;
    asm volatile("{\n.reg .b64 l;\nld.relaxed.gpu.global.b64 l, [%2];\nmov.b64 {%0, %1}, l;\n}" : "=r"(v.x), "=r"(v.y) : "l"(p) : "memory");
    return v;
}
__device__ __forceinline__ unsigned ldg32(const void* p) {
    unsigned v;
    asm volatile("ld.relaxed.gpu.global.u32 %0, [%1];" : "=r"(v) : "l"(p) : "memory");
    return v;
}
__device__ __forceinline__ void ldsm_x4(uint32_t (&r)[4], uint32_t a) {
    asm volatile("ldmatrix.sync.aligned.m8n8.x4.shared.b16 {%0,%1,%2,%3}, [%4];"
                 : "=r"(r[0]), "=r"(r[1]), "=r"(r[2]), "=r"(r[3]) : "r"(a));
}
__device__ __forceinline__ void ldsm_x4_t(uint32_t (&r)[4], uint32_t a) {
    asm volatile("ldmatrix.sync.aligned.m8n8.x4.trans.shared.b16 {%0,%1,%2,%3}, [%4];"
                 : "=r"(r[0]), "=r"(r[1]), "=r"(r[2]), "=r"(r[3]) : "r"(a));
}
__device__ __forceinline__ void stsm_x4(uint32_t a, const uint32_t (&r)[4]) {
    asm volatile("stmatrix.sync.aligned.m8n8.x4.shared.b16 [%0], {%1,%2,%3,%4};"
                 :: "r"(a), "r"(r[0]), "r"(r[1]), "r"(r[2]), "r"(r[3]));
}
__device__ __forceinline__ uint32_t movm(uint32_t a) {
    uint32_t d;
    asm("movmatrix.sync.aligned.m8n8.trans.b16 %0, %1;" : "=r"(d) : "r"(a));
    return d;
}
__device__ __forceinline__ void mma16816(float (&c)[4], uint32_t a0, uint32_t a1, uint32_t a2, uint32_t a3, uint32_t b0, uint32_t b1) {
    asm("mma.sync.aligned.m16n8k16.row.col.f32.bf16.bf16.f32 {%0,%1,%2,%3}, {%4,%5,%6,%7}, {%8,%9}, {%0,%1,%2,%3};"
        : "+f"(c[0]), "+f"(c[1]), "+f"(c[2]), "+f"(c[3]) : "r"(a0), "r"(a1), "r"(a2), "r"(a3), "r"(b0), "r"(b1));
}
__device__ __forceinline__ void mma1688(float (&c)[4], uint32_t a0, uint32_t a1, uint32_t b0) {
    asm("mma.sync.aligned.m16n8k8.row.col.f32.bf16.bf16.f32 {%0,%1,%2,%3}, {%4,%5}, {%6}, {%0,%1,%2,%3};"
        : "+f"(c[0]), "+f"(c[1]), "+f"(c[2]), "+f"(c[3]) : "r"(a0), "r"(a1), "r"(b0));
}
__device__ __forceinline__ void wgmma_fence() { asm volatile("wgmma.fence.sync.aligned;" ::: "memory"); }
__device__ __forceinline__ void wgmma_commit() { asm volatile("wgmma.commit_group.sync.aligned;" ::: "memory"); }
template <int N> __device__ __forceinline__ void wgmma_wait() { asm volatile("wgmma.wait_group.sync.aligned %0;" :: "n"(N) : "memory"); }
__device__ __forceinline__ uint64_t mk(uint32_t lo, uint32_t hi) { return (uint64_t)lo | ((uint64_t)hi << 32); }
constexpr uint32_t HI128 = (1024 >> 4) | (1u << 30), HI64 = (512 >> 4) | (2u << 30), HI32 = (256 >> 4) | (3u << 30);
__device__ __forceinline__ uint32_t pack_bf16(float lo, float hi) {
    uint32_t r;
    asm("cvt.rn.bf16x2.f32 %0, %1, %2;" : "=r"(r) : "f"(hi), "f"(lo));
    return r;
}
__device__ __forceinline__ float bflo(uint32_t u) { return __uint_as_float(u << 16); }
__device__ __forceinline__ float bfhi(uint32_t u) { return __uint_as_float(u & 0xFFFF0000u); }
__device__ __forceinline__ float bf16r(float v) { return __uint_as_float(pack_bf16(0.f, v)); }
__device__ __forceinline__ float ex2(float v) { float r; asm("ex2.approx.ftz.f32 %0, %1;" : "=f"(r) : "f"(v)); return r; }
__device__ __forceinline__ float rcp(float v) { float r; asm("rcp.approx.ftz.f32 %0, %1;" : "=f"(r) : "f"(v)); return r; }
__device__ __forceinline__ float sqrt_a(float v) { float r; asm("sqrt.approx.ftz.f32 %0, %1;" : "=f"(r) : "f"(v)); return r; }
__device__ __forceinline__ float tanh_a(float v) { float r; asm("tanh.approx.f32 %0, %1;" : "=f"(r) : "f"(v)); return r; }
constexpr float LOG2E = 1.4426950408889634f;
__device__ __forceinline__ float sigm(float v) { return rcp(1.0f + ex2(-LOG2E * v)); }
__device__ __forceinline__ uint4 lds128(uint32_t a) {
    uint4 v;
    asm volatile("ld.shared.v4.u32 {%0,%1,%2,%3}, [%4];" : "=r"(v.x), "=r"(v.y), "=r"(v.z), "=r"(v.w) : "r"(a));
    return v;
}
__device__ __forceinline__ float2 lds64f(uint32_t a) {
    float2 v;
    asm volatile("ld.shared.v2.f32 {%0,%1}, [%2];" : "=f"(v.x), "=f"(v.y) : "r"(a));
    return v;
}
__device__ __forceinline__ uint32_t lds32(uint32_t a) {
    uint32_t v;
    asm volatile("ld.shared.u32 %0, [%1];" : "=r"(v) : "r"(a));
    return v;
}
__device__ __forceinline__ void sts128(uint32_t a, uint32_t x, uint32_t y, uint32_t z, uint32_t w) {
    asm volatile("st.shared.v4.u32 [%0], {%1,%2,%3,%4};" :: "r"(a), "r"(x), "r"(y), "r"(z), "r"(w) : "memory");
}
__device__ __forceinline__ void sts64(uint32_t a, uint32_t x, uint32_t y) {
    asm volatile("st.shared.v2.u32 [%0], {%1,%2};" :: "r"(a), "r"(x), "r"(y) : "memory");
}
__device__ __forceinline__ void sts32(uint32_t a, uint32_t x) { asm volatile("st.shared.u32 [%0], %1;" :: "r"(a), "r"(x) : "memory"); }
__device__ __forceinline__ unsigned redux_max(unsigned v) {
    unsigned r;
    asm volatile("redux.sync.max.u32 %0, %1, 0xffffffff;" : "=r"(r) : "r"(v));
    return r;
}
__device__ __forceinline__ float shx(float v, int o) { return __shfl_xor_sync(0xffffffffu, v, o); }
__device__ __forceinline__ uint32_t U(float v) { return __float_as_uint(v); }
__device__ __forceinline__ float F(uint32_t v) { return __uint_as_float(v); }

__device__ __forceinline__ void wgmma_n192_lo(float (&d)[120], uint64_t da, uint64_t db, int scale_d) {
    asm volatile("{\n.reg .pred p;\nsetp.ne.b32 p, %98, 0;\n"
        "wgmma.mma_async.sync.aligned.m64n192k16.f32.bf16.bf16 "
        "{%0, %1, %2, %3, %4, %5, %6, %7, %8, %9, %10, %11, %12, %13, %14, %15, "
        "%16, %17, %18, %19, %20, %21, %22, %23, %24, %25, %26, %27, %28, %29, %30, %31, "
        "%32, %33, %34, %35, %36, %37, %38, %39, %40, %41, %42, %43, %44, %45, %46, %47, "
        "%48, %49, %50, %51, %52, %53, %54, %55, %56, %57, %58, %59, %60, %61, %62, %63, "
        "%64, %65, %66, %67, %68, %69, %70, %71, %72, %73, %74, %75, %76, %77, %78, %79, "
        "%80, %81, %82, %83, %84, %85, %86, %87, %88, %89, %90, %91, %92, %93, %94, %95}, "
        "%96, %97, p, 1, 1, 0, 1;\n}\n"
        : "+f"(d[0]), "+f"(d[1]), "+f"(d[2]), "+f"(d[3]), "+f"(d[4]), "+f"(d[5]), "+f"(d[6]), "+f"(d[7]),
          "+f"(d[8]), "+f"(d[9]), "+f"(d[10]), "+f"(d[11]), "+f"(d[12]), "+f"(d[13]), "+f"(d[14]), "+f"(d[15]),
          "+f"(d[16]), "+f"(d[17]), "+f"(d[18]), "+f"(d[19]), "+f"(d[20]), "+f"(d[21]), "+f"(d[22]), "+f"(d[23]),
          "+f"(d[24]), "+f"(d[25]), "+f"(d[26]), "+f"(d[27]), "+f"(d[28]), "+f"(d[29]), "+f"(d[30]), "+f"(d[31]),
          "+f"(d[32]), "+f"(d[33]), "+f"(d[34]), "+f"(d[35]), "+f"(d[36]), "+f"(d[37]), "+f"(d[38]), "+f"(d[39]),
          "+f"(d[40]), "+f"(d[41]), "+f"(d[42]), "+f"(d[43]), "+f"(d[44]), "+f"(d[45]), "+f"(d[46]), "+f"(d[47]),
          "+f"(d[48]), "+f"(d[49]), "+f"(d[50]), "+f"(d[51]), "+f"(d[52]), "+f"(d[53]), "+f"(d[54]), "+f"(d[55]),
          "+f"(d[56]), "+f"(d[57]), "+f"(d[58]), "+f"(d[59]), "+f"(d[60]), "+f"(d[61]), "+f"(d[62]), "+f"(d[63]),
          "+f"(d[64]), "+f"(d[65]), "+f"(d[66]), "+f"(d[67]), "+f"(d[68]), "+f"(d[69]), "+f"(d[70]), "+f"(d[71]),
          "+f"(d[72]), "+f"(d[73]), "+f"(d[74]), "+f"(d[75]), "+f"(d[76]), "+f"(d[77]), "+f"(d[78]), "+f"(d[79]),
          "+f"(d[80]), "+f"(d[81]), "+f"(d[82]), "+f"(d[83]), "+f"(d[84]), "+f"(d[85]), "+f"(d[86]), "+f"(d[87]),
          "+f"(d[88]), "+f"(d[89]), "+f"(d[90]), "+f"(d[91]), "+f"(d[92]), "+f"(d[93]), "+f"(d[94]), "+f"(d[95])
        : "l"(da), "l"(db), "r"(scale_d));
}
__device__ __forceinline__ void wgmma_n48_hi(float (&d)[120], uint64_t da, uint64_t db, int scale_d) {
    asm volatile("{\n.reg .pred p;\nsetp.ne.b32 p, %26, 0;\n"
        "wgmma.mma_async.sync.aligned.m64n48k16.f32.bf16.bf16 "
        "{%0, %1, %2, %3, %4, %5, %6, %7, %8, %9, %10, %11, %12, %13, %14, %15, "
        "%16, %17, %18, %19, %20, %21, %22, %23}, "
        "%24, %25, p, 1, 1, 0, 1;\n}\n"
        : "+f"(d[96]), "+f"(d[97]), "+f"(d[98]), "+f"(d[99]), "+f"(d[100]), "+f"(d[101]), "+f"(d[102]), "+f"(d[103]),
          "+f"(d[104]), "+f"(d[105]), "+f"(d[106]), "+f"(d[107]), "+f"(d[108]), "+f"(d[109]), "+f"(d[110]), "+f"(d[111]),
          "+f"(d[112]), "+f"(d[113]), "+f"(d[114]), "+f"(d[115]), "+f"(d[116]), "+f"(d[117]), "+f"(d[118]), "+f"(d[119])
        : "l"(da), "l"(db), "r"(scale_d));
}
__device__ __forceinline__ void wgmma_rs_n80(float (&d)[40], uint32_t a0, uint32_t a1, uint32_t a2, uint32_t a3, uint64_t db, int scale_d) {
    asm volatile("{\n.reg .pred p;\nsetp.ne.b32 p, %45, 0;\n"
        "wgmma.mma_async.sync.aligned.m64n80k16.f32.bf16.bf16 "
        "{%0, %1, %2, %3, %4, %5, %6, %7, %8, %9, %10, %11, %12, %13, %14, %15, "
        "%16, %17, %18, %19, %20, %21, %22, %23, %24, %25, %26, %27, %28, %29, %30, %31, "
        "%32, %33, %34, %35, %36, %37, %38, %39}, "
        "{%40, %41, %42, %43}, %44, p, 1, 1, 1;\n}\n"
        : "+f"(d[0]), "+f"(d[1]), "+f"(d[2]), "+f"(d[3]), "+f"(d[4]), "+f"(d[5]), "+f"(d[6]), "+f"(d[7]),
          "+f"(d[8]), "+f"(d[9]), "+f"(d[10]), "+f"(d[11]), "+f"(d[12]), "+f"(d[13]), "+f"(d[14]), "+f"(d[15]),
          "+f"(d[16]), "+f"(d[17]), "+f"(d[18]), "+f"(d[19]), "+f"(d[20]), "+f"(d[21]), "+f"(d[22]), "+f"(d[23]),
          "+f"(d[24]), "+f"(d[25]), "+f"(d[26]), "+f"(d[27]), "+f"(d[28]), "+f"(d[29]), "+f"(d[30]), "+f"(d[31]),
          "+f"(d[32]), "+f"(d[33]), "+f"(d[34]), "+f"(d[35]), "+f"(d[36]), "+f"(d[37]), "+f"(d[38]), "+f"(d[39])
        : "r"(a0), "r"(a1), "r"(a2), "r"(a3), "l"(db), "r"(scale_d));
}
__device__ __forceinline__ void wgmma_rs_n192_lo(float (&d)[120], uint32_t a0, uint32_t a1, uint32_t a2, uint32_t a3, uint64_t db, int scale_d) {
    asm volatile("{\n.reg .pred p;\nsetp.ne.b32 p, %101, 0;\n"
        "wgmma.mma_async.sync.aligned.m64n192k16.f32.bf16.bf16 "
        "{%0, %1, %2, %3, %4, %5, %6, %7, %8, %9, %10, %11, %12, %13, %14, %15, "
        "%16, %17, %18, %19, %20, %21, %22, %23, %24, %25, %26, %27, %28, %29, %30, %31, "
        "%32, %33, %34, %35, %36, %37, %38, %39, %40, %41, %42, %43, %44, %45, %46, %47, "
        "%48, %49, %50, %51, %52, %53, %54, %55, %56, %57, %58, %59, %60, %61, %62, %63, "
        "%64, %65, %66, %67, %68, %69, %70, %71, %72, %73, %74, %75, %76, %77, %78, %79, "
        "%80, %81, %82, %83, %84, %85, %86, %87, %88, %89, %90, %91, %92, %93, %94, %95}, "
        "{%96, %97, %98, %99}, %100, p, 1, 1, 1;\n}\n"
        : "+f"(d[0]), "+f"(d[1]), "+f"(d[2]), "+f"(d[3]), "+f"(d[4]), "+f"(d[5]), "+f"(d[6]), "+f"(d[7]),
          "+f"(d[8]), "+f"(d[9]), "+f"(d[10]), "+f"(d[11]), "+f"(d[12]), "+f"(d[13]), "+f"(d[14]), "+f"(d[15]),
          "+f"(d[16]), "+f"(d[17]), "+f"(d[18]), "+f"(d[19]), "+f"(d[20]), "+f"(d[21]), "+f"(d[22]), "+f"(d[23]),
          "+f"(d[24]), "+f"(d[25]), "+f"(d[26]), "+f"(d[27]), "+f"(d[28]), "+f"(d[29]), "+f"(d[30]), "+f"(d[31]),
          "+f"(d[32]), "+f"(d[33]), "+f"(d[34]), "+f"(d[35]), "+f"(d[36]), "+f"(d[37]), "+f"(d[38]), "+f"(d[39]),
          "+f"(d[40]), "+f"(d[41]), "+f"(d[42]), "+f"(d[43]), "+f"(d[44]), "+f"(d[45]), "+f"(d[46]), "+f"(d[47]),
          "+f"(d[48]), "+f"(d[49]), "+f"(d[50]), "+f"(d[51]), "+f"(d[52]), "+f"(d[53]), "+f"(d[54]), "+f"(d[55]),
          "+f"(d[56]), "+f"(d[57]), "+f"(d[58]), "+f"(d[59]), "+f"(d[60]), "+f"(d[61]), "+f"(d[62]), "+f"(d[63]),
          "+f"(d[64]), "+f"(d[65]), "+f"(d[66]), "+f"(d[67]), "+f"(d[68]), "+f"(d[69]), "+f"(d[70]), "+f"(d[71]),
          "+f"(d[72]), "+f"(d[73]), "+f"(d[74]), "+f"(d[75]), "+f"(d[76]), "+f"(d[77]), "+f"(d[78]), "+f"(d[79]),
          "+f"(d[80]), "+f"(d[81]), "+f"(d[82]), "+f"(d[83]), "+f"(d[84]), "+f"(d[85]), "+f"(d[86]), "+f"(d[87]),
          "+f"(d[88]), "+f"(d[89]), "+f"(d[90]), "+f"(d[91]), "+f"(d[92]), "+f"(d[93]), "+f"(d[94]), "+f"(d[95])
        : "r"(a0), "r"(a1), "r"(a2), "r"(a3), "l"(db), "r"(scale_d));
}
__device__ __forceinline__ void wgmma_rs_n48_hi(float (&d)[120], uint32_t a0, uint32_t a1, uint32_t a2, uint32_t a3, uint64_t db, int scale_d) {
    asm volatile("{\n.reg .pred p;\nsetp.ne.b32 p, %29, 0;\n"
        "wgmma.mma_async.sync.aligned.m64n48k16.f32.bf16.bf16 "
        "{%0, %1, %2, %3, %4, %5, %6, %7, %8, %9, %10, %11, %12, %13, %14, %15, "
        "%16, %17, %18, %19, %20, %21, %22, %23}, "
        "{%24, %25, %26, %27}, %28, p, 1, 1, 1;\n}\n"
        : "+f"(d[96]), "+f"(d[97]), "+f"(d[98]), "+f"(d[99]), "+f"(d[100]), "+f"(d[101]), "+f"(d[102]), "+f"(d[103]),
          "+f"(d[104]), "+f"(d[105]), "+f"(d[106]), "+f"(d[107]), "+f"(d[108]), "+f"(d[109]), "+f"(d[110]), "+f"(d[111]),
          "+f"(d[112]), "+f"(d[113]), "+f"(d[114]), "+f"(d[115]), "+f"(d[116]), "+f"(d[117]), "+f"(d[118]), "+f"(d[119])
        : "r"(a0), "r"(a1), "r"(a2), "r"(a3), "l"(db), "r"(scale_d));
}
__device__ __forceinline__ constexpr int jt_of(int sec, int c, bool odd) {
    return odd ? (c >= 2 ? sec * 8 + c - 2 : 24 + sec * 2 + c) : (c < 8 ? sec * 8 + c : 24 + sec * 2 + (c - 8));
}
#define BOTH(...) if (hg & 1) { constexpr bool odd = true; __VA_ARGS__ } else { constexpr bool odd = false; __VA_ARGS__ }

__device__ __forceinline__ bool elect() {
    uint32_t r;
    asm volatile("{\n.reg .pred p;\nelect.sync _|p, 0xffffffff;\nselp.u32 %0, 1, 0, p;\n}" : "=r"(r));
    return r != 0;
}
__device__ __forceinline__ uint32_t clock32() { uint32_t r; asm volatile("mov.u32 %0, %%clock;" : "=r"(r)); return r; }
#define BLOCK_SPLIT(v) asm volatile("{\n.reg .pred p;\nLAB_SPLIT:\nsetp.eq.u32 p, %0, 0;\n@p nanosleep.u32 1;\n@p bra LAB_SPLIT;\n}" :: "r"(v) : "memory")
__device__ __forceinline__ bool any(bool v) { return __any_sync(0xffffffffu, v); }
__device__ __forceinline__ uint32_t opaque_tid() { uint32_t r; asm volatile("mov.u32 %0, %%tid.x;" : "=r"(r)); return r; }

template <bool BY_SM>
__global__ void __cluster_dims__(2, 1, 1) __launch_bounds__(NTHREADS, 1)
fused_kernel(const __grid_constant__ Params P) {
    extern __shared__ __align__(1024) uint8_t smem[];
    const uint32_t sb = (uint32_t)__cvta_generic_to_shared(smem);
    const uint32_t warp = __shfl_sync(0xffffffffu, threadIdx.x >> 5, 0);
    const uint32_t rank = blockIdx.x & 1;
    constexpr uint32_t sbd = 1024 >> 4;
    const uint32_t t0 = clock32();
    if (warp >= 10 && elect()) {
        const uint32_t bb = sb + B_AX - 320 + warp * 32;
        const int cnt = warp < 12 ? 8 : (warp == 14 ? 16 : 1);
        mbar_init(bb, cnt); mbar_init(bb + 8, cnt); mbar_init(bb + 16, cnt); mbar_init(bb + 24, cnt);
        if (warp == 12) { mbar_expect_tx(sb + B_H, 1024); mbar_expect_tx(sb + B_GU, 40960); }
        if (warp == 13) mbar_expect_tx(sb + B_FULL + 16, ST);
        asm volatile("fence.mbarrier_init.release.cluster;" ::: "memory");
    }
    __syncwarp();
    cluster_arrive();
    if (warp < 3 && elect()) asm volatile("prefetch.tensormap [%0];" :: "l"(&P.tm[warp]) : "memory");
    if (warp - 3 < 2 && blockIdx.x < 128 && elect()) l2_prefetch(P.w + ((warp - 3) * 5 * 245760 + blockIdx.x * 1920), 1920);
    if ((sb & 0xFFFFFF) != 1024) __trap();
    uint32_t gpc = blockIdx.x >> 4, pos = (blockIdx.x >> 1) & 7;
    if (BY_SM) {
        uint32_t tpc;
        asm("mov.u32 %0, %%smid;" : "=r"(tpc));
        tpc >>= 1;
        if (tpc - 60 < 2) {
            __nanosleep(2000);
            return;
        }
        const uint32_t q = ((tpc - 32) * 37) >> 8;
        gpc = tpc < 32 ? tpc & 7 : (tpc < 60 ? tpc - 31 - 7 * q : 0);
        pos = tpc < 32 ? tpc >> 3 : (tpc < 60 ? 4 + q : tpc - 58);
    }
    const uint32_t hg = (0x62740351u >> (4 * pos)) & 7, rb = gpc * 2 + rank, fp = 8 * pos + gpc - 10;
    const uint32_t b = rb * 8 + hg;
    const uint32_t k0 = (((hg >> 2) ^ (rb >> 1)) & 1) * 320;

    if (warp == 13 && elect()) tma(sb + 2 * ST, &P.tm[T_X], sb + B_FULL + 16, k0, rb * 64);
    if (warp == 12) {
        cluster_wait();
        if (elect()) {
            tma_mc(sb + 2 * ST + ST_BM + rank * 12288, &P.tm[T_W], sb + B_FULL + 16, hg * 80 + (hg & 1) * 16, k0 + rank * 32);
            tma_mc(sb + 2 * ST + ST_BR + rank * 3072, &P.tm[T_WR], sb + B_FULL + 16, hg * 80 + 64 - (hg & 1) * 64, k0 + rank * 32);
        }
        __syncwarp();
    }

    if (warp < 8) {
        asm volatile("setmaxnreg.inc.sync.aligned.u32 208;");
        const uint32_t lane = opaque_tid() & 31, g = lane >> 2, t = lane & 3;
        const uint32_t p = warp >> 2, w = warp & 3;
        const uint32_t empty_cl = mapa(sb + B_EMPTY, lane & 1);
        uint8_t* const orow = P.scr + (rb * (8 * XB) + warp * 2560 + lane * 16);
        const uint32_t ta = sb + warp * 2560 + (lane & 15) * 160 + (lane >> 4) * 16;
        uint32_t A[5][20];
        uint32_t xr[5][4], gf[5][4];
        TRD(r12); TRD(r32); TRD(r34); TRD(r22); TRD(r44);
        uint32_t par;
        uint8_t* const halo = orow + (hg * XB + (8 + p - warp) * 2560);
        uint8_t* const flag = P.scr + (G_FLAG + b * XB + w * 8 + p * 4);
        cluster_wait();
        {
            float acc[120];
            bool ok, prep, rel = false;
            float2 s0, s1;
            uint32_t xa[5], cap[2] = {0u, 0u};
#pragma unroll
            for (uint32_t j = 0; j < 5; j++) {
                const uint32_t cg = 5 * hg + (j < 4 ? j + (hg & 1) : (~hg & 1) * 4);
                xa[j] = (sb + (warp * 16 + (lane & 15)) * 128 + (((lane >> 4) ^ (lane & 7)) << 4)) ^ ((cg & 3) << 5);
                const uint32_t i = cg >> 2, late = (i >= 5) ^ (k0 != 0), bit = 1u << (5 * (i >= 5 ? i - 5 : i) + j);
                cap[0] |= late ? 0u : bit; cap[1] |= late ? bit : 0u;
            }
            uint32_t sta = sb + M_ST + (warp * 16 + g) * 8;
            asm volatile("" : "+r"(sta), "+r"(cap[0]), "+r"(cap[1]), "+r"(xa[0]), "+r"(xa[1]), "+r"(xa[2]), "+r"(xa[3]), "+r"(xa[4]));
            mbar_wait(sb + B_FULL + 16, 0);
#pragma unroll
            for (uint32_t kb = 2; kb < 12; kb++) {
                const uint32_t s = kb & 3;
                const bool hold = kb == 12 - LEAD && p;
                if (hold) {
                    wgmma_wait<0>();
                    if (lane < 2) mbar_arrive_cl(empty_cl + 8 * ((11 - LEAD) & 3));
                    bar_sync(1, 256);
                }
                if (kb == 13 - LEAD && p) bar_sync(7, 256);
                wgmma_fence();
                const uint32_t st = sbd + s * (ST >> 4);
#pragma unroll
                for (int ks = 0; ks < 4; ks++) {
                    const uint64_t da = mk(st + p * 512 + ks * 2 + 0x10000, HI128);
                    wgmma_n48_hi(acc, da, mk(st + (ST_BR >> 4) + (ks >> 1) * 192 + (ks & 1) * 32 + (64 << 16), HI32), ks || kb > 2);
                    wgmma_n192_lo(acc, da, mk(st + (ST_BM >> 4) + (ks >> 1) * 768 + (ks & 1) * 128 + (256 << 16), HI128), ks || kb > 2);
                    if (ks == 0) {
                        wgmma_commit();
                        wgmma_wait<1>();
                        if (!hold && kb > 2 && lane < 2) mbar_arrive_cl(empty_cl + 8 * ((kb - 1) & 3));
                    }
                    if (ks == 1) {
#pragma unroll
                        for (uint32_t j = 0; j < 5; j++)
                            if ((cap[kb >= 7] >> (5 * ((kb - 2) % 5) + j)) & 1) ldsm_x4(xr[j], xa[j] + s * ST);
                        if (w == 3 && kb < 7) stg128(halo + (kb - 2) * 512, 0u, 0u, 0u, 0u);
                        if (lane == 0 && kb == 2) stg32(flag, 0u);
                        if (kb < 11) ok = mbar_try(sb + B_FULL + 8 * ((kb + 1) & 3), ((kb - 1) >> 2) & 1);
                        if (kb == 10) prep = mbar_try(sb + B_PREP, 0);
                        if (kb == 11 && prep) {
                            s0 = lds64f(sta); s1 = lds64f(sta + 64);
                            par = lds32(sb + M_SEL + 8);
                        }
                    }
                }
                wgmma_commit();
                if (kb < 11 && !ok) {
                    if (kb >= 12 - LEAD && !p && !rel && !mbar_try(sb + B_FULL + 8 * ((kb + 1) & 3), ((kb - 1) >> 2) & 1)) { rel = true; bar_arrive(1, 256); }
                    mbar_wait(sb + B_FULL + 8 * ((kb + 1) & 3), ((kb - 1) >> 2) & 1);
                }
            }
            if (!prep) {
                mbar_wait(sb + B_PREP, 0);
                s0 = lds64f(sta); s1 = lds64f(sta + 64);
                par = lds32(sb + M_SEL + 8);
            }
            {
                const uint32_t a0 = t ? 0u : __byte_perm(U(-s0.y), 0, 0x3232), a1 = t ? 0u : __byte_perm(U(-s1.y), 0, 0x3232);
                wgmma_fence();
                wgmma_rs_n48_hi(acc, a0, a1, 0u, 0u, mk(sbd + (M_CS >> 4) + 48, 2), 1);
                wgmma_rs_n192_lo(acc, a0, a1, 0u, 0u, mk(sbd + (M_CS >> 4), 2), 1);
                wgmma_commit();
            }
            if (!p) { if (!rel) bar_arrive(1, 256); bar_arrive(7, 256); }
            wgmma_wait<1>();
            if (lane < 2) mbar_arrive_cl(empty_cl + 24);
            wgmma_wait<0>();
#pragma unroll
            for (int i = 0; i < 120; i++) asm volatile("" : "+f"(acc[i]) :: "memory");
            TR(r12);
            uint32_t Q[10], Ql[10], KX[10], VX[10], Y[20];
#define KI(c) ((c) == 2 ? 8 : (c) == 7 ? 9 : (c) - ((c) > 2) - ((c) > 7))
#define KY(c) Y[KI(c)]
#define VY(c) Y[10 + (c)]
            uint32_t Z[20];
            const bool start = w == 0 && rb == 0, remote = w == 0 && rb != 0;
            const uint32_t slot = sb + OFF_HO + p * 8192 + w * 2560 - 2560 + lane * 16;
            {
                BOTH(_Pragma("unroll") for (int c = 0; c < 10; c++) {
                    const int jk = jt_of(1, c, odd), jv = jt_of(2, c, odd);
                    VY(c) = movm(pack_bf16(acc[4 * jv + 2] * s1.x, acc[4 * jv + 3] * s1.x));
                    KY(c) = pack_bf16(acc[4 * jk + 2] * s1.x, acc[4 * jk + 3] * s1.x);
                    asm volatile("" : "+r"(KY(c)), "+r"(VY(c)));
                })
                if (w == 3) {
#pragma unroll
                    for (int j = 0; j < 5; j++) {
                        Y[4 * j] = (Y[4 * j] & ~0x10001u) | par;
                        stg128(halo + j * 512, Y[4 * j], Y[4 * j + 1], Y[4 * j + 2], Y[4 * j + 3]);
                    }
                } else {
#pragma unroll
                    for (int j = 0; j < 5; j++) sts128(slot + 2560 + j * 512, Y[4 * j], Y[4 * j + 1], Y[4 * j + 2], Y[4 * j + 3]);
                }
                BOTH(_Pragma("unroll") for (int c = 0; c < 10; c++) {
                    const int jk = jt_of(1, c, odd), jv = jt_of(2, c, odd);
                    KX[c] = pack_bf16(acc[4 * jk] * s0.x, acc[4 * jk + 1] * s0.x);
                    VX[c] = movm(pack_bf16(acc[4 * jv] * s0.x, acc[4 * jv + 1] * s0.x));
                    asm volatile("" : "+r"(KX[c]), "+r"(VX[c]));
                })
                bar_sync(2 + p, 128);
                if (remote) {
#pragma unroll
                    for (int j = 0; j < 5; j++) ldg128(halo - 8 * XB + j * 512, Z[4 * j], Z[4 * j + 1], Z[4 * j + 2], Z[4 * j + 3]);
                } else {
#pragma unroll
                    for (int j = 0; j < 5; j++) {
                        const uint4 v = lds128(slot + (w ? 0 : 2560) + j * 512);
                        Z[4 * j] = v.x; Z[4 * j + 1] = v.y; Z[4 * j + 2] = v.z; Z[4 * j + 3] = v.w;
                    }
                }
                BOTH(_Pragma("unroll") for (int c = 0; c < 10; c++) {
                    const int jq = jt_of(0, c, odd);
                    Ql[c] = pack_bf16(acc[4 * jq], acc[4 * jq + 1]);
                    Q[c] = pack_bf16(acc[4 * jq + 2], acc[4 * jq + 3]);
                    asm volatile("" : "+r"(Ql[c]), "+r"(Q[c]));
                })
            }
            auto scores = [&](float (&l)[4], const uint32_t (&q)[10], const uint32_t (&z)[20], const int c0, const uint32_t mx, const float nz) {
                const uint32_t qa = t < 2 ? q[c0 + 2] : 0u, qb = t < 2 ? 0u : q[c0 + 2];
                float xa[4] = {0.f, 0.f, 0.f, 0.f}, za[4] = {nz, nz, nz, nz}, xb[4], zb[4];
                mma1688(xa, qa, qb, KX[c0 + 2]);
                mma1688(za, qa, qb, z[KI(c0 + 2)]);
#pragma unroll
                for (int e = 0; e < 4; e++) { xb[e] = xa[e]; zb[e] = za[e]; }
                mma16816(xa, q[c0], q[c0 + 3], q[c0 + 1], q[c0 + 4], KX[c0], KX[c0 + 1]);
                mma16816(za, q[c0], q[c0 + 3], q[c0 + 1], q[c0 + 4], z[KI(c0)], z[KI(c0 + 1)]);
                mma16816(xb, q[c0], q[c0 + 3], q[c0 + 1], q[c0 + 4], KX[c0 + 3], KX[c0 + 4]);
                mma16816(zb, q[c0], q[c0 + 3], q[c0 + 1], q[c0 + 4], z[KI(c0 + 3)], z[KI(c0 + 4)]);
                const bool h0 = mx & 1u, h1 = (int)mx < 0;
                l[0] = h0 ? xa[0] : za[0]; l[1] = h1 ? xa[1] : za[1];
                l[2] = h0 ? xb[2] : zb[2]; l[3] = h1 ? xb[3] : zb[3];
                asm volatile("" : "+f"(l[0]), "+f"(l[1]), "+f"(l[2]), "+f"(l[3]));
            };
            auto soft = [&](uint32_t (&pr)[2], const float (&l)[4], const float sq) {
                float m0 = fmaxf(l[0], l[1]), m1 = fmaxf(l[2], l[3]);
                m0 = fmaxf(m0, shx(m0, 1)); m1 = fmaxf(m1, shx(m1, 1));
                m0 = fmaxf(m0, shx(m0, 2)) * -sq; m1 = fmaxf(m1, shx(m1, 2)) * -sq;
                pr[0] = pack_bf16(ex2(fmaf(l[0], sq, m0)), ex2(fmaf(l[1], sq, m0)));
                pr[1] = pack_bf16(ex2(fmaf(l[2], sq, m1)), ex2(fmaf(l[3], sq, m1)));
                asm volatile("" : "+r"(pr[0]), "+r"(pr[1]));
            };
            auto values = [&](const uint32_t (&pr)[2], const uint32_t (&z)[20], const int c0, const uint32_t mx, const int h) {
                float dn[4] = {0.f, 0.f, 0.f, 0.f};
                mma1688(dn, pr[0], pr[1], 0x3F803F80u);
                const float i0 = rcp(dn[0]), i1 = rcp(dn[2]), i2 = t < 2 ? i0 : i1;
#pragma unroll
                for (int c = 0; c < 5; c++) {
                    float oc[4] = {0.f, 0.f, 0.f, 0.f};
                    mma16816(oc, pr[0] & mx, pr[1] & mx, pr[0] & ~mx, pr[1] & ~mx, VX[c0 + c], z[10 + c0 + c]);
                    const bool first = c < 2 || (c == 2 && t < 2);
                    const float iv = c < 2 ? i0 : (c > 2 ? i1 : i2);
                    A[0][2 * (c0 + c) + h] = pack_bf16((first ? oc[0] : oc[2]) * iv, (first ? oc[1] : oc[3]) * iv);
                    asm volatile("" : "+r"(A[0][2 * (c0 + c) + h]));
                }
            };
            auto gate = [&]() {
                const float r0 = 0.5f * s0.x, r1 = 0.5f * s1.x, n0 = -r0 * s0.y, n1 = -r1 * s1.y;
#pragma unroll
                for (int j = 0; j < 5; j++) {
#pragma unroll
                    for (int q = 0; q < 4; q++) {
                        const float v0 = fmaf(bflo(xr[j][q]), q & 1 ? r1 : r0, q & 1 ? n1 : n0), v1 = fmaf(bfhi(xr[j][q]), q & 1 ? r1 : r0, q & 1 ? n1 : n0);
                        gf[j][q] = pack_bf16(fmaf(v0, tanh_a(v0), v0), fmaf(v1, tanh_a(v1), v1));
                        asm volatile("" : "+r"(gf[j][q]));
                    }
                }
            };
            const uint32_t mo = (2 * t > g ? 0xFFFFu : 0u) | (2 * t + 1 > g ? 0xFFFF0000u : 0u);
            constexpr float SC = 0.22360679774997896f * LOG2E;
            {
                float l[4][4];
                uint32_t pr[4][2];
                unsigned spins = 0;
#pragma unroll 1
                while (remote && any((Z[0] & Z[4] & Z[8] & Z[12] & Z[16] & par) == 0u) && ++spins < SPIN) {
#pragma unroll
                    for (int j = 0; j < 5; j++) ldg128(halo - 8 * XB + j * 512, Z[4 * j], Z[4 * j + 1], Z[4 * j + 2], Z[4 * j + 3]);
                }
                TR(r32);
                const float nz = start ? -INFINITY : 0.f;
                auto publish = [&](const int j) {
                    A[0][4 * j] = (A[0][4 * j] & ~0x10001u) | par;
                    stg128(orow + hg * XB + j * 512, A[0][4 * j], A[0][4 * j + 1], A[0][4 * j + 2], A[0][4 * j + 3]);
                };
                scores(l[0], Q, Y, 0, mo, 0.f);
                scores(l[2], Ql, Z, 0, ~mo, nz);
                scores(l[1], Q, Y, 5, mo, 0.f);
                scores(l[3], Ql, Z, 5, ~mo, nz);
                soft(pr[0], l[0], s1.x * SC);
                soft(pr[2], l[2], s0.x * SC);
                soft(pr[1], l[1], s1.x * SC);
                soft(pr[3], l[3], s0.x * SC);
                values(pr[0], Y, 0, mo, 1);
                values(pr[2], Z, 0, ~mo, 0);
                publish(0);
                if (lane == 0 && !p) stg32(flag, par);
                publish(1);
                values(pr[1], Y, 5, mo, 1);
                values(pr[3], Z, 5, ~mo, 0);
                publish(2); publish(3); publish(4);
            }
            if (lane == 0 && p) stg32(flag, par);
            TR(r34);
            if (p) bar_arrive(8, 384);
            BLOCK_SPLIT(par);
            gate();
        }
        {
            float acc2[40];
            unsigned spins = 0;
            bool again, first = true;
            const uint8_t* src[7];
#pragma unroll
            for (uint32_t i = 0; i < 7; i++) { src[i] = orow + (i >= hg ? XB : 0u); asm volatile("" : "+l"(src[i])); }
            mbar_wait(sb + B_SEL, 0);
            const float2 sel = lds64f(sb + M_SEL);
            uint32_t routed = (U(sel.x) >> 4) == warp || (U(sel.y) >> 4) == warp;
            asm volatile("" : "+r"(routed));
            BLOCK_SPLIT(par);
            if (p) bar_sync(9, 288); else bar_sync(5, 160);
#pragma unroll 1
            do {
#pragma unroll
                for (uint32_t i = 1; i < 5; i++)
#pragma unroll
                    for (int j = 0; j < 5; j++)
                        ldg128(src[i - 1] + (i - 1) * XB + j * 512, A[i][4 * j], A[i][4 * j + 1], A[i][4 * j + 2], A[i][4 * j + 3]);
                if (!p && first) bar_sync(8, 384);
                uint32_t mn = par;
#pragma unroll
                for (int i = 0; i < 8; i++) {
                    const uint32_t (&a)[20] = A[i % 5];
                    if (i == 4 && !p && first) bar_sync(6, 160);
                    wgmma_fence();
#pragma unroll
                    for (int j = 0; j < 5; j++) {
                        wgmma_rs_n80(acc2, a[4 * j], a[4 * j + 1], a[4 * j + 2], a[4 * j + 3],
                                     mk(sbd + (wo_slot(i) >> 4) + j * 64 + (320 << 16), HI64), i || j);
                        if (i == 7 && j == 2) {
#pragma unroll
                            for (int q = 0; q < 5; q++) mn &= A[q][0] & A[q][4] & A[q][8] & A[q][12] & A[q][16];
                            again = bar_or(2 + p, 128, mn == 0u && ++spins < SPIN);
                        }
                    }
                    if (i < 4 || i == 7) wgmma_commit();
                    if (i == SERAT && !p && first) bar_arrive(9, 288);
                    if (i == 0) TR(r22);
                    if (i >= 1 && i < 4) {
                        uint32_t (&n)[20] = A[i - 1];
                        if (i > 1) mn &= n[0] & n[4] & n[8] & n[12] & n[16];
                        const uint8_t* q = src[i + 3] + (i > 1 ? mn & 256u : 0u);
                        wgmma_wait<1>();
                        bar_arrive(10, 32);
#pragma unroll
                        for (int j = 0; j < 5; j++) ldg128(q + (i + 3) * XB + j * 512, n[4 * j], n[4 * j + 1], n[4 * j + 2], n[4 * j + 3]);
                        bar_arrive(10, 32);
                    }
                }
                first = false;
                if (again) {
                    wgmma_wait<0>();
#pragma unroll
                    for (int j = 0; j < 5; j++)
                        ldg128(orow + hg * XB + j * 512, A[0][4 * j], A[0][4 * j + 1], A[0][4 * j + 2], A[0][4 * j + 3]);
                }
            } while (again);
            const uint32_t o0 = (hg & 1) * 32, o4 = (~hg & 1) * 128;
            if (routed) {
                const float2 sel = lds64f(sb + M_SEL);
                mbar_wait(sb + B_UPD, 0);
#pragma unroll
                for (uint32_t h = 0; h < 2; h++) {
                    const uint32_t row = warp * 16 + g + 8 * h, ga = sb + M_UPD + (row == U(sel.x) ? 0 : 160) + t * 4;
                    if (row == U(sel.x) || row == U(sel.y)) {
#pragma unroll
                        for (int c = 0; c < 5; c++) { gf[c][h] = lds32(ga + (c < 4 ? o0 + c * 32 : o4)); gf[c][h + 2] = lds32(ga + (c < 4 ? o0 + c * 32 : o4) + 16); }
                    }
                }
                __syncwarp();
            }
            wgmma_wait<0>();
#pragma unroll
            for (int i = 0; i < 40; i++) asm volatile("" : "+f"(acc2[i]) :: "memory");
            TR(r44);
#pragma unroll
            for (int c = 0; c < 5; c++) {
#pragma unroll
                for (int q = 0; q < 4; q++)
                    asm("fma.rn.bf16x2 %0, %1, %2, %0;" : "+r"(xr[c][q]) : "r"(pack_bf16(acc2[8 * c + 2 * q], acc2[8 * c + 2 * q + 1])), "r"(gf[c][q]));
                stsm_x4(ta + (c < 4 ? o0 + c * 32 : o4) + OFF_DN, xr[c]);
            }
            fence_proxy_async_smem();
            __syncwarp();
            if (lane == 0) {
                tma_st(&P.tm[T_OUT], sb + OFF_DN + warp * 2560, hg * 80, rb * 64 + 16 * w, p);
                asm volatile("cp.async.bulk.wait_group.read 0;" ::: "memory");
            }
        }
        TS(46);
        TRW(r12, 12); TRW(r32, 32); TRW(r34, 34); TRW(r22, 22); TRW(r44, 44);
    } else if (warp >= 12) {
        asm volatile("setmaxnreg.dec.sync.aligned.u32 24;");
        if (warp == 12) {
            uint32_t slot = t0 + PACE0;
            if (elect()) {
#pragma unroll 1
                for (uint32_t kb = 1; kb < 10; kb++) {
                    const uint32_t s = (kb + 2) & 3;
                    const uint32_t st = sb + s * ST, fb = sb + B_FULL + 8 * s;
                    const uint32_t kc = kb * 64 + (kb < 5 ? k0 : -k0);
                    if (kb >= 4) {
                        mbar_wait(fb + 32, kb >> 3);
                        if (kb < 9) mbar_wait(sb + B_AX - 32 + 8 * kb, 0);
                    }
                    {
                        slot += PACE1;
#pragma unroll 1
                        while ((int)(clock32() - slot) < 0) { }
                        mbar_expect_tx(fb, ST);
                        tma(st, &P.tm[T_X], fb, kc, rb * 64);
                    }
                    tma_mc(st + ST_BM + rank * 12288, &P.tm[T_W], fb, hg * 80 + (hg & 1) * 16, kc + rank * 32);
                    tma_mc(st + ST_BR + rank * 3072, &P.tm[T_WR], fb, hg * 80 + 64 - (hg & 1) * 64, kc + rank * 32);
                }
                uint32_t wb = sb + B_WO - 8;
#pragma unroll 1
                for (uint32_t i = 0; i < 8; i++) {
                    if ((0x93 >> i) & 1) {
                        wb += 8;
                        mbar_wait(wb - (B_WO - B_EMPTY), i < 2);
                        mbar_expect_tx(wb, (i + 1) & 6 ? 3 * 12800 : 12800);
                    }
                    if (i == 0) {
                        mbar_expect_tx(sb + B_DN, 20480);
                        tma(sb + OFF_DN, &P.tm[T_D], sb + B_DN, 0, 32 * fp, 5 * rank);
                    }
                    if (WOP) {
#pragma unroll 1
                        while ((int)(clock32() - slot) < 0) { }
                        slot = clock32() + WOP;
                    }
                    const uint32_t d = sb + wo_slot(i);
                    const uint32_t kr = 80 * (i ? i - (i <= hg) : hg);
                    tma_mc(d + rank * 5120, &P.tm[T_WO], wb, hg * 80 + (hg & 1) * 16 + rank * 32, kr);
                    tma_mc(d + 10240 + rank * 2560, &P.tm[T_WOR], wb, hg * 80 + (~hg & 1) * 64, kr + rank * 40);
                }
            }
        } else if (warp == 13) {
            if (elect()) {
#pragma unroll 1
                for (uint32_t i = 0; i < 3; i++) {
#pragma unroll 1
                    while (clock32() - t0 < PX0 + i * PX1) __nanosleep(20);
                    l2_prefetch(P.w + ((i + 2) * 245760 + b * 1920), 1920);
                    l2_prefetch(P.w + ((i + 7) * 245760 + b * 1920), 1920);
                }
#pragma unroll 1
                for (uint32_t i = 0; i < 14; i++) {
#pragma unroll 1
                    while (clock32() - t0 < GU0 + i * GU1) __nanosleep(20);
                    if (i < 10) l2_prefetch(P.wd + (i * 128 + b) * 1728, 1728);
                    else l2_prefetch(P.wo + ((i - 10) * 128 + b) * 1600, 1600);
                }
            }
        } else if (warp == 15) {
            const uint32_t lane = opaque_tid() & 31;
            const uint8_t* fl = P.scr + (G_FLAG + (rb * 8 + (lane & 7)) * XB + (lane >> 3) * 8);
            cluster_wait();
            mbar_wait(sb + B_PREP, 0);
            const uint32_t par = lds32(sb + M_SEL + 8);
            mbar_wait(sb + B_WO, 0); mbar_wait(sb + B_WO + 8, 0);
            mbar_wait(sb + B_EMPTY + 24, 0);
            __nanosleep(WSL);
            unsigned spins = 0;
            uint2 f;
#pragma unroll 1
            do f = ldg64(fl); while (any(f.x != par) && ++spins < SPIN);
            bar_arrive(5, 160);
            TS(24);
            mbar_wait(sb + B_WO + 16, 0); mbar_wait(sb + B_WO + 24, 0);
            bar_arrive(6, 160);
#pragma unroll 1
            while (any(f.y != par) && ++spins < SPIN) f.y = ldg32(fl + 4);
            bar_arrive(9, 288);
            TS(25);
        } else {
            uint32_t slot = t0 + GT0;
            cluster_wait();
            if (elect()) {
#pragma unroll 1
                for (uint32_t i = 0; i < 20; i++) {
                    slot += GT1;
#pragma unroll 1
                    while ((int)(clock32() - slot) < 0) __nanosleep(20);
                    tma(sb + OFF_GU + i * 2048, &P.tm[T_GU], sb + B_GU, 32 * fp, rank * 320 + i * 16);
                }
            }
        }
    } else {
        asm volatile("setmaxnreg.dec.sync.aligned.u32 72;");
        const uint32_t at = opaque_tid() - 256, lane = at & 31, g = lane >> 2, t = lane & 3, c7 = lane & 7, aw = warp - 8;
        uint8_t* const yz = P.scr + (G_Y + b * 512 + at * 4);
        stg32(yz, 0u);
        __nanosleep(AUXS);
        const uint32_t epoch = ldg32(P.scr + G_EPOCH) + 1 + ldg32(yz), tag = (epoch & 15u) | 16u;
        const uint32_t empty_cl = mapa(sb + B_EMPTY, lane & 1);
        unsigned spins = 0;
        TRD(r51); TRD(r30); TRD(r52); TRD(r53); TRD(r54); TRD(r55); TRD(r20); TRD(r22);
        {
            const uint2 wv = __ldg(reinterpret_cast<const uint2*>(P.w_r + k0 * 2 + min(at, 79u) * 8));
            if (at < 80) sts64(sb + M_UPD + at * 8, wv.x, wv.y);
        }
        uint8_t* const stw = P.scr + (b * XB + G_ST + (lane & 4) * 64 + (at >> 3) * 16);
        uint8_t* const csw = P.scr + (b * XB + G_CS + at);
        uint8_t* const tpw = P.scr + (G_TOP + (hg >> 2) * XB + rb * 64 + aw * 16);
        const bool tpub = lane == 0 && (hg & 3) == 3;
        cluster_wait();
        bar_sync(4, 128);
        mbar_wait(sb + B_FULL + 16, 0);
        if (t == 0) { stg128(stw, 0u, 0u, 0u, 0u); stg32(csw, 0u); }
        if (tpub) stg128(tpw, 0u, 0u, 0u, 0u);

        uint32_t k1, sv;
        {
            const uint32_t xoff = (32 * (hg & 3) + (at >> 3)) * 128 + ((c7 ^ ((at >> 3) & 7)) << 4);
            const uint32_t jt = (rb >> 2) * 8 + rank * 4 + aw;
            const uint32_t coff = jt < 24 ? ST_BM + (jt >> 3) * 4096 + lane * 128 + (((jt ^ lane) & 7) << 4)
                                          : ST_BR + ((jt >> 1) & 3) * 1024 + lane * 32 + (((jt ^ g) & 1) << 4);
            float q[8], c8[8];
#pragma unroll
            for (int e = 0; e < 8; e++) q[e] = c8[e] = 0.f;
#pragma unroll 1
            for (uint32_t kb = 2; kb < 7; kb++) {
                const uint32_t st = sb + (kb & 3) * ST;
                const uint4 wv = lds128(sb + M_UPD - 256 + kb * 128 + c7 * 16);
                mbar_wait(sb + B_FULL + 8 * (kb & 3), kb == 6);
                const uint4 v = lds128(st + xoff), vn = lds128(st + xoff + 2048);
                const uint4 cv = lds128(st + coff), cn = lds128(st + coff + (jt < 24 ? 12288 : 3072));
                if (lane < 2) mbar_arrive_cl(empty_cl - (B_EMPTY + 16 - B_AX) + 8 * kb);
                const uint32_t u[4] = {v.x, v.y, v.z, v.w}, un[4] = {vn.x, vn.y, vn.z, vn.w}, ww[4] = {wv.x, wv.y, wv.z, wv.w};
                const uint32_t cc[4] = {cv.x, cv.y, cv.z, cv.w}, cd[4] = {cn.x, cn.y, cn.z, cn.w};
#pragma unroll
                for (int e = 0; e < 4; e++) {
                    const float a0 = bflo(u[e]), a1 = bfhi(u[e]), b0 = bflo(un[e]), b1 = bfhi(un[e]), w0 = bflo(ww[e]), w1 = bfhi(ww[e]);
                    q[0] += a0 + a1; q[4] += b0 + b1; q[3] += w0 + w1;
                    q[1] = fmaf(a0, a0, fmaf(a1, a1, q[1])); q[5] = fmaf(b0, b0, fmaf(b1, b1, q[5]));
                    q[2] = fmaf(a0, w0, fmaf(a1, w1, q[2])); q[6] = fmaf(b0, w0, fmaf(b1, w1, q[6]));
                    c8[2 * e] += bflo(cc[e]) + bflo(cd[e]); c8[2 * e + 1] += bfhi(cc[e]) + bfhi(cd[e]);
                }
            }
            TR(r51);
            q[7] = q[3];
#pragma unroll
            for (int e = 0; e < 4; e++) {
                q[e] = ((lane & 4) ? q[e + 4] : q[e]) + shx((lane & 4) ? q[e] : q[e + 4], 4);
                q[e] += shx(q[e], 1); q[e] += shx(q[e], 2);
            }
            const float mh = q[0] * (1.0f / 320);
            if (t == 0) stg128(stw, U(mh), U(fmaf(-mh, q[0], q[1])), U(q[2]), (U(q[3]) & ~31u) | tag);
#define TSTEP(H) { const bool up = (lane & (4 * H)) != 0; _Pragma("unroll") for (int e = 0; e < H; e++) { \
            const float send = up ? c8[e] : c8[e + H]; const float keep = up ? c8[e + H] : c8[e]; \
            c8[e] = keep + shx(send, 4 * H); } }
            TSTEP(4) TSTEP(2) TSTEP(1)
#undef TSTEP
            c8[0] += shx(c8[0], 1); c8[0] += shx(c8[0], 2);
            if (t == 0) stg32(csw, (U(c8[0]) & ~31u) | tag);
            TR(r30);
            const uint8_t* csp = P.scr + (G_CS + (aw * 32 + (lane >> 4) * 8 + hg) * XB + (lane & 15) * 8);
            const uint8_t* stp = P.scr + (G_ST + (rb * 8 + aw) * XB + lane * 16);
            uint32_t ra[4], rc[4];
            uint2 ca, cc;
#pragma unroll 1
            while (clock32() - t0 < EX1T) __nanosleep(20);
#pragma unroll 1
            do {
                ldg128(stp, ra[0], ra[1], ra[2], ra[3]);
                ldg128(stp + 4 * XB, rc[0], rc[1], rc[2], rc[3]);
                ca = ldg64(csp); cc = ldg64(csp + 16 * XB);
            } while (any((ra[3] ^ tag | rc[3] ^ tag) & 31u) && ++spins < SPIN);
            TR(r20);
            const float dm = 0.5f * (F(ra[0]) - F(rc[0])), m = bf16r(F(rc[0]) + dm);
            const float sd = bf16r(sqrt_a(bf16r(bf16r(fmaxf(fmaf(dm, dm, (F(ra[1]) + F(rc[1])) * (1.0f / DM)), 0.f)) + 1e-5f)));
            const float rs = rcp(sd);
            uint32_t w1, w2;
            if ((hg & 3) == 3) {
                k1 = pack_bf16(0.f, fmaf(-m, F(ra[3]) + F(rc[3]), F(ra[2]) + F(rc[2])) * rs);
                k1 ^= ((int)k1 >> 31) | 0x80000000u;
                k1 = (k1 & 0xFFFF0000u) | ((2047 - (rb * 128 + 2 * (at & 63) + (at >> 6))) << 5) | tag;
                w1 = redux_max(k1); w2 = redux_max(k1 == w1 ? 0u : k1);
                sv = U(m) | (U(sd) >> 16);
                const uint32_t v1 = redux_max(k1 == w1 ? sv : 0u), v2 = redux_max(k1 == w2 ? sv : 0u);
                if (lane == 0) stg128(tpw, w1, v1, w2, v2);
            }
            sts64(sb + M_ST + at * 8, U(rs), U(m));
            sts32(sb + M_SEL + 8, (tag & 1) ? 1u : 0x10000u);
#pragma unroll 1
            while (any((ca.x ^ tag | ca.y ^ tag | cc.x ^ tag | cc.y ^ tag) & 31u) && ++spins < SPIN) { ca = ldg64(csp); cc = ldg64(csp + 16 * XB); }
            {
                const float c0 = at < 120 ? F(ca.x) + F(cc.x) : 0.f, c1 = at < 120 ? F(ca.y) + F(cc.y) : 0.f;
                const uint32_t hi = pack_bf16(c0, c1);
                sts32(sb + M_CS + (at >> 2) * 32 + t * 4, hi);
                sts32(sb + M_CS + (at >> 2) * 32 + t * 4 + 16, pack_bf16(c0 - bflo(hi), c1 - bfhi(hi)));
                fence_proxy_async_smem();
                __syncwarp();
                if (lane < 2) mbar_arrive(sb + B_PREP);
            }
            TR(r52);
            if (aw == 0) {
                uint32_t ka[4], kb[4];
#pragma unroll 1
                while (clock32() - t0 < EX1T + EX2D) __nanosleep(20);
#pragma unroll 1
                do {
                    const uint8_t* tp = P.scr + (G_TOP + lane * 16);
                    uint32_t kc[4], kd[4];
                    ldg128(tp, ka[0], ka[1], ka[2], ka[3]);
                    ldg128(tp + 512, kb[0], kb[1], kb[2], kb[3]);
                    ldg128(tp + XB, kc[0], kc[1], kc[2], kc[3]);
                    ldg128(tp + XB + 512, kd[0], kd[1], kd[2], kd[3]);
                    const bool ba = (ka[0] ^ tag) & 31u, bb = (kb[0] ^ tag) & 31u;
#pragma unroll
                    for (int e = 0; e < 4; e++) { ka[e] = ba ? kc[e] : ka[e]; kb[e] = bb ? kd[e] : kb[e]; }
                } while (any((ka[0] ^ tag | kb[0] ^ tag) & 31u) && ++spins < SPIN);
                TR(r22);
                if (kb[0] > ka[0]) {
#pragma unroll
                    for (int e = 0; e < 4; e++) { const uint32_t x = ka[e]; ka[e] = kb[e]; kb[e] = x; }
                }
                if (kb[0] > ka[2]) { ka[2] = kb[0]; ka[3] = kb[1]; }
                w1 = redux_max(ka[0]);
                const uint32_t t1 = redux_max(ka[0] == w1 ? ka[1] : 0u);
                if (ka[0] == w1) { ka[0] = ka[2]; ka[1] = ka[3]; }
                w2 = redux_max(ka[0]);
                const uint32_t t3 = redux_max(ka[0] == w2 ? ka[1] : 0u);
                sts128(sb + M_TOP, w1, t1, w2, t3);
            }
            bar_sync(4, 128);
            const float2 tv = lds64f(sb + M_TOP + (lane & 1) * 8);
            k1 = U(tv.x);
            sv = U(tv.y);
        }
        TR(r53);
        const uint32_t tok = ~(k1 >> 5) & 2047;
        const unsigned owns = __ballot_sync(0xffffffffu, (tok >> 7) == rb) & 3u;
        if (at < 2) sts32(sb + M_SEL + at * 4, (tok >> 7) == rb ? (tok & 1) * 64 + ((tok & 127) >> 1) : ~0u);
        if ((at | b) == 0) *reinterpret_cast<uint32_t*>(P.scr + G_EPOCH) = epoch;
        __syncwarp();
        if (at == 0) mbar_arrive(sb + B_SEL);
        if (fp < NFFN / 2) {
            uint4 xv = __ldg(reinterpret_cast<const uint4*>(P.x + (tok * 1280 + rank * 640 + min(at >> 1, 39u) * 16)));
            const uint32_t m2 = __byte_perm(sv, 0, 0x3232);
            asm("sub.rn.bf16x2 %0, %0, %4;\nsub.rn.bf16x2 %1, %1, %4;\nsub.rn.bf16x2 %2, %2, %4;\nsub.rn.bf16x2 %3, %3, %4;"
                : "+r"(xv.x), "+r"(xv.y), "+r"(xv.z), "+r"(xv.w) : "r"(m2));
            mbar_wait(sb + B_DN, 0);
            if (at < 80) sts128(sb + OFF_PART + at * 16, xv.x, xv.y, xv.z, xv.w);
            mbar_wait(sb + B_GU, 0);
            mbar_wait(sb + B_EMPTY + 24, 0);
            bar_sync(4, 128);
            float c[5][4];
            uint32_t wf[10][4];
#pragma unroll
            for (int i = 0; i < 5; i++) c[i][0] = c[i][1] = c[i][2] = c[i][3] = 0.f;
            const uint32_t mi = lane >> 3, kr = c7 + (mi >> 1) * 8;
            {
                const uint32_t wa = sb + OFF_GU + (aw >> 1) * 1024 + kr * 64 + ((((aw & 1) * 2 + (mi & 1)) ^ ((kr >> 1) & 3)) << 4);
#pragma unroll
                for (uint32_t i = 0; i < NPRE; i++) ldsm_x4_t(wf[i], wa + i * 2048);
                __nanosleep(FFNS);
                BLOCK_SPLIT(tag);
#pragma unroll
                for (uint32_t i = 0; i < 20; i += 2) {
                    uint32_t xb[4];
                    ldsm_x4(xb, sb + OFF_PART + i * 64 + mi * 32 + (lane & 1) * 16);
#pragma unroll
                    for (uint32_t j = i; j < i + 2; j++) {
                        const uint32_t (&a)[4] = wf[j % NPRE];
                        mma16816(c[j & 1], a[0], a[1], a[2], a[3], xb[2 * (j & 1)], xb[2 * (j & 1) + 1]);
                        if (j + NPRE < 20) ldsm_x4_t(wf[j % NPRE], wa + (j + NPRE) * 2048);
                    }
                }
#pragma unroll
                for (int e = 0; e < 4; e++) c[0][e] += c[1][e];
                const uint32_t rd = mapa(sb, rank ^ (t & 1));
                if (t < 2)
                    asm volatile("st.async.shared::cluster.mbarrier::complete_tx::bytes.v4.f32 [%0], {%1,%2,%3,%4}, [%5];"
                                 :: "r"(rd + (t ? OFF_PART + 1280 : M_UPD + 192) + aw * 128 + g * 16), "f"(c[0][0]), "f"(c[0][1]), "f"(c[0][2]), "f"(c[0][3]), "r"(rd + B_H) : "memory");
            }
            TR(r54);
            const float rs = rcp(bflo(sv));
            const uint32_t da = sb + OFF_DN + kr * 128 + (((2 * aw + (mi & 1)) ^ c7) << 4);
            uint8_t* yp = P.scr + (G_Y + (fp % 6) * 10240 + rank * 2560 + t * 512 + aw * 128 + g * 16);
#pragma unroll
            for (int i = 0; i < 5; i++) c[i][0] = c[i][1] = c[i][2] = c[i][3] = 0.f;
#pragma unroll
            for (uint32_t j = 0; j < NPD; j++) ldsm_x4_t(wf[j], da + (j % 5) * 4096 + (j / 5) * 2048);
            mbar_wait(sb + B_H, 0);
#pragma unroll
            for (uint32_t ks = 0; ks < 2; ks++) {
                const uint32_t og = sb + ks * 128 + lane * 4 + P.up_first, ou = og ^ 256;
                const float gs = bf16r((F(lds32(og + M_UPD + 192)) + F(lds32(og + OFF_PART + 1280))) * rs);
                const float h = bf16r(gs * sigm(gs)) * bf16r((F(lds32(ou + M_UPD + 192)) + F(lds32(ou + OFF_PART + 1280))) * rs);
                const uint32_t hp = pack_bf16(h, __shfl_down_sync(0xffffffffu, h, 4));
                const uint32_t h0 = __shfl_sync(0xffffffffu, hp, t * 8 + (g & 1)), h1 = __shfl_sync(0xffffffffu, hp, t * 8 + (g & 1) + 2);
#pragma unroll
                for (uint32_t j = 0; j < 5; j++) {
                    uint32_t (&a)[4] = wf[ks * 5 + j];
                    if (ks * 5 + j >= NPD) ldsm_x4_t(a, da + j * 4096 + ks * 2048);
                    mma16816(c[j], a[0], a[1], a[2], a[3], h0, h1);
                }
            }
#pragma unroll
            for (int e = 0; e < 4; e++) {
                const float lo = (t & 1) ? c[1][e] : c[0][e], hi = (t & 1) ? c[3][e] : c[2][e];
                c[0][e] = (t & 2) ? hi : lo;
            }
            asm volatile("" : "+f"(c[0][0]), "+f"(c[4][0]) :: "memory");
            BLOCK_SPLIT(tag);
            bar_sync(8, 384);
            { red4(yp, c[0][0], c[0][2]); red4(yp + 5120, c[0][1], c[0][3]); }
            if (t == 0) { red4(yp + 2048, c[4][0], c[4][2]); red4(yp + 2048 + 5120, c[4][1], c[4][3]); }
            TR(r55);
        }
        else {
            mbar_wait(sb + B_DN, 0); mbar_wait(sb + B_GU, 0);
            bar_arrive(8, 384);
        }
        TRW(r51, 51); TRW(r30, 30); TRW(r52, 52); TRW(r53, 53); TRW(r54, 54); TRW(r55, 55); TRW(r20, 20); TRW(r22, 22);
        if (owns) {
            const uint32_t u = min(at >> 1, 39u), col = (u >> 3) * 32 + (u & 7) * 2;
            const bool mine = (tok >> 7) == rb && at < 80;
            k1 ^= ((~(int)k1) >> 31) | 0x80000000u;
            const float sg = bf16r(sigm(bfhi(k1))), rs = rcp(bflo(sv));
            uint32_t x0, x1, y0, y1, n0, n1;
            asm volatile("ld.global.nc.u16 %0, [%2];\nld.global.nc.u16 %1, [%2 + 16];" : "=r"(x0), "=r"(x1) : "l"(P.x + (tok * 1280 + hg * 160 + col)));
            const float a0 = (bflo(x0) - bfhi(sv)) * rs, a1 = (bflo(x1) - bfhi(sv)) * rs;
            bar_sync(4, 128);
#pragma unroll 1
            do {
                __nanosleep(YSL);
                uint32_t v[6][4];
#pragma unroll
                for (int r = 0; r < 6; r++) if (mine) ldg128(P.scr + (G_Y + (at & 1) * 5120 + hg * 640 + u * 16) + r * 10240, v[r][0], v[r][1], v[r][2], v[r][3]);
                y0 = U(((F(v[0][0]) + F(v[1][0])) + (F(v[2][0]) + F(v[3][0]))) + (F(v[4][0]) + F(v[5][0])));
                y1 = U(((F(v[0][1]) + F(v[1][1])) + (F(v[2][1]) + F(v[3][1]))) + (F(v[4][1]) + F(v[5][1])));
                n0 = U(((F(v[0][2]) + F(v[1][2])) + (F(v[2][2]) + F(v[3][2]))) + (F(v[4][2]) + F(v[5][2])));
                n1 = U(((F(v[0][3]) + F(v[1][3])) + (F(v[2][3]) + F(v[3][3]))) + (F(v[4][3]) + F(v[5][3])));
            } while (any(mine && (F(n0) != NFFN / 2 || F(n1) != NFFN / 2)) && ++spins < SPIN);
            const float v0 = a0 + bf16r(bf16r(F(y0)) * sg), v1 = a1 + bf16r(bf16r(F(y1)) * sg);
            const uint32_t gp = pack_bf16(v0 * sigm(v0), v1 * sigm(v1));
            if (mine) asm volatile("st.shared.u16 [%0], %1;\nst.shared.u16 [%0 + 16], %2;" :: "r"(sb + M_UPD + (at & 1) * 160 + col), "r"(gp), "r"(gp >> 16) : "memory");
            __syncwarp();
            if (lane < 2) mbar_arrive(sb + B_UPD);
            TS(56);
        }
    }
}

typedef CUresult (*EncodeFn)(CUtensorMap*, CUtensorMapDataType, cuuint32_t, void*, const cuuint64_t*, const cuuint64_t*,
                             const cuuint32_t*, const cuuint32_t*, CUtensorMapInterleave, CUtensorMapSwizzle,
                             CUtensorMapL2promotion, CUtensorMapFloatOOBfill);

bool encode(EncodeFn fn, CUtensorMap* tm, const void* ptr, cuuint64_t d0, cuuint64_t d1, cuuint64_t d2, cuuint64_t s1, cuuint64_t s2,
            cuuint32_t b0, cuuint32_t b1, cuuint32_t b2, CUtensorMapSwizzle sw) {
    const cuuint64_t dims[3] = {d0, d1, d2}, strides[2] = {s1, s2};
    const cuuint32_t box[3] = {b0, b1, b2}, es[3] = {1, 1, 1};
    return fn(tm, CU_TENSOR_MAP_DATA_TYPE_BFLOAT16, 3, const_cast<void*>(ptr), dims, strides, box, es,
              CU_TENSOR_MAP_INTERLEAVE_NONE, sw, CU_TENSOR_MAP_L2_PROMOTION_L2_128B,
              CU_TENSOR_MAP_FLOAT_OOB_FILL_NONE) == CUDA_SUCCESS;
}

}

extern "C" void kernel_launch(void* const* d_in, const int* in_sizes, int n_in, void* d_out, int out_size) {
    static Params P;
    static bool by_sm = false;
    static const void* cached[9] = {};
    bool same = cached[8] == d_out;
    for (int i = 0; i < 8; i++) same = same && cached[i] == d_in[i];
    if (!same) {
        const void *x = d_in[0], *wqkv = d_in[1], *wo = d_in[2], *wg = d_in[5], *wu = d_in[6], *wd = d_in[7];
        void* fnp = nullptr;
        cudaDriverEntryPointQueryResult qr;
        cudaGetDriverEntryPoint("cuTensorMapEncodeTiled", &fnp, cudaEnableDefault, &qr);
        EncodeFn fn = (EncodeFn)fnp;
        const CUtensorMapSwizzle S0 = CU_TENSOR_MAP_SWIZZLE_NONE, S32 = CU_TENSOR_MAP_SWIZZLE_32B, S64 = CU_TENSOR_MAP_SWIZZLE_64B,
                                 S128 = CU_TENSOR_MAP_SWIZZLE_128B;
        const bool ok = fn != nullptr &&
            encode(fn, &P.tm[T_X], x, 640, 1024, 2, 2560, 1280, 64, 64, 2, S128) &&
            encode(fn, &P.tm[T_OUT], d_out, 640, 1024, 2, 2560, 1280, 80, 16, 1, S0) &&
            encode(fn, &P.tm[T_W], wqkv, 640, 640, 3, 3840, 1280, 64, 32, 3, S128) &&
            encode(fn, &P.tm[T_WR], wqkv, 640, 640, 3, 3840, 1280, 16, 32, 3, S32) &&
            encode(fn, &P.tm[T_GU], wg < wu ? wg : wu, 1728, 640, 2, 3456, wg < wu ? (const char*)wu - (const char*)wg : (const char*)wg - (const char*)wu,
                   32, 16, 2, S64) &&
            encode(fn, &P.tm[T_D], wd, 64, 1728, 10, 1280, 128, 64, 32, 5, S128) &&
            encode(fn, &P.tm[T_WO], wo, 640, 640, 1, 1280, 1280 * 640, 32, 80, 1, S64) &&
            encode(fn, &P.tm[T_WOR], wo, 640, 640, 1, 1280, 1280 * 640, 16, 40, 1, S64);
        if (!ok) return;
        P.up_first = wg < wu ? 0 : 256;
        P.wo = (const uint8_t*)wo; P.wd = (const uint8_t*)wd;
        P.x = (const uint8_t*)x; P.w = (const uint8_t*)wqkv; P.w_r = (const uint8_t*)d_in[4];
        if (cudaGetSymbolAddress((void**)&P.scr, g_scr) != cudaSuccess) return;
        cudaFuncSetAttribute(fused_kernel<true>, cudaFuncAttributeMaxDynamicSharedMemorySize, SMEM_BYTES);
        cudaFuncSetAttribute(fused_kernel<false>, cudaFuncAttributeMaxDynamicSharedMemorySize, SMEM_BYTES);
        int ncl = 0, sms = 0, dev = 0;
        {
            cudaLaunchConfig_t cfg = {};
            cfg.gridDim = dim3(128); cfg.blockDim = dim3(NTHREADS); cfg.dynamicSmemBytes = SMEM_BYTES;
            cudaLaunchAttribute at[1];
            at[0].id = cudaLaunchAttributeClusterDimension;
            at[0].val.clusterDim.x = 2; at[0].val.clusterDim.y = 1; at[0].val.clusterDim.z = 1;
            cfg.attrs = at; cfg.numAttrs = 1;
            if (cudaOccupancyMaxActiveClusters(&ncl, fused_kernel<true>, &cfg) != cudaSuccess || ncl < 64) return;
            cudaGetDevice(&dev);
            cudaDeviceGetAttribute(&sms, cudaDevAttrMultiProcessorCount, dev);
        }
        by_sm = sms == 132 && ncl == 66;
        for (int i = 0; i < 8; i++) cached[i] = d_in[i];
        cached[8] = d_out;
    }
    if (by_sm) fused_kernel<true><<<132, NTHREADS, SMEM_BYTES>>>(P);
    else fused_kernel<false><<<128, NTHREADS, SMEM_BYTES>>>(P);
}
```

```cpp
#include <cuda_runtime.h>
#include <cuda_bf16.h>
#include <cuda.h>
#include <stdint.h>

namespace {

constexpr int DM = 640;
constexpr int NTHREADS = 512;
constexpr int NFFN = 108;
#define LEAD 3
#define PACE0 420
#define PACE1 880
#define PX0 2400
#define PX1 250
#define GU0 6000
#define GU1 220
#define GT0 2800
#define GT1 410
#define WOP 150
#define AUXS 500
#define EX1T 8100
#define EX2D 2500
#define SERAT 2
#define FFNS 400
#define NPRE 8
#define NPD 8
#define YSL 100
#define WSL 300

constexpr int ST = 47104;
constexpr int ST_BM = 16384, ST_BR = 40960;
constexpr int OFF_DN = 0;
constexpr int OFF_PART = 20480;
constexpr int OFF_WO = 22528;
constexpr int WO_SLOT = 15360;
constexpr int OFF_HO = 3 * ST;
__host__ __device__ constexpr int wo_slot(int i) { return i < 7 ? OFF_WO + i * WO_SLOT : 3 * ST + ST_BM; }
constexpr int OFF_GU = 4 * ST;
constexpr int M_ST = OFF_GU + 40960;
constexpr int M_CS = M_ST + 1024;
constexpr int M_UPD = M_CS + 1024;
constexpr int M_TOP = M_UPD + 640;
constexpr int M_SEL = M_TOP + 64;
constexpr int B_AX = M_SEL + 16, B_PREP = B_AX + 40, B_UPD = B_PREP + 8,
              B_GU = B_AX + 64, B_DN = B_GU + 8, B_H = B_DN + 8, B_SEL = B_H + 8,
              B_FULL = B_GU + 32, B_EMPTY = B_FULL + 32, B_WO = B_EMPTY + 32;
constexpr int SMEM_BYTES = B_WO + 32;
static_assert(SMEM_BYTES <= 232448 && wo_slot(1) <= ST && wo_slot(4) <= 2 * ST && wo_slot(6) + WO_SLOT <= 3 * ST, "smem");

enum { T_X, T_W, T_WR, T_GU, T_D, T_WO, T_WOR, T_OUT, T_N };
struct Params {
    CUtensorMap tm[T_N];
    const uint8_t* x;
    const uint8_t* w_r;
    const uint8_t* w;
    const uint8_t* wo;
    const uint8_t* wd;
    uint8_t* scr;
    uint32_t up_first;
};

constexpr uint32_t XB = 27392;
constexpr uint32_t G_TOP = 25600;
constexpr uint32_t G_CS = G_TOP + 1024;
constexpr uint32_t G_ST = G_CS + 128;
constexpr uint32_t G_FLAG = G_ST + 512;
constexpr uint32_t G_Y = 128 * XB;
constexpr uint32_t G_EPOCH = G_Y + 128 * 512;
static_assert(G_FLAG + 128 == XB, "scratch");
__device__ __align__(1024) uint8_t g_scr[G_EPOCH + 1024];

constexpr unsigned SPIN = 1u << 20;

__device__ __forceinline__ void mbar_init(uint32_t bar, int cnt) {
    asm volatile("mbarrier.init.shared::cta.b64 [%0], %1;" :: "r"(bar), "r"(cnt) : "memory");
}
__device__ __forceinline__ void mbar_expect_tx(uint32_t bar, int bytes) {
    asm volatile("mbarrier.arrive.expect_tx.shared::cta.b64 _, [%0], %1;" :: "r"(bar), "r"(bytes) : "memory");
}
__device__ __forceinline__ void mbar_arrive(uint32_t bar) {
    asm volatile("mbarrier.arrive.shared::cta.b64 _, [%0];" :: "r"(bar) : "memory");
}
__device__ __forceinline__ uint32_t mapa(uint32_t a, uint32_t cta) {
    uint32_t r;
    asm("mapa.shared::cluster.u32 %0, %1, %2;" : "=r"(r) : "r"(a), "r"(cta));
    return r;
}
__device__ __forceinline__ void mbar_arrive_cl(uint32_t cbar) {
    asm volatile("mbarrier.arrive.shared::cluster.b64 _, [%0];" :: "r"(cbar) : "memory");
}
__device__ __forceinline__ void mbar_wait(uint32_t bar, int parity) {
    asm volatile("{\n.reg .pred p;\nLAB_WAIT:\nmbarrier.try_wait.parity.shared::cta.b64 p, [%0], %1;\n@!p bra LAB_WAIT;\n}"
                 :: "r"(bar), "r"(parity) : "memory");
}
__device__ __forceinline__ bool mbar_try(uint32_t bar, int parity) {
    uint32_t r;
    asm volatile("{\n.reg .pred p;\nmbarrier.test_wait.parity.shared::cta.b64 p, [%1], %2;\nselp.u32 %0, 1, 0, p;\n}"
                 : "=r"(r) : "r"(bar), "r"(parity) : "memory");
    return r != 0;
}
__device__ __forceinline__ void tma(uint32_t dst, const CUtensorMap* tm, uint32_t bar, int c0, int c1, int c2 = 0) {
    asm volatile("cp.async.bulk.tensor.3d.shared::cluster.global.mbarrier::complete_tx::bytes [%0], [%1, {%3, %4, %5}], [%2];"
                 :: "r"(dst), "l"(tm), "r"(bar), "r"(c0), "r"(c1), "r"(c2) : "memory");
}
__device__ __forceinline__ void tma_mc(uint32_t dst, const CUtensorMap* tm, uint32_t bar, int c0, int c1) {
    asm volatile("cp.async.bulk.tensor.3d.shared::cluster.global.mbarrier::complete_tx::bytes.multicast::cluster [%0], [%1, {%3, %4, %5}], [%2], %6;"
                 :: "r"(dst), "l"(tm), "r"(bar), "r"(c0), "r"(c1), "r"(0), "h"((uint16_t)3) : "memory");
}
__device__ __forceinline__ void tma_st(const CUtensorMap* tm, uint32_t src, int c0, int c1, int c2) {
    asm volatile("cp.async.bulk.tensor.3d.global.shared::cta.bulk_group [%0, {%2, %3, %4}], [%1];\ncp.async.bulk.commit_group;"
                 :: "l"(tm), "r"(src), "r"(c0), "r"(c1), "r"(c2) : "memory");
}
__device__ __forceinline__ void l2_prefetch(const void* p, int bytes) {
    asm volatile("cp.async.bulk.prefetch.L2.global [%0], %1;" :: "l"(p), "r"(bytes) : "memory");
}
__device__ __forceinline__ void cluster_arrive() { asm volatile("barrier.cluster.arrive.relaxed.aligned;" ::: "memory"); }
__device__ __forceinline__ void cluster_wait() { asm volatile("barrier.cluster.wait.aligned;" ::: "memory"); }
__device__ __forceinline__ void bar_sync(int id, int n) { asm volatile("bar.sync %0, %1;" :: "r"(id), "r"(n) : "memory"); }
__device__ __forceinline__ void bar_arrive(int id, int n) { asm volatile("bar.arrive %0, %1;" :: "r"(id), "r"(n) : "memory"); }
__device__ __forceinline__ bool bar_or(int id, int n, bool v) {
    uint32_t r;
    asm volatile("{\n.reg .pred p, q;\nsetp.ne.u32 p, %3, 0;\nbar.red.or.pred q, %1, %2, p;\nselp.u32 %0, 1, 0, q;\n}"
                 : "=r"(r) : "r"(id), "r"(n), "r"((uint32_t)v) : "memory");
    return r != 0;
}
__device__ __forceinline__ void fence_proxy_async_smem() { asm volatile("fence.proxy.async.shared::cta;" ::: "memory"); }
__device__ __forceinline__ void stg128(void* p, uint32_t a, uint32_t b, uint32_t c, uint32_t d) {
    asm volatile("{\n.reg .b64 l, h;\n.reg .b128 q;\nmov.b64 l, {%1, %2};\nmov.b64 h, {%3, %4};\nmov.b128 q, {l, h};\n"
                 "st.relaxed.gpu.global.b128 [%0], q;\n}" :: "l"(p), "r"(a), "r"(b), "r"(c), "r"(d) : "memory");
}
__device__ __forceinline__ void ldg128(const void* p, uint32_t& a, uint32_t& b, uint32_t& c, uint32_t& d) {
    asm volatile("{\n.reg .b64 l, h;\n.reg .b128 q;\nld.relaxed.gpu.global.b128 q, [%4];\nmov.b128 {l, h}, q;\n"
                 "mov.b64 {%0, %1}, l;\nmov.b64 {%2, %3}, h;\n}" : "=r"(a), "=r"(b), "=r"(c), "=r"(d) : "l"(p) : "memory");
}
__device__ __forceinline__ void red4(void* p, float a, float b) {
    asm volatile("red.relaxed.gpu.global.add.v4.f32 [%0], {%1, %2, %3, %3};" :: "l"(p), "f"(a), "f"(b), "f"(1.0f) : "memory");
}
__device__ __forceinline__ void stg32(void* p, uint32_t a) {
    asm volatile("st.relaxed.gpu.global.u32 [%0], %1;" :: "l"(p), "r"(a) : "memory");
}
__device__ __forceinline__ uint2 ldg64(const void* p) {
    uint2 v;
    asm volatile("{\n.reg .b64 l;\nld.relaxed.gpu.global.b64 l, [%2];\nmov.b64 {%0, %1}, l;\n}" : "=r"(v.x), "=r"(v.y) : "l"(p) : "memory");
    return v;
}
__device__ __forceinline__ unsigned ldg32(const void* p) {
    unsigned v;
    asm volatile("ld.relaxed.gpu.global.u32 %0, [%1];" : "=r"(v) : "l"(p) : "memory");
    return v;
}
__device__ __forceinline__ void ldsm_x4(uint32_t (&r)[4], uint32_t a) {
    asm volatile("ldmatrix.sync.aligned.m8n8.x4.shared.b16 {%0,%1,%2,%3}, [%4];"
                 : "=r"(r[0]), "=r"(r[1]), "=r"(r[2]), "=r"(r[3]) : "r"(a));
}
__device__ __forceinline__ void ldsm_x4_t(uint32_t (&r)[4], uint32_t a) {
    asm volatile("ldmatrix.sync.aligned.m8n8.x4.trans.shared.b16 {%0,%1,%2,%3}, [%4];"
                 : "=r"(r[0]), "=r"(r[1]), "=r"(r[2]), "=r"(r[3]) : "r"(a));
}
__device__ __forceinline__ void stsm_x4(uint32_t a, const uint32_t (&r)[4]) {
    asm volatile("stmatrix.sync.aligned.m8n8.x4.shared.b16 [%0], {%1,%2,%3,%4};"
                 :: "r"(a), "r"(r[0]), "r"(r[1]), "r"(r[2]), "r"(r[3]));
}
__device__ __forceinline__ uint32_t movm(uint32_t a) {
    uint32_t d;
    asm("movmatrix.sync.aligned.m8n8.trans.b16 %0, %1;" : "=r"(d) : "r"(a));
    return d;
}
__device__ __forceinline__ void mma16816(float (&c)[4], uint32_t a0, uint32_t a1, uint32_t a2, uint32_t a3, uint32_t b0, uint32_t b1) {
    asm("mma.sync.aligned.m16n8k16.row.col.f32.bf16.bf16.f32 {%0,%1,%2,%3}, {%4,%5,%6,%7}, {%8,%9}, {%0,%1,%2,%3};"
        : "+f"(c[0]), "+f"(c[1]), "+f"(c[2]), "+f"(c[3]) : "r"(a0), "r"(a1), "r"(a2), "r"(a3), "r"(b0), "r"(b1));
}
__device__ __forceinline__ void mma1688(float (&c)[4], uint32_t a0, uint32_t a1, uint32_t b0) {
    asm("mma.sync.aligned.m16n8k8.row.col.f32.bf16.bf16.f32 {%0,%1,%2,%3}, {%4,%5}, {%6}, {%0,%1,%2,%3};"
        : "+f"(c[0]), "+f"(c[1]), "+f"(c[2]), "+f"(c[3]) : "r"(a0), "r"(a1), "r"(b0));
}
__device__ __forceinline__ void wgmma_fence() { asm volatile("wgmma.fence.sync.aligned;" ::: "memory"); }
__device__ __forceinline__ void wgmma_commit() { asm volatile("wgmma.commit_group.sync.aligned;" ::: "memory"); }
template <int N> __device__ __forceinline__ void wgmma_wait() { asm volatile("wgmma.wait_group.sync.aligned %0;" :: "n"(N) : "memory"); }
__device__ __forceinline__ uint64_t mk(uint32_t lo, uint32_t hi) { return (uint64_t)lo | ((uint64_t)hi << 32); }
constexpr uint32_t HI128 = (1024 >> 4) | (1u << 30), HI64 = (512 >> 4) | (2u << 30), HI32 = (256 >> 4) | (3u << 30);
__device__ __forceinline__ uint32_t pack_bf16(float lo, float hi) {
    uint32_t r;
    asm("cvt.rn.bf16x2.f32 %0, %1, %2;" : "=r"(r) : "f"(hi), "f"(lo));
    return r;
}
__device__ __forceinline__ float bflo(uint32_t u) { return __uint_as_float(u << 16); }
__device__ __forceinline__ float bfhi(uint32_t u) { return __uint_as_float(u & 0xFFFF0000u); }
__device__ __forceinline__ float bf16r(float v) { return __uint_as_float(pack_bf16(0.f, v)); }
__device__ __forceinline__ float ex2(float v) { float r; asm("ex2.approx.ftz.f32 %0, %1;" : "=f"(r) : "f"(v)); return r; }
__device__ __forceinline__ float rcp(float v) { float r; asm("rcp.approx.ftz.f32 %0, %1;" : "=f"(r) : "f"(v)); return r; }
__device__ __forceinline__ float sqrt_a(float v) { float r; asm("sqrt.approx.ftz.f32 %0, %1;" : "=f"(r) : "f"(v)); return r; }
__device__ __forceinline__ float tanh_a(float v) { float r; asm("tanh.approx.f32 %0, %1;" : "=f"(r) : "f"(v)); return r; }
constexpr float LOG2E = 1.4426950408889634f;
__device__ __forceinline__ float sigm(float v) { return rcp(1.0f + ex2(-LOG2E * v)); }
__device__ __forceinline__ uint4 lds128(uint32_t a) {
    uint4 v;
    asm volatile("ld.shared.v4.u32 {%0,%1,%2,%3}, [%4];" : "=r"(v.x), "=r"(v.y), "=r"(v.z), "=r"(v.w) : "r"(a));
    return v;
}
__device__ __forceinline__ float2 lds64f(uint32_t a) {
    float2 v;
    asm volatile("ld.shared.v2.f32 {%0,%1}, [%2];" : "=f"(v.x), "=f"(v.y) : "r"(a));
    return v;
}
__device__ __forceinline__ uint32_t lds32(uint32_t a) {
    uint32_t v;
    asm volatile("ld.shared.u32 %0, [%1];" : "=r"(v) : "r"(a));
    return v;
}
__device__ __forceinline__ void sts128(uint32_t a, uint32_t x, uint32_t y, uint32_t z, uint32_t w) {
    asm volatile("st.shared.v4.u32 [%0], {%1,%2,%3,%4};" :: "r"(a), "r"(x), "r"(y), "r"(z), "r"(w) : "memory");
}
__device__ __forceinline__ void sts64(uint32_t a, uint32_t x, uint32_t y) {
    asm volatile("st.shared.v2.u32 [%0], {%1,%2};" :: "r"(a), "r"(x), "r"(y) : "memory");
}
__device__ __forceinline__ void sts32(uint32_t a, uint32_t x) { asm volatile("st.shared.u32 [%0], %1;" :: "r"(a), "r"(x) : "memory"); }
__device__ __forceinline__ unsigned redux_max(unsigned v) {
    unsigned r;
    asm volatile("redux.sync.max.u32 %0, %1, 0xffffffff;" : "=r"(r) : "r"(v));
    return r;
}
__device__ __forceinline__ float shx(float v, int o) { return __shfl_xor_sync(0xffffffffu, v, o); }
__device__ __forceinline__ uint32_t U(float v) { return __float_as_uint(v); }
__device__ __forceinline__ float F(uint32_t v) { return __uint_as_float(v); }

__device__ __forceinline__ void wgmma_n192_lo(float (&d)[120], uint64_t da, uint64_t db, int scale_d) {
    asm volatile("{\n.reg .pred p;\nsetp.ne.b32 p, %98, 0;\n"
        "wgmma.mma_async.sync.aligned.m64n192k16.f32.bf16.bf16 "
        "{%0, %1, %2, %3, %4, %5, %6, %7, %8, %9, %10, %11, %12, %13, %14, %15, "
        "%16, %17, %18, %19, %20, %21, %22, %23, %24, %25, %26, %27, %28, %29, %30, %31, "
        "%32, %33, %34, %35, %36, %37, %38, %39, %40, %41, %42, %43, %44, %45, %46, %47, "
        "%48, %49, %50, %51, %52, %53, %54, %55, %56, %57, %58, %59, %60, %61, %62, %63, "
        "%64, %65, %66, %67, %68, %69, %70, %71, %72, %73, %74, %75, %76, %77, %78, %79, "
        "%80, %81, %82, %83, %84, %85, %86, %87, %88, %89, %90, %91, %92, %93, %94, %95}, "
        "%96, %97, p, 1, 1, 0, 1;\n}\n"
        : "+f"(d[0]), "+f"(d[1]), "+f"(d[2]), "+f"(d[3]), "+f"(d[4]), "+f"(d[5]), "+f"(d[6]), "+f"(d[7]),
          "+f"(d[8]), "+f"(d[9]), "+f"(d[10]), "+f"(d[11]), "+f"(d[12]), "+f"(d[13]), "+f"(d[14]), "+f"(d[15]),
          "+f"(d[16]), "+f"(d[17]), "+f"(d[18]), "+f"(d[19]), "+f"(d[20]), "+f"(d[21]), "+f"(d[22]), "+f"(d[23]),
          "+f"(d[24]), "+f"(d[25]), "+f"(d[26]), "+f"(d[27]), "+f"(d[28]), "+f"(d[29]), "+f"(d[30]), "+f"(d[31]),
          "+f"(d[32]), "+f"(d[33]), "+f"(d[34]), "+f"(d[35]), "+f"(d[36]), "+f"(d[37]), "+f"(d[38]), "+f"(d[39]),
          "+f"(d[40]), "+f"(d[41]), "+f"(d[42]), "+f"(d[43]), "+f"(d[44]), "+f"(d[45]), "+f"(d[46]), "+f"(d[47]),
          "+f"(d[48]), "+f"(d[49]), "+f"(d[50]), "+f"(d[51]), "+f"(d[52]), "+f"(d[53]), "+f"(d[54]), "+f"(d[55]),
          "+f"(d[56]), "+f"(d[57]), "+f"(d[58]), "+f"(d[59]), "+f"(d[60]), "+f"(d[61]), "+f"(d[62]), "+f"(d[63]),
          "+f"(d[64]), "+f"(d[65]), "+f"(d[66]), "+f"(d[67]), "+f"(d[68]), "+f"(d[69]), "+f"(d[70]), "+f"(d[71]),
          "+f"(d[72]), "+f"(d[73]), "+f"(d[74]), "+f"(d[75]), "+f"(d[76]), "+f"(d[77]), "+f"(d[78]), "+f"(d[79]),
          "+f"(d[80]), "+f"(d[81]), "+f"(d[82]), "+f"(d[83]), "+f"(d[84]), "+f"(d[85]), "+f"(d[86]), "+f"(d[87]),
          "+f"(d[88]), "+f"(d[89]), "+f"(d[90]), "+f"(d[91]), "+f"(d[92]), "+f"(d[93]), "+f"(d[94]), "+f"(d[95])
        : "l"(da), "l"(db), "r"(scale_d));
}
__device__ __forceinline__ void wgmma_n48_hi(float (&d)[120], uint64_t da, uint64_t db, int scale_d) {
    asm volatile("{\n.reg .pred p;\nsetp.ne.b32 p, %26, 0;\n"
        "wgmma.mma_async.sync.aligned.m64n48k16.f32.bf16.bf16 "
        "{%0, %1, %2, %3, %4, %5, %6, %7, %8, %9, %10, %11, %12, %13, %14, %15, "
        "%16, %17, %18, %19, %20, %21, %22, %23}, "
        "%24, %25, p, 1, 1, 0, 1;\n}\n"
        : "+f"(d[96]), "+f"(d[97]), "+f"(d[98]), "+f"(d[99]), "+f"(d[100]), "+f"(d[101]), "+f"(d[102]), "+f"(d[103]),
          "+f"(d[104]), "+f"(d[105]), "+f"(d[106]), "+f"(d[107]), "+f"(d[108]), "+f"(d[109]), "+f"(d[110]), "+f"(d[111]),
          "+f"(d[112]), "+f"(d[113]), "+f"(d[114]), "+f"(d[115]), "+f"(d[116]), "+f"(d[117]), "+f"(d[118]), "+f"(d[119])
        : "l"(da), "l"(db), "r"(scale_d));
}
__device__ __forceinline__ void wgmma_rs_n80(float (&d)[40], uint32_t a0, uint32_t a1, uint32_t a2, uint32_t a3, uint64_t db, int scale_d) {
    asm volatile("{\n.reg .pred p;\nsetp.ne.b32 p, %45, 0;\n"
        "wgmma.mma_async.sync.aligned.m64n80k16.f32.bf16.bf16 "
        "{%0, %1, %2, %3, %4, %5, %6, %7, %8, %9, %10, %11, %12, %13, %14, %15, "
        "%16, %17, %18, %19, %20, %21, %22, %23, %24, %25, %26, %27, %28, %29, %30, %31, "
        "%32, %33, %34, %35, %36, %37, %38, %39}, "
        "{%40, %41, %42, %43}, %44, p, 1, 1, 1;\n}\n"
        : "+f"(d[0]), "+f"(d[1]), "+f"(d[2]), "+f"(d[3]), "+f"(d[4]), "+f"(d[5]), "+f"(d[6]), "+f"(d[7]),
          "+f"(d[8]), "+f"(d[9]), "+f"(d[10]), "+f"(d[11]), "+f"(d[12]), "+f"(d[13]), "+f"(d[14]), "+f"(d[15]),
          "+f"(d[16]), "+f"(d[17]), "+f"(d[18]), "+f"(d[19]), "+f"(d[20]), "+f"(d[21]), "+f"(d[22]), "+f"(d[23]),
          "+f"(d[24]), "+f"(d[25]), "+f"(d[26]), "+f"(d[27]), "+f"(d[28]), "+f"(d[29]), "+f"(d[30]), "+f"(d[31]),
          "+f"(d[32]), "+f"(d[33]), "+f"(d[34]), "+f"(d[35]), "+f"(d[36]), "+f"(d[37]), "+f"(d[38]), "+f"(d[39])
        : "r"(a0), "r"(a1), "r"(a2), "r"(a3), "l"(db), "r"(scale_d));
}
__device__ __forceinline__ void wgmma_rs_n192_lo(float (&d)[120], uint32_t a0, uint32_t a1, uint32_t a2, uint32_t a3, uint64_t db, int scale_d) {
    asm volatile("{\n.reg .pred p;\nsetp.ne.b32 p, %101, 0;\n"
        "wgmma.mma_async.sync.aligned.m64n192k16.f32.bf16.bf16 "
        "{%0, %1, %2, %3, %4, %5, %6, %7, %8, %9, %10, %11, %12, %13, %14, %15, "
        "%16, %17, %18, %19, %20, %21, %22, %23, %24, %25, %26, %27, %28, %29, %30, %31, "
        "%32, %33, %34, %35, %36, %37, %38, %39, %40, %41, %42, %43, %44, %45, %46, %47, "
        "%48, %49, %50, %51, %52, %53, %54, %55, %56, %57, %58, %59, %60, %61, %62, %63, "
        "%64, %65, %66, %67, %68, %69, %70, %71, %72, %73, %74, %75, %76, %77, %78, %79, "
        "%80, %81, %82, %83, %84, %85, %86, %87, %88, %89, %90, %91, %92, %93, %94, %95}, "
        "{%96, %97, %98, %99}, %100, p, 1, 1, 1;\n}\n"
        : "+f"(d[0]), "+f"(d[1]), "+f"(d[2]), "+f"(d[3]), "+f"(d[4]), "+f"(d[5]), "+f"(d[6]), "+f"(d[7]),
          "+f"(d[8]), "+f"(d[9]), "+f"(d[10]), "+f"(d[11]), "+f"(d[12]), "+f"(d[13]), "+f"(d[14]), "+f"(d[15]),
          "+f"(d[16]), "+f"(d[17]), "+f"(d[18]), "+f"(d[19]), "+f"(d[20]), "+f"(d[21]), "+f"(d[22]), "+f"(d[23]),
          "+f"(d[24]), "+f"(d[25]), "+f"(d[26]), "+f"(d[27]), "+f"(d[28]), "+f"(d[29]), "+f"(d[30]), "+f"(d[31]),
          "+f"(d[32]), "+f"(d[33]), "+f"(d[34]), "+f"(d[35]), "+f"(d[36]), "+f"(d[37]), "+f"(d[38]), "+f"(d[39]),
          "+f"(d[40]), "+f"(d[41]), "+f"(d[42]), "+f"(d[43]), "+f"(d[44]), "+f"(d[45]), "+f"(d[46]), "+f"(d[47]),
          "+f"(d[48]), "+f"(d[49]), "+f"(d[50]), "+f"(d[51]), "+f"(d[52]), "+f"(d[53]), "+f"(d[54]), "+f"(d[55]),
          "+f"(d[56]), "+f"(d[57]), "+f"(d[58]), "+f"(d[59]), "+f"(d[60]), "+f"(d[61]), "+f"(d[62]), "+f"(d[63]),
          "+f"(d[64]), "+f"(d[65]), "+f"(d[66]), "+f"(d[67]), "+f"(d[68]), "+f"(d[69]), "+f"(d[70]), "+f"(d[71]),
          "+f"(d[72]), "+f"(d[73]), "+f"(d[74]), "+f"(d[75]), "+f"(d[76]), "+f"(d[77]), "+f"(d[78]), "+f"(d[79]),
          "+f"(d[80]), "+f"(d[81]), "+f"(d[82]), "+f"(d[83]), "+f"(d[84]), "+f"(d[85]), "+f"(d[86]), "+f"(d[87]),
          "+f"(d[88]), "+f"(d[89]), "+f"(d[90]), "+f"(d[91]), "+f"(d[92]), "+f"(d[93]), "+f"(d[94]), "+f"(d[95])
        : "r"(a0), "r"(a1), "r"(a2), "r"(a3), "l"(db), "r"(scale_d));
}
__device__ __forceinline__ void wgmma_rs_n48_hi(float (&d)[120], uint32_t a0, uint32_t a1, uint32_t a2, uint32_t a3, uint64_t db, int scale_d) {
    asm volatile("{\n.reg .pred p;\nsetp.ne.b32 p, %29, 0;\n"
        "wgmma.mma_async.sync.aligned.m64n48k16.f32.bf16.bf16 "
        "{%0, %1, %2, %3, %4, %5, %6, %7, %8, %9, %10, %11, %12, %13, %14, %15, "
        "%16, %17, %18, %19, %20, %21, %22, %23}, "
        "{%24, %25, %26, %27}, %28, p, 1, 1, 1;\n}\n"
        : "+f"(d[96]), "+f"(d[97]), "+f"(d[98]), "+f"(d[99]), "+f"(d[100]), "+f"(d[101]), "+f"(d[102]), "+f"(d[103]),
          "+f"(d[104]), "+f"(d[105]), "+f"(d[106]), "+f"(d[107]), "+f"(d[108]), "+f"(d[109]), "+f"(d[110]), "+f"(d[111]),
          "+f"(d[112]), "+f"(d[113]), "+f"(d[114]), "+f"(d[115]), "+f"(d[116]), "+f"(d[117]), "+f"(d[118]), "+f"(d[119])
        : "r"(a0), "r"(a1), "r"(a2), "r"(a3), "l"(db), "r"(scale_d));
}
__device__ __forceinline__ constexpr int jt_of(int sec, int c, bool odd) {
    return odd ? (c >= 2 ? sec * 8 + c - 2 : 24 + sec * 2 + c) : (c < 8 ? sec * 8 + c : 24 + sec * 2 + (c - 8));
}
#define BOTH(...) if (hg & 1) { constexpr bool odd = true; __VA_ARGS__ } else { constexpr bool odd = false; __VA_ARGS__ }

__device__ __forceinline__ bool elect() {
    uint32_t r;
    asm volatile("{\n.reg .pred p;\nelect.sync _|p, 0xffffffff;\nselp.u32 %0, 1, 0, p;\n}" : "=r"(r));
    return r != 0;
}
__device__ __forceinline__ uint32_t clock32() { uint32_t r; asm volatile("mov.u32 %0, %%clock;" : "=r"(r)); return r; }
#define BLOCK_SPLIT(v) asm volatile("{\n.reg .pred p;\nLAB_SPLIT:\nsetp.eq.u32 p, %0, 0;\n@p nanosleep.u32 1;\n@p bra LAB_SPLIT;\n}" :: "r"(v) : "memory")
__device__ __forceinline__ bool any(bool v) { return __any_sync(0xffffffffu, v); }
__device__ __forceinline__ uint32_t opaque_tid() { uint32_t r; asm volatile("mov.u32 %0, %%tid.x;" : "=r"(r)); return r; }

template <bool BY_SM>
__global__ void __cluster_dims__(2, 1, 1) __launch_bounds__(NTHREADS, 1)
fused_kernel(const __grid_constant__ Params P) {
    extern __shared__ __align__(1024) uint8_t smem[];
    const uint32_t sb = (uint32_t)__cvta_generic_to_shared(smem);
    const uint32_t warp = __shfl_sync(0xffffffffu, threadIdx.x >> 5, 0);
    const uint32_t rank = blockIdx.x & 1;
    constexpr uint32_t sbd = 1024 >> 4;
    const uint32_t t0 = clock32();
    if (warp >= 10 && elect()) {
        const uint32_t bb = sb + B_AX - 320 + warp * 32;
        const int cnt = warp < 12 ? 8 : (warp == 14 ? 16 : 1);
        mbar_init(bb, cnt); mbar_init(bb + 8, cnt); mbar_init(bb + 16, cnt); mbar_init(bb + 24, cnt);
        if (warp == 12) { mbar_expect_tx(sb + B_H, 1024); mbar_expect_tx(sb + B_GU, 40960); }
        if (warp == 13) mbar_expect_tx(sb + B_FULL + 16, ST);
        asm volatile("fence.mbarrier_init.release.cluster;" ::: "memory");
    }
    __syncwarp();
    cluster_arrive();
    if (warp < 3 && elect()) asm volatile("prefetch.tensormap [%0];" :: "l"(&P.tm[warp]) : "memory");
    if (warp - 3 < 2 && blockIdx.x < 128 && elect()) l2_prefetch(P.w + ((warp - 3) * 5 * 245760 + blockIdx.x * 1920), 1920);
    if ((sb & 0xFFFFFF) != 1024) __trap();
    uint32_t gpc = blockIdx.x >> 4, pos = (blockIdx.x >> 1) & 7;
    if (BY_SM) {
        uint32_t tpc;
        asm("mov.u32 %0, %%smid;" : "=r"(tpc));
        tpc >>= 1;
        if (tpc - 60 < 2) {
            __nanosleep(2000);
            return;
        }
        const uint32_t q = ((tpc - 32) * 37) >> 8;
        gpc = tpc < 32 ? tpc & 7 : (tpc < 60 ? tpc - 31 - 7 * q : 0);
        pos = tpc < 32 ? tpc >> 3 : (tpc < 60 ? 4 + q : tpc - 58);
    }
    const uint32_t hg = (0x62740351u >> (4 * pos)) & 7, rb = gpc * 2 + rank, fp = 8 * pos + gpc - 10;
    const uint32_t b = rb * 8 + hg;
    const uint32_t k0 = (((hg >> 2) ^ (rb >> 1)) & 1) * 320;

    if (warp == 13 && elect()) tma(sb + 2 * ST, &P.tm[T_X], sb + B_FULL + 16, k0, rb * 64);
    if (warp == 12) {
        cluster_wait();
        if (elect()) {
            tma_mc(sb + 2 * ST + ST_BM + rank * 12288, &P.tm[T_W], sb + B_FULL + 16, hg * 80 + (hg & 1) * 16, k0 + rank * 32);
            tma_mc(sb + 2 * ST + ST_BR + rank * 3072, &P.tm[T_WR], sb + B_FULL + 16, hg * 80 + 64 - (hg & 1) * 64, k0 + rank * 32);
        }
        __syncwarp();
    }

    if (warp < 8) {
        asm volatile("setmaxnreg.inc.sync.aligned.u32 208;");
        const uint32_t lane = opaque_tid() & 31, g = lane >> 2, t = lane & 3;
        const uint32_t p = warp >> 2, w = warp & 3;
        const uint32_t empty_cl = mapa(sb + B_EMPTY, lane & 1);
        uint8_t* const orow = P.scr + (rb * (8 * XB) + warp * 2560 + lane * 16);
        const uint32_t ta = sb + warp * 2560 + (lane & 15) * 160 + (lane >> 4) * 16;
        uint32_t A[5][20];
        uint32_t xr[5][4], gf[5][4];
        uint32_t par;
        uint8_t* const halo = orow + (hg * XB + (8 + p - warp) * 2560);
        uint8_t* const flag = P.scr + (G_FLAG + b * XB + w * 8 + p * 4);
        cluster_wait();
        {
            float acc[120];
            bool ok, prep, rel = false;
            float2 s0, s1;
            uint32_t xa[5], cap[2] = {0u, 0u};
#pragma unroll
            for (uint32_t j = 0; j < 5; j++) {
                const uint32_t cg = 5 * hg + (j < 4 ? j + (hg & 1) : (~hg & 1) * 4);
                xa[j] = (sb + (warp * 16 + (lane & 15)) * 128 + (((lane >> 4) ^ (lane & 7)) << 4)) ^ ((cg & 3) << 5);
                const uint32_t i = cg >> 2, late = (i >= 5) ^ (k0 != 0), bit = 1u << (5 * (i >= 5 ? i - 5 : i) + j);
                cap[0] |= late ? 0u : bit; cap[1] |= late ? bit : 0u;
            }
            uint32_t sta = sb + M_ST + (warp * 16 + g) * 8;
            asm volatile("" : "+r"(sta), "+r"(cap[0]), "+r"(cap[1]), "+r"(xa[0]), "+r"(xa[1]), "+r"(xa[2]), "+r"(xa[3]), "+r"(xa[4]));
            mbar_wait(sb + B_FULL + 16, 0);
#pragma unroll
            for (uint32_t kb = 2; kb < 12; kb++) {
                const uint32_t s = kb & 3;
                const bool hold = kb == 12 - LEAD && p;
                if (hold) {
                    wgmma_wait<0>();
                    if (lane < 2) mbar_arrive_cl(empty_cl + 8 * ((11 - LEAD) & 3));
                    bar_sync(1, 256);
                }
                if (kb == 13 - LEAD && p) bar_sync(7, 256);
                wgmma_fence();
                const uint32_t st = sbd + s * (ST >> 4);
#pragma unroll
                for (int ks = 0; ks < 4; ks++) {
                    const uint64_t da = mk(st + p * 512 + ks * 2 + 0x10000, HI128);
                    wgmma_n48_hi(acc, da, mk(st + (ST_BR >> 4) + (ks >> 1) * 192 + (ks & 1) * 32 + (64 << 16), HI32), ks || kb > 2);
                    wgmma_n192_lo(acc, da, mk(st + (ST_BM >> 4) + (ks >> 1) * 768 + (ks & 1) * 128 + (256 << 16), HI128), ks || kb > 2);
                    if (ks == 0) {
                        wgmma_commit();
                        wgmma_wait<1>();
                        if (!hold && kb > 2 && lane < 2) mbar_arrive_cl(empty_cl + 8 * ((kb - 1) & 3));
                    }
                    if (ks == 1) {
#pragma unroll
                        for (uint32_t j = 0; j < 5; j++)
                            if ((cap[kb >= 7] >> (5 * ((kb - 2) % 5) + j)) & 1) ldsm_x4(xr[j], xa[j] + s * ST);
                        if (w == 3 && kb < 7) stg128(halo + (kb - 2) * 512, 0u, 0u, 0u, 0u);
                        if (lane == 0 && kb == 2) stg32(flag, 0u);
                        if (kb < 11) ok = mbar_try(sb + B_FULL + 8 * ((kb + 1) & 3), ((kb - 1) >> 2) & 1);
                        if (kb == 10) prep = mbar_try(sb + B_PREP, 0);
                        if (kb == 11 && prep) {
                            s0 = lds64f(sta); s1 = lds64f(sta + 64);
                            par = lds32(sb + M_SEL + 8);
                        }
                    }
                }
                wgmma_commit();
                if (kb < 11 && !ok) {
                    if (kb >= 12 - LEAD && !p && !rel && !mbar_try(sb + B_FULL + 8 * ((kb + 1) & 3), ((kb - 1) >> 2) & 1)) { rel = true; bar_arrive(1, 256); }
                    mbar_wait(sb + B_FULL + 8 * ((kb + 1) & 3), ((kb - 1) >> 2) & 1);
                }
            }
            if (!prep) {
                mbar_wait(sb + B_PREP, 0);
                s0 = lds64f(sta); s1 = lds64f(sta + 64);
                par = lds32(sb + M_SEL + 8);
            }
            {
                const uint32_t a0 = t ? 0u : __byte_perm(U(-s0.y), 0, 0x3232), a1 = t ? 0u : __byte_perm(U(-s1.y), 0, 0x3232);
                wgmma_fence();
                wgmma_rs_n48_hi(acc, a0, a1, 0u, 0u, mk(sbd + (M_CS >> 4) + 48, 2), 1);
                wgmma_rs_n192_lo(acc, a0, a1, 0u, 0u, mk(sbd + (M_CS >> 4), 2), 1);
                wgmma_commit();
            }
            if (!p) { if (!rel) bar_arrive(1, 256); bar_arrive(7, 256); }
            wgmma_wait<1>();
            if (lane < 2) mbar_arrive_cl(empty_cl + 24);
            wgmma_wait<0>();
#pragma unroll
            for (int i = 0; i < 120; i++) asm volatile("" : "+f"(acc[i]) :: "memory");
            uint32_t Q[10], Ql[10], KX[10], VX[10], Y[20];
#define KI(c) ((c) == 2 ? 8 : (c) == 7 ? 9 : (c) - ((c) > 2) - ((c) > 7))
#define KY(c) Y[KI(c)]
#define VY(c) Y[10 + (c)]
            uint32_t Z[20];
            const bool start = w == 0 && rb == 0, remote = w == 0 && rb != 0;
            const uint32_t slot = sb + OFF_HO + p * 8192 + w * 2560 - 2560 + lane * 16;
            {
                BOTH(_Pragma("unroll") for (int c = 0; c < 10; c++) {
                    const int jk = jt_of(1, c, odd), jv = jt_of(2, c, odd);
                    VY(c) = movm(pack_bf16(acc[4 * jv + 2] * s1.x, acc[4 * jv + 3] * s1.x));
                    KY(c) = pack_bf16(acc[4 * jk + 2] * s1.x, acc[4 * jk + 3] * s1.x);
                    asm volatile("" : "+r"(KY(c)), "+r"(VY(c)));
                })
                if (w == 3) {
#pragma unroll
                    for (int j = 0; j < 5; j++) {
                        Y[4 * j] = (Y[4 * j] & ~0x10001u) | par;
                        stg128(halo + j * 512, Y[4 * j], Y[4 * j + 1], Y[4 * j + 2], Y[4 * j + 3]);
                    }
                } else {
#pragma unroll
                    for (int j = 0; j < 5; j++) sts128(slot + 2560 + j * 512, Y[4 * j], Y[4 * j + 1], Y[4 * j + 2], Y[4 * j + 3]);
                }
                BOTH(_Pragma("unroll") for (int c = 0; c < 10; c++) {
                    const int jk = jt_of(1, c, odd), jv = jt_of(2, c, odd);
                    KX[c] = pack_bf16(acc[4 * jk] * s0.x, acc[4 * jk + 1] * s0.x);
                    VX[c] = movm(pack_bf16(acc[4 * jv] * s0.x, acc[4 * jv + 1] * s0.x));
                    asm volatile("" : "+r"(KX[c]), "+r"(VX[c]));
                })
                bar_sync(2 + p, 128);
                if (remote) {
#pragma unroll
                    for (int j = 0; j < 5; j++) ldg128(halo - 8 * XB + j * 512, Z[4 * j], Z[4 * j + 1], Z[4 * j + 2], Z[4 * j + 3]);
                } else {
#pragma unroll
                    for (int j = 0; j < 5; j++) {
                        const uint4 v = lds128(slot + (w ? 0 : 2560) + j * 512);
                        Z[4 * j] = v.x; Z[4 * j + 1] = v.y; Z[4 * j + 2] = v.z; Z[4 * j + 3] = v.w;
                    }
                }
                BOTH(_Pragma("unroll") for (int c = 0; c < 10; c++) {
                    const int jq = jt_of(0, c, odd);
                    Ql[c] = pack_bf16(acc[4 * jq], acc[4 * jq + 1]);
                    Q[c] = pack_bf16(acc[4 * jq + 2], acc[4 * jq + 3]);
                    asm volatile("" : "+r"(Ql[c]), "+r"(Q[c]));
                })
            }
            auto scores = [&](float (&l)[4], const uint32_t (&q)[10], const uint32_t (&z)[20], const int c0, const uint32_t mx, const float nz) {
                const uint32_t qa = t < 2 ? q[c0 + 2] : 0u, qb = t < 2 ? 0u : q[c0 + 2];
                float xa[4] = {0.f, 0.f, 0.f, 0.f}, za[4] = {nz, nz, nz, nz}, xb[4], zb[4];
                mma1688(xa, qa, qb, KX[c0 + 2]);
                mma1688(za, qa, qb, z[KI(c0 + 2)]);
#pragma unroll
                for (int e = 0; e < 4; e++) { xb[e] = xa[e]; zb[e] = za[e]; }
                mma16816(xa, q[c0], q[c0 + 3], q[c0 + 1], q[c0 + 4], KX[c0], KX[c0 + 1]);
                mma16816(za, q[c0], q[c0 + 3], q[c0 + 1], q[c0 + 4], z[KI(c0)], z[KI(c0 + 1)]);
                mma16816(xb, q[c0], q[c0 + 3], q[c0 + 1], q[c0 + 4], KX[c0 + 3], KX[c0 + 4]);
                mma16816(zb, q[c0], q[c0 + 3], q[c0 + 1], q[c0 + 4], z[KI(c0 + 3)], z[KI(c0 + 4)]);
                const bool h0 = mx & 1u, h1 = (int)mx < 0;
                l[0] = h0 ? xa[0] : za[0]; l[1] = h1 ? xa[1] : za[1];
                l[2] = h0 ? xb[2] : zb[2]; l[3] = h1 ? xb[3] : zb[3];
                asm volatile("" : "+f"(l[0]), "+f"(l[1]), "+f"(l[2]), "+f"(l[3]));
            };
            auto soft = [&](uint32_t (&pr)[2], const float (&l)[4], const float sq) {
                float m0 = fmaxf(l[0], l[1]), m1 = fmaxf(l[2], l[3]);
                m0 = fmaxf(m0, shx(m0, 1)); m1 = fmaxf(m1, shx(m1, 1));
                m0 = fmaxf(m0, shx(m0, 2)) * -sq; m1 = fmaxf(m1, shx(m1, 2)) * -sq;
                pr[0] = pack_bf16(ex2(fmaf(l[0], sq, m0)), ex2(fmaf(l[1], sq, m0)));
                pr[1] = pack_bf16(ex2(fmaf(l[2], sq, m1)), ex2(fmaf(l[3], sq, m1)));
                asm volatile("" : "+r"(pr[0]), "+r"(pr[1]));
            };
            auto values = [&](const uint32_t (&pr)[2], const uint32_t (&z)[20], const int c0, const uint32_t mx, const int h) {
                float dn[4] = {0.f, 0.f, 0.f, 0.f};
                mma1688(dn, pr[0], pr[1], 0x3F803F80u);
                const float i0 = rcp(dn[0]), i1 = rcp(dn[2]), i2 = t < 2 ? i0 : i1;
#pragma unroll
                for (int c = 0; c < 5; c++) {
                    float oc[4] = {0.f, 0.f, 0.f, 0.f};
                    mma16816(oc, pr[0] & mx, pr[1] & mx, pr[0] & ~mx, pr[1] & ~mx, VX[c0 + c], z[10 + c0 + c]);
                    const bool first = c < 2 || (c == 2 && t < 2);
                    const float iv = c < 2 ? i0 : (c > 2 ? i1 : i2);
                    A[0][2 * (c0 + c) + h] = pack_bf16((first ? oc[0] : oc[2]) * iv, (first ? oc[1] : oc[3]) * iv);
                    asm volatile("" : "+r"(A[0][2 * (c0 + c) + h]));
                }
            };
            auto gate = [&]() {
                const float r0 = 0.5f * s0.x, r1 = 0.5f * s1.x, n0 = -r0 * s0.y, n1 = -r1 * s1.y;
#pragma unroll
                for (int j = 0; j < 5; j++) {
#pragma unroll
                    for (int q = 0; q < 4; q++) {
                        const float v0 = fmaf(bflo(xr[j][q]), q & 1 ? r1 : r0, q & 1 ? n1 : n0), v1 = fmaf(bfhi(xr[j][q]), q & 1 ? r1 : r0, q & 1 ? n1 : n0);
                        gf[j][q] = pack_bf16(fmaf(v0, tanh_a(v0), v0), fmaf(v1, tanh_a(v1), v1));
                        asm volatile("" : "+r"(gf[j][q]));
                    }
                }
            };
            const uint32_t mo = (2 * t > g ? 0xFFFFu : 0u) | (2 * t + 1 > g ? 0xFFFF0000u : 0u);
            constexpr float SC = 0.22360679774997896f * LOG2E;
            {
                float l[4][4];
                uint32_t pr[4][2];
                unsigned spins = 0;
#pragma unroll 1
                while (remote && any((Z[0] & Z[4] & Z[8] & Z[12] & Z[16] & par) == 0u) && ++spins < SPIN) {
#pragma unroll
                    for (int j = 0; j < 5; j++) ldg128(halo - 8 * XB + j * 512, Z[4 * j], Z[4 * j + 1], Z[4 * j + 2], Z[4 * j + 3]);
                }
                const float nz = start ? -INFINITY : 0.f;
                auto publish = [&](const int j) {
                    A[0][4 * j] = (A[0][4 * j] & ~0x10001u) | par;
                    stg128(orow + hg * XB + j * 512, A[0][4 * j], A[0][4 * j + 1], A[0][4 * j + 2], A[0][4 * j + 3]);
                };
                scores(l[0], Q, Y, 0, mo, 0.f);
                scores(l[2], Ql, Z, 0, ~mo, nz);
                scores(l[1], Q, Y, 5, mo, 0.f);
                scores(l[3], Ql, Z, 5, ~mo, nz);
                soft(pr[0], l[0], s1.x * SC);
                soft(pr[2], l[2], s0.x * SC);
                soft(pr[1], l[1], s1.x * SC);
                soft(pr[3], l[3], s0.x * SC);
                values(pr[0], Y, 0, mo, 1);
                values(pr[2], Z, 0, ~mo, 0);
                publish(0);
                if (lane == 0 && !p) stg32(flag, par);
                publish(1);
                values(pr[1], Y, 5, mo, 1);
                values(pr[3], Z, 5, ~mo, 0);
                publish(2); publish(3); publish(4);
            }
            if (lane == 0 && p) stg32(flag, par);
            if (p) bar_arrive(8, 384);
            BLOCK_SPLIT(par);
            gate();
        }
        {
            float acc2[40];
            unsigned spins = 0;
            bool again, first = true;
            const uint8_t* src[7];
#pragma unroll
            for (uint32_t i = 0; i < 7; i++) { src[i] = orow + (i >= hg ? XB : 0u); asm volatile("" : "+l"(src[i])); }
            mbar_wait(sb + B_SEL, 0);
            const float2 sel = lds64f(sb + M_SEL);
            uint32_t routed = (U(sel.x) >> 4) == warp || (U(sel.y) >> 4) == warp;
            asm volatile("" : "+r"(routed));
            BLOCK_SPLIT(par);
            if (p) bar_sync(9, 288); else bar_sync(5, 160);
#pragma unroll 1
            do {
#pragma unroll
                for (uint32_t i = 1; i < 5; i++)
#pragma unroll
                    for (int j = 0; j < 5; j++)
                        ldg128(src[i - 1] + (i - 1) * XB + j * 512, A[i][4 * j], A[i][4 * j + 1], A[i][4 * j + 2], A[i][4 * j + 3]);
                if (!p && first) bar_sync(8, 384);
                uint32_t mn = par;
#pragma unroll
                for (int i = 0; i < 8; i++) {
                    const uint32_t (&a)[20] = A[i % 5];
                    if (i == 4 && !p && first) bar_sync(6, 160);
                    wgmma_fence();
#pragma unroll
                    for (int j = 0; j < 5; j++) {
                        wgmma_rs_n80(acc2, a[4 * j], a[4 * j + 1], a[4 * j + 2], a[4 * j + 3],
                                     mk(sbd + (wo_slot(i) >> 4) + j * 64 + (320 << 16), HI64), i || j);
                        if (i == 7 && j == 2) {
#pragma unroll
                            for (int q = 0; q < 5; q++) mn &= A[q][0] & A[q][4] & A[q][8] & A[q][12] & A[q][16];
                            again = bar_or(2 + p, 128, mn == 0u && ++spins < SPIN);
                        }
                    }
                    if (i < 4 || i == 7) wgmma_commit();
                    if (i == SERAT && !p && first) bar_arrive(9, 288);
                    if (i >= 1 && i < 4) {
                        uint32_t (&n)[20] = A[i - 1];
                        if (i > 1) mn &= n[0] & n[4] & n[8] & n[12] & n[16];
                        const uint8_t* q = src[i + 3] + (i > 1 ? mn & 256u : 0u);
                        wgmma_wait<1>();
                        bar_arrive(10, 32);
#pragma unroll
                        for (int j = 0; j < 5; j++) ldg128(q + (i + 3) * XB + j * 512, n[4 * j], n[4 * j + 1], n[4 * j + 2], n[4 * j + 3]);
                        bar_arrive(10, 32);
                    }
                }
                first = false;
                if (again) {
                    wgmma_wait<0>();
#pragma unroll
                    for (int j = 0; j < 5; j++)
                        ldg128(orow + hg * XB + j * 512, A[0][4 * j], A[0][4 * j + 1], A[0][4 * j + 2], A[0][4 * j + 3]);
                }
            } while (again);
            const uint32_t o0 = (hg & 1) * 32, o4 = (~hg & 1) * 128;
            if (routed) {
                const float2 sel = lds64f(sb + M_SEL);
                mbar_wait(sb + B_UPD, 0);
#pragma unroll
                for (uint32_t h = 0; h < 2; h++) {
                    const uint32_t row = warp * 16 + g + 8 * h, ga = sb + M_UPD + (row == U(sel.x) ? 0 : 160) + t * 4;
                    if (row == U(sel.x) || row == U(sel.y)) {
#pragma unroll
                        for (int c = 0; c < 5; c++) { gf[c][h] = lds32(ga + (c < 4 ? o0 + c * 32 : o4)); gf[c][h + 2] = lds32(ga + (c < 4 ? o0 + c * 32 : o4) + 16); }
                    }
                }
                __syncwarp();
            }
            wgmma_wait<0>();
#pragma unroll
            for (int i = 0; i < 40; i++) asm volatile("" : "+f"(acc2[i]) :: "memory");
#pragma unroll
            for (int c = 0; c < 5; c++) {
#pragma unroll
                for (int q = 0; q < 4; q++)
                    asm("fma.rn.bf16x2 %0, %1, %2, %0;" : "+r"(xr[c][q]) : "r"(pack_bf16(acc2[8 * c + 2 * q], acc2[8 * c + 2 * q + 1])), "r"(gf[c][q]));
                stsm_x4(ta + (c < 4 ? o0 + c * 32 : o4) + OFF_DN, xr[c]);
            }
            fence_proxy_async_smem();
            __syncwarp();
            if (lane == 0) {
                tma_st(&P.tm[T_OUT], sb + OFF_DN + warp * 2560, hg * 80, rb * 64 + 16 * w, p);
                asm volatile("cp.async.bulk.wait_group.read 0;" ::: "memory");
            }
        }
    } else if (warp >= 12) {
        asm volatile("setmaxnreg.dec.sync.aligned.u32 24;");
        if (warp == 12) {
            uint32_t slot = t0 + PACE0;
            if (elect()) {
#pragma unroll 1
                for (uint32_t kb = 1; kb < 10; kb++) {
                    const uint32_t s = (kb + 2) & 3;
                    const uint32_t st = sb + s * ST, fb = sb + B_FULL + 8 * s;
                    const uint32_t kc = kb * 64 + (kb < 5 ? k0 : -k0);
                    if (kb >= 4) {
                        mbar_wait(fb + 32, kb >> 3);
                        if (kb < 9) mbar_wait(sb + B_AX - 32 + 8 * kb, 0);
                    }
                    {
                        slot += PACE1;
#pragma unroll 1
                        while ((int)(clock32() - slot) < 0) { }
                        mbar_expect_tx(fb, ST);
                        tma(st, &P.tm[T_X], fb, kc, rb * 64);
                    }
                    tma_mc(st + ST_BM + rank * 12288, &P.tm[T_W], fb, hg * 80 + (hg & 1) * 16, kc + rank * 32);
                    tma_mc(st + ST_BR + rank * 3072, &P.tm[T_WR], fb, hg * 80 + 64 - (hg & 1) * 64, kc + rank * 32);
                }
                uint32_t wb = sb + B_WO - 8;
#pragma unroll 1
                for (uint32_t i = 0; i < 8; i++) {
                    if ((0x93 >> i) & 1) {
                        wb += 8;
                        mbar_wait(wb - (B_WO - B_EMPTY), i < 2);
                        mbar_expect_tx(wb, (i + 1) & 6 ? 3 * 12800 : 12800);
                    }
                    if (i == 0) {
                        mbar_expect_tx(sb + B_DN, 20480);
                        tma(sb + OFF_DN, &P.tm[T_D], sb + B_DN, 0, 32 * fp, 5 * rank);
                    }
                    if (WOP) {
#pragma unroll 1
                        while ((int)(clock32() - slot) < 0) { }
                        slot = clock32() + WOP;
                    }
                    const uint32_t d = sb + wo_slot(i);
                    const uint32_t kr = 80 * (i ? i - (i <= hg) : hg);
                    tma_mc(d + rank * 5120, &P.tm[T_WO], wb, hg * 80 + (hg & 1) * 16 + rank * 32, kr);
                    tma_mc(d + 10240 + rank * 2560, &P.tm[T_WOR], wb, hg * 80 + (~hg & 1) * 64, kr + rank * 40);
                }
            }
        } else if (warp == 13) {
            if (elect()) {
#pragma unroll 1
                for (uint32_t i = 0; i < 3; i++) {
#pragma unroll 1
                    while (clock32() - t0 < PX0 + i * PX1) __nanosleep(20);
                    l2_prefetch(P.w + ((i + 2) * 245760 + b * 1920), 1920);
                    l2_prefetch(P.w + ((i + 7) * 245760 + b * 1920), 1920);
                }
#pragma unroll 1
                for (uint32_t i = 0; i < 14; i++) {
#pragma unroll 1
                    while (clock32() - t0 < GU0 + i * GU1) __nanosleep(20);
                    if (i < 10) l2_prefetch(P.wd + (i * 128 + b) * 1728, 1728);
                    else l2_prefetch(P.wo + ((i - 10) * 128 + b) * 1600, 1600);
                }
            }
        } else if (warp == 15) {
            const uint32_t lane = opaque_tid() & 31;
            const uint8_t* fl = P.scr + (G_FLAG + (rb * 8 + (lane & 7)) * XB + (lane >> 3) * 8);
            cluster_wait();
            mbar_wait(sb + B_PREP, 0);
            const uint32_t par = lds32(sb + M_SEL + 8);
            mbar_wait(sb + B_WO, 0); mbar_wait(sb + B_WO + 8, 0);
            mbar_wait(sb + B_EMPTY + 24, 0);
            __nanosleep(WSL);
            unsigned spins = 0;
            uint2 f;
#pragma unroll 1
            do f = ldg64(fl); while (any(f.x != par) && ++spins < SPIN);
            bar_arrive(5, 160);
            mbar_wait(sb + B_WO + 16, 0); mbar_wait(sb + B_WO + 24, 0);
            bar_arrive(6, 160);
#pragma unroll 1
            while (any(f.y != par) && ++spins < SPIN) f.y = ldg32(fl + 4);
            bar_arrive(9, 288);
        } else {
            uint32_t slot = t0 + GT0;
            cluster_wait();
            if (elect()) {
#pragma unroll 1
                for (uint32_t i = 0; i < 20; i++) {
                    slot += GT1;
#pragma unroll 1
                    while ((int)(clock32() - slot) < 0) __nanosleep(20);
                    tma(sb + OFF_GU + i * 2048, &P.tm[T_GU], sb + B_GU, 32 * fp, rank * 320 + i * 16);
                }
            }
        }
    } else {
        asm volatile("setmaxnreg.dec.sync.aligned.u32 72;");
        const uint32_t at = opaque_tid() - 256, lane = at & 31, g = lane >> 2, t = lane & 3, c7 = lane & 7, aw = warp - 8;
        uint8_t* const yz = P.scr + (G_Y + b * 512 + at * 4);
        stg32(yz, 0u);
        __nanosleep(AUXS);
        const uint32_t epoch = ldg32(P.scr + G_EPOCH) + 1 + ldg32(yz), tag = (epoch & 15u) | 16u;
        const uint32_t empty_cl = mapa(sb + B_EMPTY, lane & 1);
        unsigned spins = 0;
        {
            const uint2 wv = __ldg(reinterpret_cast<const uint2*>(P.w_r + k0 * 2 + min(at, 79u) * 8));
            if (at < 80) sts64(sb + M_UPD + at * 8, wv.x, wv.y);
        }
        uint8_t* const stw = P.scr + (b * XB + G_ST + (lane & 4) * 64 + (at >> 3) * 16);
        uint8_t* const csw = P.scr + (b * XB + G_CS + at);
        uint8_t* const tpw = P.scr + (G_TOP + (hg >> 2) * XB + rb * 64 + aw * 16);
        const bool tpub = lane == 0 && (hg & 3) == 3;
        cluster_wait();
        bar_sync(4, 128);
        mbar_wait(sb + B_FULL + 16, 0);
        if (t == 0) { stg128(stw, 0u, 0u, 0u, 0u); stg32(csw, 0u); }
        if (tpub) stg128(tpw, 0u, 0u, 0u, 0u);

        uint32_t k1, sv;
        {
            const uint32_t xoff = (32 * (hg & 3) + (at >> 3)) * 128 + ((c7 ^ ((at >> 3) & 7)) << 4);
            const uint32_t jt = (rb >> 2) * 8 + rank * 4 + aw;
            const uint32_t coff = jt < 24 ? ST_BM + (jt >> 3) * 4096 + lane * 128 + (((jt ^ lane) & 7) << 4)
                                          : ST_BR + ((jt >> 1) & 3) * 1024 + lane * 32 + (((jt ^ g) & 1) << 4);
            float q[8], c8[8];
#pragma unroll
            for (int e = 0; e < 8; e++) q[e] = c8[e] = 0.f;
#pragma unroll 1
            for (uint32_t kb = 2; kb < 7; kb++) {
                const uint32_t st = sb + (kb & 3) * ST;
                const uint4 wv = lds128(sb + M_UPD - 256 + kb * 128 + c7 * 16);
                mbar_wait(sb + B_FULL + 8 * (kb & 3), kb == 6);
                const uint4 v = lds128(st + xoff), vn = lds128(st + xoff + 2048);
                const uint4 cv = lds128(st + coff), cn = lds128(st + coff + (jt < 24 ? 12288 : 3072));
                if (lane < 2) mbar_arrive_cl(empty_cl - (B_EMPTY + 16 - B_AX) + 8 * kb);
                const uint32_t u[4] = {v.x, v.y, v.z, v.w}, un[4] = {vn.x, vn.y, vn.z, vn.w}, ww[4] = {wv.x, wv.y, wv.z, wv.w};
                const uint32_t cc[4] = {cv.x, cv.y, cv.z, cv.w}, cd[4] = {cn.x, cn.y, cn.z, cn.w};
#pragma unroll
                for (int e = 0; e < 4; e++) {
                    const float a0 = bflo(u[e]), a1 = bfhi(u[e]), b0 = bflo(un[e]), b1 = bfhi(un[e]), w0 = bflo(ww[e]), w1 = bfhi(ww[e]);
                    q[0] += a0 + a1; q[4] += b0 + b1; q[3] += w0 + w1;
                    q[1] = fmaf(a0, a0, fmaf(a1, a1, q[1])); q[5] = fmaf(b0, b0, fmaf(b1, b1, q[5]));
                    q[2] = fmaf(a0, w0, fmaf(a1, w1, q[2])); q[6] = fmaf(b0, w0, fmaf(b1, w1, q[6]));
                    c8[2 * e] += bflo(cc[e]) + bflo(cd[e]); c8[2 * e + 1] += bfhi(cc[e]) + bfhi(cd[e]);
                }
            }
            q[7] = q[3];
#pragma unroll
            for (int e = 0; e < 4; e++) {
                q[e] = ((lane & 4) ? q[e + 4] : q[e]) + shx((lane & 4) ? q[e] : q[e + 4], 4);
                q[e] += shx(q[e], 1); q[e] += shx(q[e], 2);
            }
            const float mh = q[0] * (1.0f / 320);
            if (t == 0) stg128(stw, U(mh), U(fmaf(-mh, q[0], q[1])), U(q[2]), (U(q[3]) & ~31u) | tag);
#define TSTEP(H) { const bool up = (lane & (4 * H)) != 0; _Pragma("unroll") for (int e = 0; e < H; e++) { \
            const float send = up ? c8[e] : c8[e + H]; const float keep = up ? c8[e + H] : c8[e]; \
            c8[e] = keep + shx(send, 4 * H); } }
            TSTEP(4) TSTEP(2) TSTEP(1)
#undef TSTEP
            c8[0] += shx(c8[0], 1); c8[0] += shx(c8[0], 2);
            if (t == 0) stg32(csw, (U(c8[0]) & ~31u) | tag);
            const uint8_t* csp = P.scr + (G_CS + (aw * 32 + (lane >> 4) * 8 + hg) * XB + (lane & 15) * 8);
            const uint8_t* stp = P.scr + (G_ST + (rb * 8 + aw) * XB + lane * 16);
            uint32_t ra[4], rc[4];
            uint2 ca, cc;
#pragma unroll 1
            while (clock32() - t0 < EX1T) __nanosleep(20);
#pragma unroll 1
            do {
                ldg128(stp, ra[0], ra[1], ra[2], ra[3]);
                ldg128(stp + 4 * XB, rc[0], rc[1], rc[2], rc[3]);
                ca = ldg64(csp); cc = ldg64(csp + 16 * XB);
            } while (any((ra[3] ^ tag | rc[3] ^ tag) & 31u) && ++spins < SPIN);
            const float dm = 0.5f * (F(ra[0]) - F(rc[0])), m = bf16r(F(rc[0]) + dm);
            const float sd = bf16r(sqrt_a(bf16r(bf16r(fmaxf(fmaf(dm, dm, (F(ra[1]) + F(rc[1])) * (1.0f / DM)), 0.f)) + 1e-5f)));
            const float rs = rcp(sd);
            uint32_t w1, w2;
            if ((hg & 3) == 3) {
                k1 = pack_bf16(0.f, fmaf(-m, F(ra[3]) + F(rc[3]), F(ra[2]) + F(rc[2])) * rs);
                k1 ^= ((int)k1 >> 31) | 0x80000000u;
                k1 = (k1 & 0xFFFF0000u) | ((2047 - (rb * 128 + 2 * (at & 63) + (at >> 6))) << 5) | tag;
                w1 = redux_max(k1); w2 = redux_max(k1 == w1 ? 0u : k1);
                sv = U(m) | (U(sd) >> 16);
                const uint32_t v1 = redux_max(k1 == w1 ? sv : 0u), v2 = redux_max(k1 == w2 ? sv : 0u);
                if (lane == 0) stg128(tpw, w1, v1, w2, v2);
            }
            sts64(sb + M_ST + at * 8, U(rs), U(m));
            sts32(sb + M_SEL + 8, (tag & 1) ? 1u : 0x10000u);
#pragma unroll 1
            while (any((ca.x ^ tag | ca.y ^ tag | cc.x ^ tag | cc.y ^ tag) & 31u) && ++spins < SPIN) { ca = ldg64(csp); cc = ldg64(csp + 16 * XB); }
            {
                const float c0 = at < 120 ? F(ca.x) + F(cc.x) : 0.f, c1 = at < 120 ? F(ca.y) + F(cc.y) : 0.f;
                const uint32_t hi = pack_bf16(c0, c1);
                sts32(sb + M_CS + (at >> 2) * 32 + t * 4, hi);
                sts32(sb + M_CS + (at >> 2) * 32 + t * 4 + 16, pack_bf16(c0 - bflo(hi), c1 - bfhi(hi)));
                fence_proxy_async_smem();
                __syncwarp();
                if (lane < 2) mbar_arrive(sb + B_PREP);
            }
            if (aw == 0) {
                uint32_t ka[4], kb[4];
#pragma unroll 1
                while (clock32() - t0 < EX1T + EX2D) __nanosleep(20);
#pragma unroll 1
                do {
                    const uint8_t* tp = P.scr + (G_TOP + lane * 16);
                    uint32_t kc[4], kd[4];
                    ldg128(tp, ka[0], ka[1], ka[2], ka[3]);
                    ldg128(tp + 512, kb[0], kb[1], kb[2], kb[3]);
                    ldg128(tp + XB, kc[0], kc[1], kc[2], kc[3]);
                    ldg128(tp + XB + 512, kd[0], kd[1], kd[2], kd[3]);
                    const bool ba = (ka[0] ^ tag) & 31u, bb = (kb[0] ^ tag) & 31u;
#pragma unroll
                    for (int e = 0; e < 4; e++) { ka[e] = ba ? kc[e] : ka[e]; kb[e] = bb ? kd[e] : kb[e]; }
                } while (any((ka[0] ^ tag | kb[0] ^ tag) & 31u) && ++spins < SPIN);
                if (kb[0] > ka[0]) {
#pragma unroll
                    for (int e = 0; e < 4; e++) { const uint32_t x = ka[e]; ka[e] = kb[e]; kb[e] = x; }
                }
                if (kb[0] > ka[2]) { ka[2] = kb[0]; ka[3] = kb[1]; }
                w1 = redux_max(ka[0]);
                const uint32_t t1 = redux_max(ka[0] == w1 ? ka[1] : 0u);
                if (ka[0] == w1) { ka[0] = ka[2]; ka[1] = ka[3]; }
                w2 = redux_max(ka[0]);
                const uint32_t t3 = redux_max(ka[0] == w2 ? ka[1] : 0u);
                sts128(sb + M_TOP, w1, t1, w2, t3);
            }
            bar_sync(4, 128);
            const float2 tv = lds64f(sb + M_TOP + (lane & 1) * 8);
            k1 = U(tv.x);
            sv = U(tv.y);
        }
        const uint32_t tok = ~(k1 >> 5) & 2047;
        const unsigned owns = __ballot_sync(0xffffffffu, (tok >> 7) == rb) & 3u;
        if (at < 2) sts32(sb + M_SEL + at * 4, (tok >> 7) == rb ? (tok & 1) * 64 + ((tok & 127) >> 1) : ~0u);
        if ((at | b) == 0) *reinterpret_cast<uint32_t*>(P.scr + G_EPOCH) = epoch;
        __syncwarp();
        if (at == 0) mbar_arrive(sb + B_SEL);
        if (fp < NFFN / 2) {
            uint4 xv = __ldg(reinterpret_cast<const uint4*>(P.x + (tok * 1280 + rank * 640 + min(at >> 1, 39u) * 16)));
            const uint32_t m2 = __byte_perm(sv, 0, 0x3232);
            asm("sub.rn.bf16x2 %0, %0, %4;\nsub.rn.bf16x2 %1, %1, %4;\nsub.rn.bf16x2 %2, %2, %4;\nsub.rn.bf16x2 %3, %3, %4;"
                : "+r"(xv.x), "+r"(xv.y), "+r"(xv.z), "+r"(xv.w) : "r"(m2));
            mbar_wait(sb + B_DN, 0);
            if (at < 80) sts128(sb + OFF_PART + at * 16, xv.x, xv.y, xv.z, xv.w);
            mbar_wait(sb + B_GU, 0);
            mbar_wait(sb + B_EMPTY + 24, 0);
            bar_sync(4, 128);
            float c[5][4];
            uint32_t wf[10][4];
#pragma unroll
            for (int i = 0; i < 5; i++) c[i][0] = c[i][1] = c[i][2] = c[i][3] = 0.f;
            const uint32_t mi = lane >> 3, kr = c7 + (mi >> 1) * 8;
            {
                const uint32_t wa = sb + OFF_GU + (aw >> 1) * 1024 + kr * 64 + ((((aw & 1) * 2 + (mi & 1)) ^ ((kr >> 1) & 3)) << 4);
#pragma unroll
                for (uint32_t i = 0; i < NPRE; i++) ldsm_x4_t(wf[i], wa + i * 2048);
                __nanosleep(FFNS);
                BLOCK_SPLIT(tag);
#pragma unroll
                for (uint32_t i = 0; i < 20; i += 2) {
                    uint32_t xb[4];
                    ldsm_x4(xb, sb + OFF_PART + i * 64 + mi * 32 + (lane & 1) * 16);
#pragma unroll
                    for (uint32_t j = i; j < i + 2; j++) {
                        const uint32_t (&a)[4] = wf[j % NPRE];
                        mma16816(c[j & 1], a[0], a[1], a[2], a[3], xb[2 * (j & 1)], xb[2 * (j & 1) + 1]);
                        if (j + NPRE < 20) ldsm_x4_t(wf[j % NPRE], wa + (j + NPRE) * 2048);
                    }
                }
#pragma unroll
                for (int e = 0; e < 4; e++) c[0][e] += c[1][e];
                const uint32_t rd = mapa(sb, rank ^ (t & 1));
                if (t < 2)
                    asm volatile("st.async.shared::cluster.mbarrier::complete_tx::bytes.v4.f32 [%0], {%1,%2,%3,%4}, [%5];"
                                 :: "r"(rd + (t ? OFF_PART + 1280 : M_UPD + 192) + aw * 128 + g * 16), "f"(c[0][0]), "f"(c[0][1]), "f"(c[0][2]), "f"(c[0][3]), "r"(rd + B_H) : "memory");
            }
            const float rs = rcp(bflo(sv));
            const uint32_t da = sb + OFF_DN + kr * 128 + (((2 * aw + (mi & 1)) ^ c7) << 4);
            uint8_t* yp = P.scr + (G_Y + (fp % 6) * 10240 + rank * 2560 + t * 512 + aw * 128 + g * 16);
#pragma unroll
            for (int i = 0; i < 5; i++) c[i][0] = c[i][1] = c[i][2] = c[i][3] = 0.f;
#pragma unroll
            for (uint32_t j = 0; j < NPD; j++) ldsm_x4_t(wf[j], da + (j % 5) * 4096 + (j / 5) * 2048);
            mbar_wait(sb + B_H, 0);
#pragma unroll
            for (uint32_t ks = 0; ks < 2; ks++) {
                const uint32_t og = sb + ks * 128 + lane * 4 + P.up_first, ou = og ^ 256;
                const float gs = bf16r((F(lds32(og + M_UPD + 192)) + F(lds32(og + OFF_PART + 1280))) * rs);
                const float h = bf16r(gs * sigm(gs)) * bf16r((F(lds32(ou + M_UPD + 192)) + F(lds32(ou + OFF_PART + 1280))) * rs);
                const uint32_t hp = pack_bf16(h, __shfl_down_sync(0xffffffffu, h, 4));
                const uint32_t h0 = __shfl_sync(0xffffffffu, hp, t * 8 + (g & 1)), h1 = __shfl_sync(0xffffffffu, hp, t * 8 + (g & 1) + 2);
#pragma unroll
                for (uint32_t j = 0; j < 5; j++) {
                    uint32_t (&a)[4] = wf[ks * 5 + j];
                    if (ks * 5 + j >= NPD) ldsm_x4_t(a, da + j * 4096 + ks * 2048);
                    mma16816(c[j], a[0], a[1], a[2], a[3], h0, h1);
                }
            }
#pragma unroll
            for (int e = 0; e < 4; e++) {
                const float lo = (t & 1) ? c[1][e] : c[0][e], hi = (t & 1) ? c[3][e] : c[2][e];
                c[0][e] = (t & 2) ? hi : lo;
            }
            asm volatile("" : "+f"(c[0][0]), "+f"(c[4][0]) :: "memory");
            BLOCK_SPLIT(tag);
            bar_sync(8, 384);
            { red4(yp, c[0][0], c[0][2]); red4(yp + 5120, c[0][1], c[0][3]); }
            if (t == 0) { red4(yp + 2048, c[4][0], c[4][2]); red4(yp + 2048 + 5120, c[4][1], c[4][3]); }
        }
        else {
            mbar_wait(sb + B_DN, 0); mbar_wait(sb + B_GU, 0);
            bar_arrive(8, 384);
        }
        if (owns) {
            const uint32_t u = min(at >> 1, 39u), col = (u >> 3) * 32 + (u & 7) * 2;
            const bool mine = (tok >> 7) == rb && at < 80;
            k1 ^= ((~(int)k1) >> 31) | 0x80000000u;
            const float sg = bf16r(sigm(bfhi(k1))), rs = rcp(bflo(sv));
            uint32_t x0, x1, y0, y1, n0, n1;
            asm volatile("ld.global.nc.u16 %0, [%2];\nld.global.nc.u16 %1, [%2 + 16];" : "=r"(x0), "=r"(x1) : "l"(P.x + (tok * 1280 + hg * 160 + col)));
            const float a0 = (bflo(x0) - bfhi(sv)) * rs, a1 = (bflo(x1) - bfhi(sv)) * rs;
            bar_sync(4, 128);
#pragma unroll 1
            do {
                __nanosleep(YSL);
                uint32_t v[6][4];
#pragma unroll
                for (int r = 0; r < 6; r++) if (mine) ldg128(P.scr + (G_Y + (at & 1) * 5120 + hg * 640 + u * 16) + r * 10240, v[r][0], v[r][1], v[r][2], v[r][3]);
                y0 = U(((F(v[0][0]) + F(v[1][0])) + (F(v[2][0]) + F(v[3][0]))) + (F(v[4][0]) + F(v[5][0])));
                y1 = U(((F(v[0][1]) + F(v[1][1])) + (F(v[2][1]) + F(v[3][1]))) + (F(v[4][1]) + F(v[5][1])));
                n0 = U(((F(v[0][2]) + F(v[1][2])) + (F(v[2][2]) + F(v[3][2]))) + (F(v[4][2]) + F(v[5][2])));
                n1 = U(((F(v[0][3]) + F(v[1][3])) + (F(v[2][3]) + F(v[3][3]))) + (F(v[4][3]) + F(v[5][3])));
            } while (any(mine && (F(n0) != NFFN / 2 || F(n1) != NFFN / 2)) && ++spins < SPIN);
            const float v0 = a0 + bf16r(bf16r(F(y0)) * sg), v1 = a1 + bf16r(bf16r(F(y1)) * sg);
            const uint32_t gp = pack_bf16(v0 * sigm(v0), v1 * sigm(v1));
            if (mine) asm volatile("st.shared.u16 [%0], %1;\nst.shared.u16 [%0 + 16], %2;" :: "r"(sb + M_UPD + (at & 1) * 160 + col), "r"(gp), "r"(gp >> 16) : "memory");
            __syncwarp();
            if (lane < 2) mbar_arrive(sb + B_UPD);
        }
    }
}

typedef CUresult (*EncodeFn)(CUtensorMap*, CUtensorMapDataType, cuuint32_t, void*, const cuuint64_t*, const cuuint64_t*,
                             const cuuint32_t*, const cuuint32_t*, CUtensorMapInterleave, CUtensorMapSwizzle,
                             CUtensorMapL2promotion, CUtensorMapFloatOOBfill);

bool encode(EncodeFn fn, CUtensorMap* tm, const void* ptr, cuuint64_t d0, cuuint64_t d1, cuuint64_t d2, cuuint64_t s1, cuuint64_t s2,
            cuuint32_t b0, cuuint32_t b1, cuuint32_t b2, CUtensorMapSwizzle sw) {
    const cuuint64_t dims[3] = {d0, d1, d2}, strides[2] = {s1, s2};
    const cuuint32_t box[3] = {b0, b1, b2}, es[3] = {1, 1, 1};
    return fn(tm, CU_TENSOR_MAP_DATA_TYPE_BFLOAT16, 3, const_cast<void*>(ptr), dims, strides, box, es,
              CU_TENSOR_MAP_INTERLEAVE_NONE, sw, CU_TENSOR_MAP_L2_PROMOTION_L2_128B,
              CU_TENSOR_MAP_FLOAT_OOB_FILL_NONE) == CUDA_SUCCESS;
}

}

extern "C" void kernel_launch(void* const* d_in, const int* in_sizes, int n_in, void* d_out, int out_size) {
    static Params P;
    static bool by_sm = false;
    static const void* cached[9] = {};
    bool same = cached[8] == d_out;
    for (int i = 0; i < 8; i++) same = same && cached[i] == d_in[i];
    if (!same) {
        const void *x = d_in[0], *wqkv = d_in[1], *wo = d_in[2], *wg = d_in[5], *wu = d_in[6], *wd = d_in[7];
        void* fnp = nullptr;
        cudaDriverEntryPointQueryResult qr;
        cudaGetDriverEntryPoint("cuTensorMapEncodeTiled", &fnp, cudaEnableDefault, &qr);
        EncodeFn fn = (EncodeFn)fnp;
        const CUtensorMapSwizzle S0 = CU_TENSOR_MAP_SWIZZLE_NONE, S32 = CU_TENSOR_MAP_SWIZZLE_32B, S64 = CU_TENSOR_MAP_SWIZZLE_64B,
                                 S128 = CU_TENSOR_MAP_SWIZZLE_128B;
        const bool ok = fn != nullptr &&
            encode(fn, &P.tm[T_X], x, 640, 1024, 2, 2560, 1280, 64, 64, 2, S128) &&
            encode(fn, &P.tm[T_OUT], d_out, 640, 1024, 2, 2560, 1280, 80, 16, 1, S0) &&
            encode(fn, &P.tm[T_W], wqkv, 640, 640, 3, 3840, 1280, 64, 32, 3, S128) &&
            encode(fn, &P.tm[T_WR], wqkv, 640, 640, 3, 3840, 1280, 16, 32, 3, S32) &&
            encode(fn, &P.tm[T_GU], wg < wu ? wg : wu, 1728, 640, 2, 3456, wg < wu ? (const char*)wu - (const char*)wg : (const char*)wg - (const char*)wu,
                   32, 16, 2, S64) &&
            encode(fn, &P.tm[T_D], wd, 64, 1728, 10, 1280, 128, 64, 32, 5, S128) &&
            encode(fn, &P.tm[T_WO], wo, 640, 640, 1, 1280, 1280 * 640, 32, 80, 1, S64) &&
            encode(fn, &P.tm[T_WOR], wo, 640, 640, 1, 1280, 1280 * 640, 16, 40, 1, S64);
        if (!ok) return;
        P.up_first = wg < wu ? 0 : 256;
        P.wo = (const uint8_t*)wo; P.wd = (const uint8_t*)wd;
        P.x = (const uint8_t*)x; P.w = (const uint8_t*)wqkv; P.w_r = (const uint8_t*)d_in[4];
        if (cudaGetSymbolAddress((void**)&P.scr, g_scr) != cudaSuccess) return;
        cudaFuncSetAttribute(fused_kernel<true>, cudaFuncAttributeMaxDynamicSharedMemorySize, SMEM_BYTES);
        cudaFuncSetAttribute(fused_kernel<false>, cudaFuncAttributeMaxDynamicSharedMemorySize, SMEM_BYTES);
        int ncl = 0, sms = 0, dev = 0;
        {
            cudaLaunchConfig_t cfg = {};
            cfg.gridDim = dim3(128); cfg.blockDim = dim3(NTHREADS); cfg.dynamicSmemBytes = SMEM_BYTES;
            cudaLaunchAttribute at[1];
            at[0].id = cudaLaunchAttributeClusterDimension;
            at[0].val.clusterDim.x = 2; at[0].val.clusterDim.y = 1; at[0].val.clusterDim.z = 1;
            cfg.attrs = at; cfg.numAttrs = 1;
            if (cudaOccupancyMaxActiveClusters(&ncl, fused_kernel<true>, &cfg) != cudaSuccess || ncl < 64) return;
            cudaGetDevice(&dev);
            cudaDeviceGetAttribute(&sms, cudaDevAttrMultiProcessorCount, dev);
        }
        by_sm = sms == 132 && ncl == 66;
        for (int i = 0; i < 8; i++) cached[i] = d_in[i];
        cached[8] = d_out;
    }
    if (by_sm) fused_kernel<true><<<132, NTHREADS, SMEM_BYTES>>>(P);
    else fused_kernel<false><<<128, NTHREADS, SMEM_BYTES>>>(P);
}
```
